```python
import torch

def _softmax(x, axis=-1):
    return torch.softmax(x, dim=axis)
def _gelu(x):
    return torch.nn.functional.gelu(x, approximate="tanh")
def _silu(x):
    return torch.nn.functional.silu(x)
def _sigmoid(x):
    return torch.sigmoid(x)
def _layernorm(x, axis=-1, eps=1e-5):
    m = x.mean(dim=axis, keepdim=True)
    v = x.var(dim=axis, keepdim=True, unbiased=False)
    return (x - m) / torch.sqrt(v + eps)
def _scatter_add(tgt, idx, src, axis=0):
    return tgt.clone().index_add_(axis, idx, src)
def _segment_sum(src, seg, n):
    out = torch.zeros((n,) + src.shape[1:], dtype=src.dtype)
    return out.index_add_(0, seg, src)
def _pad(x, pw):
    flat = tuple(v for pair in reversed(pw) for v in pair)
    return torch.nn.functional.pad(x, flat)

kernel_name = 'standalone__convnext_block__vision'

def setup_inputs():

    _w = (lambda a: (lambda t: t.to(torch.bfloat16) if t.is_floating_point() else t)(torch.as_tensor(a)))
    H = W = 512
    C = 96
    return {
        "x": _w((lambda *s: torch.randn(*s, dtype=torch.bfloat16) * 0.05)(1, H, W, C)),
        "dw": _w((lambda *s: torch.randn(*s, dtype=torch.bfloat16) * 0.05)(7, 7, C)),
        "w1": _w((lambda *s: torch.randn(*s, dtype=torch.bfloat16) * 0.05)(C, 4 * C)),
        "w2": _w((lambda *s: torch.randn(*s, dtype=torch.bfloat16) * 0.05)(4 * C, C)),
    }

def reference(x, dw, w1, w2):
    B, H, W, C = x.shape
    pad = 3
    xp = _pad(x, ((0,0),(pad,pad),(pad,pad),(0,0)))
    out = torch.zeros_like(x)
    for i in range(7):
        for j in range(7):
            out = out + xp[:, i:i+H, j:j+W, :] * dw[i, j][None, None, None, :]
    h = _layernorm(out, axis=-1)
    return x + _gelu(h @ w1) @ w2
```

```cpp
#include <cuda_runtime.h>
#include <cuda_bf16.h>
#include <cuda.h>
#include <stdint.h>

namespace {

constexpr int IMG = 512, CH = 96;
constexpr int NSTEP = 67;
constexpr int SIGMA = 5;
constexpr int NGATED = NSTEP - SIGMA;

constexpr uint32_t OFF_W1 = 0;
constexpr uint32_t OFF_W2 = 73728;
constexpr uint32_t OFF_RAW = 147456;
constexpr uint32_t RAW_BYTES = 2 * 38 * 96;
constexpr uint32_t OFF_XRES = OFF_RAW + 4 * RAW_BYTES;
constexpr uint32_t OFF_C = OFF_XRES + 12288;
constexpr uint32_t C_BYTES = 12416;
constexpr uint32_t OFF_PLAN = OFF_C + 2 * C_BYTES;
constexpr uint32_t PLAN_PITCH = 176;
constexpr uint32_t PLAN_BYTES = 48 * PLAN_PITCH;
constexpr uint32_t OFF_BAR = OFF_PLAN + 2 * PLAN_BYTES;
constexpr uint32_t BAR_RAW = OFF_BAR;
constexpr uint32_t BAR_CFULL = OFF_BAR + 32;
constexpr uint32_t BAR_CEMPTY = OFF_BAR + 48;
constexpr uint32_t BAR_XFULL = OFF_BAR + 80;
constexpr uint32_t OFF_MAX = OFF_BAR + 144;
constexpr uint32_t SMEM_BYTES = OFF_BAR + 160;

constexpr float GELU_A = 0.32918364f;
constexpr uint32_t GELU_K2 = 0x40d940d9u;

constexpr int NB_OPEN = 1, NB_CLOSE = 2, NB_PLAN = 3, NB_PREP = 4;

#define WG_FENCE() asm volatile("wgmma.fence.sync.aligned;" ::: "memory")
#define WG_COMMIT() asm volatile("wgmma.commit_group.sync.aligned;" ::: "memory")
#define WG_WAIT0() asm volatile("wgmma.wait_group.sync.aligned 0;" ::: "memory")
#define NB_SYNC(id, n) asm volatile("bar.sync %0, %1;" ::"n"(id), "n"(n) : "memory")
#define NB_ARRIVE(id, n) asm volatile("bar.arrive %0, %1;" ::"n"(id), "n"(n) : "memory")

#define R24(c, d)                                                                                        \
  c(d[0]), c(d[1]), c(d[2]), c(d[3]), c(d[4]), c(d[5]), c(d[6]), c(d[7]), c(d[8]), c(d[9]), c(d[10]),    \
      c(d[11]), c(d[12]), c(d[13]), c(d[14]), c(d[15]), c(d[16]), c(d[17]), c(d[18]), c(d[19]), c(d[20]), \
      c(d[21]), c(d[22]), c(d[23])
#define WG_TXT(sd)                                                                             \
  "wgmma.mma_async.sync.aligned.m64n96k16.f16.f16.f16 "                                        \
  "{%0,%1,%2,%3,%4,%5,%6,%7,%8,%9,%10,%11,%12,%13,%14,%15,%16,%17,%18,%19,%20,%21,%22,%23}, " \
  "{%24,%25,%26,%27}, %28, " sd ", 1, 1, 1;\n"

__device__ __forceinline__ void wg_acc(uint32_t (&d)[24], const uint32_t* a, uint64_t db) {
  asm volatile(WG_TXT("1") : R24("+r", d) : "r"(a[0]), "r"(a[1]), "r"(a[2]), "r"(a[3]), "l"(db));
}
__device__ __forceinline__ void wg_init(uint32_t (&d)[24], const uint32_t* a, uint64_t db) {
  asm volatile(WG_TXT("0") : R24("=r", d) : "r"(a[0]), "r"(a[1]), "r"(a[2]), "r"(a[3]), "l"(db));
}
template <int N>
__device__ __forceinline__ void rfence(uint32_t (&d)[N]) {
#pragma unroll
  for (int i = 0; i < N; i++) asm volatile("" : "+r"(d[i])::"memory");
}
template <bool INIT>
__device__ __forceinline__ void gemm6(uint32_t (&d)[24], const uint32_t (&a)[24], uint64_t db) {
#pragma unroll
  for (int k = 0; k < 6; k++) {
    if (INIT && k == 0) wg_init(d, &a[0], db);
    else wg_acc(d, &a[4 * k], db + k * 192);
  }
  WG_COMMIT();
}

__device__ __forceinline__ void mbar_init(uint32_t bar, uint32_t cnt) {
  asm volatile("mbarrier.init.shared::cta.b64 [%0], %1;" ::"r"(bar), "r"(cnt) : "memory");
}
__device__ __forceinline__ void mbar_expect(uint32_t bar, uint32_t bytes) {
  asm volatile("mbarrier.arrive.expect_tx.shared::cta.b64 _, [%0], %1;" ::"r"(bar), "r"(bytes) : "memory");
}
__device__ __forceinline__ void mbar_arrive_cluster(uint32_t bar) {
  asm volatile("mbarrier.arrive.shared::cluster.b64 _, [%0];" ::"r"(bar) : "memory");
}
__device__ __forceinline__ void mbar_wait(uint32_t bar, uint32_t parity) {
  uint32_t ok, n = 0;
  do {
    asm volatile(
        "{\n.reg .pred p;\nmbarrier.try_wait.parity.shared::cta.b64 p, [%1], %2;\nselp.u32 %0, 1, 0, p;\n}\n"
        : "=r"(ok)
        : "r"(bar), "r"(parity)
        : "memory");
    if (++n > (1u << 22)) __trap();
  } while (!ok);
}
__device__ __forceinline__ uint32_t mapa(uint32_t addr, uint32_t rank) {
  uint32_t r;
  asm("mapa.shared::cluster.u32 %0, %1, %2;" : "=r"(r) : "r"(addr), "r"(rank));
  return r;
}
__device__ __forceinline__ void tma_raw(uint32_t dst, const CUtensorMap* tm, int c, int w, int h, uint32_t bar) {
  asm volatile(
      "cp.async.bulk.tensor.3d.shared::cluster.global.mbarrier::complete_tx::bytes [%0], [%1, {%2, %3, %4}], [%5];"
      ::"r"(dst), "l"(tm), "r"(c), "r"(w), "r"(h), "r"(bar)
      : "memory");
}
__device__ __forceinline__ void bulk_load(uint32_t dst, const void* src, uint32_t bytes, uint32_t bar) {
  asm volatile("cp.async.bulk.shared::cluster.global.mbarrier::complete_tx::bytes [%0], [%1], %2, [%3];" ::"r"(dst),
               "l"(src), "r"(bytes), "r"(bar)
               : "memory");
}
__device__ __forceinline__ uint32_t pack_bf16(float lo, float hi) {
  uint32_t r;
  asm("cvt.rn.bf16x2.f32 %0, %1, %2;" : "=r"(r) : "f"(hi), "f"(lo));
  return r;
}
__device__ __forceinline__ uint32_t pack_f16(float lo, float hi) {
  uint32_t r;
  asm("cvt.rn.f16x2.f32 %0, %1, %2;" : "=r"(r) : "f"(hi), "f"(lo));
  return r;
}
__device__ __forceinline__ float bf_lo(uint32_t v) { return __uint_as_float(v << 16); }
__device__ __forceinline__ float bf_hi(uint32_t v) { return __uint_as_float(v & 0xffff0000u); }
__device__ __forceinline__ uint32_t bf_add(uint32_t a, uint32_t b) {
  uint32_t r;
  asm("add.rn.bf16x2 %0, %1, %2;" : "=r"(r) : "r"(a), "r"(b));
  return r;
}
__device__ __forceinline__ uint32_t bf_mul(uint32_t a, uint32_t b) {
  uint32_t r;
  asm("mul.rn.bf16x2 %0, %1, %2;" : "=r"(r) : "r"(a), "r"(b));
  return r;
}
__device__ __forceinline__ uint32_t bf_fma(uint32_t a, uint32_t b, uint32_t c) {
  uint32_t r;
  asm("fma.rn.bf16x2 %0, %1, %2, %3;" : "=r"(r) : "r"(a), "r"(b), "r"(c));
  return r;
}

template <int LO, int HI>
__device__ __forceinline__ void gelu(uint32_t (&o)[24], const uint32_t (&d)[24]) {
#pragma unroll
  for (int q = LO; q < HI; q++) {
    uint32_t t, u;
    asm("fma.rn.f16x2 %0, %1, %1, %2;" : "=r"(t) : "r"(d[q]), "r"(GELU_K2));
    asm("mul.rn.f16x2 %0, %1, %2;" : "=r"(u) : "r"(d[q]), "r"(t));
    asm("tanh.approx.f16x2 %0, %1;" : "=r"(t) : "r"(u));
    asm("fma.rn.f16x2 %0, %1, %2, %1;" : "=r"(o[q]) : "r"(d[q]), "r"(t));
  }
}

struct MlpCtx {
  uint32_t sb;
  uint32_t caddr;
  uint32_t xaddr;
  uint32_t unscale;
  uint32_t peer_off;
  int wg, warp, lane, rank;
  const uint8_t* xsrc;
  uint8_t* optr;
};

__device__ __forceinline__ void layernorm(const MlpCtx& m, uint32_t (&a)[24], int i) {
  mbar_wait(m.sb + BAR_CFULL + 8 * m.wg, i & 1);
  uint32_t c[24];
#pragma unroll
  for (int p = 0; p < 12; p++)
    asm volatile("ld.shared.v2.b32 {%0,%1}, [%2];" : "=r"(c[2 * p]), "=r"(c[2 * p + 1]) : "r"(m.caddr + p * 256) : "memory");
  float mean[2];
#pragma unroll
  for (int r = 0; r < 2; r++) {
    uint32_t s0 = bf_add(c[r], c[r + 2]), s1 = bf_add(c[r + 4], c[r + 6]), s2 = bf_add(c[r + 8], c[r + 10]);
    uint32_t s3 = bf_add(c[r + 12], c[r + 14]), s4 = bf_add(c[r + 16], c[r + 18]), s5 = bf_add(c[r + 20], c[r + 22]);
    s0 = bf_add(s0, s1); s2 = bf_add(s2, s3); s4 = bf_add(s4, s5);
    s0 = bf_add(bf_add(s0, s2), s4);
    mean[r] = bf_lo(s0) + bf_hi(s0);
  }
  __syncwarp();
  if (m.lane == 0) {
    if (m.warp == 0) mbar_expect(m.sb + BAR_CFULL + 8 * m.wg, 12288);
    uint32_t e = m.sb + BAR_CEMPTY + 8 * (2 * m.rank + m.wg);
    mbar_arrive_cluster(e);
    mbar_arrive_cluster(e + m.peer_off);
  }
#pragma unroll
  for (int r = 0; r < 2; r++) {
    mean[r] += __shfl_xor_sync(0xffffffffu, mean[r], 1);
    mean[r] += __shfl_xor_sync(0xffffffffu, mean[r], 2);
  }
  float var[2];
#pragma unroll
  for (int r = 0; r < 2; r++) {
    float nm = mean[r] * (-1.0f / 96.0f);
    uint32_t nm2 = pack_bf16(nm, nm);
#pragma unroll
    for (int p = 0; p < 12; p++) c[2 * p + r] = bf_add(c[2 * p + r], nm2);
    uint32_t q0 = bf_mul(c[r], c[r]), q1 = bf_mul(c[r + 2], c[r + 2]), q2 = bf_mul(c[r + 4], c[r + 4]);
#pragma unroll
    for (int p = 3; p < 12; p += 3) {
      q0 = bf_fma(c[2 * p + r], c[2 * p + r], q0);
      q1 = bf_fma(c[2 * p + 2 + r], c[2 * p + 2 + r], q1);
      q2 = bf_fma(c[2 * p + 4 + r], c[2 * p + 4 + r], q2);
    }
    q0 = bf_add(bf_add(q0, q1), q2);
    var[r] = bf_lo(q0) + bf_hi(q0);
  }
#pragma unroll
  for (int r = 0; r < 2; r++) {
    var[r] += __shfl_xor_sync(0xffffffffu, var[r], 1);
    var[r] += __shfl_xor_sync(0xffffffffu, var[r], 2);
  }
  float rs[2];
#pragma unroll
  for (int r = 0; r < 2; r++) rs[r] = rsqrtf(fmaf(var[r], 1.0f / 96.0f, 1e-5f)) * GELU_A;
  if (__builtin_expect(fminf(rs[0], rs[1]) < 0x1p-13f, 0)) {
#pragma unroll
    for (int r = 0; r < 2; r++) {
      uint32_t e = __float_as_uint(rs[r]) & 0x7f800000u;
      uint32_t e2 = (e >> 16) | e;
#pragma unroll
      for (int p = 0; p < 12; p++) c[2 * p + r] = bf_mul(c[2 * p + r], e2);
      rs[r] = __uint_as_float((__float_as_uint(rs[r]) & 0x007fffffu) | 0x3f800000u);
    }
  }
#pragma unroll
  for (int r = 0; r < 2; r++) {
    float rr = rs[r] * 0x1p-112f;
    uint32_t r2 = pack_bf16(rr, rr);
#pragma unroll
    for (int p = 0; p < 12; p++) {
      uint32_t v = bf_mul(c[2 * p + r], r2);
      a[2 * p + r] = (v & 0x7fff7fffu) * 7u + v;
    }
  }
}

__device__ __forceinline__ void issue_xres(const MlpCtx& m, int u, int wg_dst) {
  if (m.lane == 0) {
    uint32_t bar = m.sb + BAR_XFULL + 8 * (4 * wg_dst + m.warp);
    uint32_t dst = m.sb + OFF_XRES + m.warp * 3072;
    const uint8_t* src = m.xsrc + (size_t)(2 * (2 * u + m.rank)) * (IMG * CH * 2);
    mbar_expect(bar, 3072);
    bulk_load(dst, src, 1536, bar);
    bulk_load(dst + 1536, src + IMG * CH * 2, 1536, bar);
  }
}

__device__ __forceinline__ void epilogue(const MlpCtx& m, const uint32_t (&d)[24], int i) {
  const int u = 2 * i + m.wg;
  mbar_wait(m.sb + BAR_XFULL + 8 * (4 * m.wg + m.warp), i & 1);
  uint8_t* o = m.optr + (size_t)(2 * (2 * u + m.rank)) * (IMG * CH * 2);
#pragma unroll
  for (int r = 0; r < 2; r++) {
#pragma unroll
    for (int q = 0; q < 3; q++) {
      uint32_t x[4], y[4];
      asm volatile("ld.shared.v4.b32 {%0,%1,%2,%3}, [%4];"
                   : "=r"(x[0]), "=r"(x[1]), "=r"(x[2]), "=r"(x[3])
                   : "r"(m.xaddr + r * 384 + q * 64)
                   : "memory");
#pragma unroll
      for (int j = 0; j < 4; j++) {
        uint32_t v = d[2 * (4 * q + j) + r];
        float lo, hi;
        asm("{\n.reg .b16 l, h;\nmov.b32 {l, h}, %2;\ncvt.f32.f16 %0, l;\ncvt.f32.f16 %1, h;\n}\n" : "=f"(lo), "=f"(hi) : "r"(v));
        y[j] = bf_fma(pack_bf16(lo, hi), m.unscale, x[j]);
      }
      asm volatile("st.global.v4.b32 [%0], {%1,%2,%3,%4};" ::"l"(o + r * 384 + q * 64), "r"(y[0]), "r"(y[1]), "r"(y[2]), "r"(y[3])
                   : "memory");
    }
  }
  __syncwarp();
  if (u + 1 < 32) issue_xres(m, u + 1, m.wg ^ 1);
}

__device__ __forceinline__ void gate_close(int rho) {
  if (rho > 0 && rho <= NGATED) NB_SYNC(NB_CLOSE, 512);
}
__device__ __forceinline__ void gate_open(int rho) {
  if (rho < NGATED) NB_ARRIVE(NB_OPEN, 512);
}

constexpr int GS = 10;

__device__ __forceinline__ void mlp_role(const MlpCtx& m0, const __nv_bfloat16* w1, const __nv_bfloat16* w2) {
  MlpCtx m = m0;
  const int tid = threadIdx.x, lane = m.lane, wid = tid >> 5;
  if (m.wg == 0) issue_xres(m, 0, 0);
  {
    uint32_t mx = 0;
    const int k7 = lane & 7;
#pragma unroll 6
    for (int it = 0; it < 18; it++) {
      int item = wid * 18 + it, kb = item / 12, ng = item % 12;
      int ch = 24 * (k7 >> 1) + 2 * kb + (k7 & 1);
      int n8 = ng * 4 + (lane >> 3);
      uint4 v = __ldg(reinterpret_cast<const uint4*>(w1 + ch * 384 + n8 * 8));
      mx = __vmaxu2(mx, __vmaxu2(__vmaxu2(v.x & 0x7fff7fffu, v.y & 0x7fff7fffu), __vmaxu2(v.z & 0x7fff7fffu, v.w & 0x7fff7fffu)));
      uint32_t dst = m.sb + OFF_W1 + ((n8 / 12) * 6 + (kb >> 1)) * 3072 + (kb & 1) * 128 + (n8 % 12) * 256 + k7 * 16;
      asm volatile("st.shared.v4.b32 [%0], {%1,%2,%3,%4};" ::"r"(dst), "r"(pack_f16(bf_lo(v.x), bf_hi(v.x))),
                   "r"(pack_f16(bf_lo(v.y), bf_hi(v.y))), "r"(pack_f16(bf_lo(v.z), bf_hi(v.z))),
                   "r"(pack_f16(bf_lo(v.w), bf_hi(v.w)))
                   : "memory");
    }
    uint32_t v2[5][16];
    uint32_t mx2 = 0;
#pragma unroll
    for (int it = 0; it < 5; it++) {
      int item = (it * 8 + wid) * 4 + (lane >> 3);
      if (item > 143) item = 143;
      int kb = item / 3, q = item % 3;
      const uint4* src = reinterpret_cast<const uint4*>(w2 + (kb * 8 + k7) * 96 + q * 32);
#pragma unroll
      for (int t = 0; t < 4; t++) {
        uint4 v = __ldg(src + t);
        v2[it][4 * t] = v.x; v2[it][4 * t + 1] = v.y; v2[it][4 * t + 2] = v.z; v2[it][4 * t + 3] = v.w;
      }
    }
#pragma unroll
    for (int it = 0; it < 5; it++)
#pragma unroll
      for (int t = 0; t < 16; t++) mx2 = __vmaxu2(mx2, v2[it][t] & 0x7fff7fffu);
    mx = __reduce_max_sync(0xffffffffu, max(mx & 0xffffu, mx >> 16));
    mx2 = __reduce_max_sync(0xffffffffu, max(mx2 & 0xffffu, mx2 >> 16));
    if (lane == 0) {
      asm volatile("red.shared.max.u32 [%0], %1;" ::"r"(m.sb + OFF_MAX), "r"(mx) : "memory");
      asm volatile("red.shared.max.u32 [%0], %1;" ::"r"(m.sb + OFF_MAX + 4), "r"(mx2) : "memory");
    }
    NB_SYNC(NB_PREP, 256);
    asm volatile("ld.shared.v2.b32 {%0,%1}, [%2];" : "=r"(mx), "=r"(mx2) : "r"(m.sb + OFF_MAX) : "memory");
    int e1 = (int)(mx >> 7) - 126, e2 = (int)(mx2 >> 7) - 126;
    int s = min(-1 - e1 - e2, 14 - e2);
    s = max(-120, min(120, s));
    float sc = __uint_as_float((uint32_t)(127 + s) << 23) * (0.5f / GELU_A);
    m.unscale = ((uint32_t)(127 - s) << 7) * 0x10001u;
#pragma unroll
    for (int it = 0; it < 5; it++) {
      int item = (it * 8 + wid) * 4 + (lane >> 3);
      if (item > 143) item = 143;
      int kb = item / 3, q = item % 3;
      uint32_t dst = m.sb + OFF_W2 + (kb >> 1) * 3072 + (kb & 1) * 128 + q * 1024 + k7 * 16;
#pragma unroll
      for (int j = 0; j < 4; j++) {
        uint32_t o[4];
#pragma unroll
        for (int t = 0; t < 4; t++) o[t] = pack_f16(bf_lo(v2[it][4 * t + j]) * sc, bf_hi(v2[it][4 * t + j]) * sc);
        asm volatile("st.shared.v4.b32 [%0], {%1,%2,%3,%4};" ::"r"(dst + j * 256), "r"(o[0]), "r"(o[1]), "r"(o[2]), "r"(o[3]) : "memory");
      }
    }
    asm volatile("fence.proxy.async.shared::cta;" ::: "memory");
    NB_SYNC(NB_PREP, 256);
  }
  const uint64_t dW1 = (uint64_t)(((m.sb + OFF_W1) & 0x3FFFF) >> 4) | ((uint64_t)8 << 16) | ((uint64_t)16 << 32);
  const uint64_t dW2 = dW1 + (OFF_W2 >> 4);
  constexpr uint64_t CHK = 1152;

  int rho = 0;
  for (; rho < 2 * m.wg + m.rank; rho++) { gate_close(rho); gate_open(rho); }

  uint32_t A1[24], D2[24], g[24], d[24];
  {
    uint32_t d0[24];
    layernorm(m, A1, 0);
    WG_FENCE();
    gate_close(rho);
    gemm6<true>(d0, A1, dW1);
    gate_open(rho++);
    WG_WAIT0(); rfence(d0);
    WG_FENCE();
    gate_close(rho);
    gemm6<true>(d, A1, dW1 + CHK);
    gate_open(rho++);
    gelu<0, 24>(g, d0);
    WG_WAIT0(); rfence(d);
  }
#pragma unroll 1
  for (int i = 0; i < 16; i++) {
    const bool more = i < 15;
    uint32_t g1[24], d2[24], g2[24], d3[24], g3[24], d0[24];
    WG_FENCE();
    gate_close(rho);
    gemm6<true>(D2, g, dW2);
    gelu<0, GS>(g1, d);
    WG_WAIT0(); rfence(D2);
    WG_FENCE();
    gemm6<true>(d2, A1, dW1 + 2 * CHK);
    gate_open(rho++);
    gelu<GS, 24>(g1, d);
    WG_WAIT0(); rfence(d2);
    WG_FENCE();
    gate_close(rho);
    gemm6<false>(D2, g1, dW2 + CHK);
    gelu<0, GS>(g2, d2);
    WG_WAIT0(); rfence(D2);
    WG_FENCE();
    gemm6<true>(d3, A1, dW1 + 3 * CHK);
    gate_open(rho++);
    gelu<GS, 24>(g2, d2);
    WG_WAIT0(); rfence(d3);
    if (!more) {
      WG_FENCE();
      gate_close(rho);
      gemm6<false>(D2, g2, dW2 + 2 * CHK);
      gate_open(rho++);
      gelu<0, 24>(g3, d3);
      WG_WAIT0(); rfence(D2);
      WG_FENCE();
      gate_close(rho);
      gemm6<false>(D2, g3, dW2 + 3 * CHK);
      gate_open(rho++);
      WG_WAIT0(); rfence(D2);
      epilogue(m, D2, i);
      break;
    }
    WG_FENCE();
    gate_close(rho);
    gemm6<false>(D2, g2, dW2 + 2 * CHK);
    layernorm(m, A1, i + 1);
    WG_WAIT0(); rfence(D2);
    WG_FENCE();
    gemm6<true>(d0, A1, dW1);
    gate_open(rho++);
    gelu<0, 24>(g3, d3);
    WG_WAIT0(); rfence(d0);
    WG_FENCE();
    gate_close(rho);
    gemm6<false>(D2, g3, dW2 + 3 * CHK);
    gelu<0, GS + 4>(g, d0);
    WG_WAIT0(); rfence(D2);
    WG_FENCE();
    gemm6<true>(d, A1, dW1 + CHK);
    gate_open(rho++);
    epilogue(m, D2, i);
    gelu<GS + 4, 24>(g, d0);
    WG_WAIT0(); rfence(d);
  }
}

struct ConvCtx {
  uint32_t sb;
  uint32_t a_ldsm, a_stsm, a_frag, a_c;
  uint32_t peer_off;
  int rank, v, lane, c0, r0, zero;
  const CUtensorMap* tm;
};

__device__ __forceinline__ void conv_ldsm(const ConvCtx& c, int s, int st, uint32_t (&t)[8]) {
  mbar_wait(c.sb + BAR_RAW + 8 * st, (s >> 2) & 1);
#pragma unroll
  for (int h = 0; h < 2; h++)
    asm volatile("ldmatrix.sync.aligned.m8n8.x4.trans.shared.b16 {%0,%1,%2,%3}, [%4];"
                 : "=r"(t[4 * h]), "=r"(t[4 * h + 1]), "=r"(t[4 * h + 2]), "=r"(t[4 * h + 3])
                 : "r"(c.a_ldsm + st * RAW_BYTES + h * 48)
                 : "memory");
}
__device__ __forceinline__ void conv_stage(const ConvCtx& c, int s, int st, const uint32_t (&t)[8], uint32_t (&A)[24]) {
#pragma unroll
  for (int h = 0; h < 2; h++)
    asm volatile("stmatrix.sync.aligned.m8n8.x4.shared.b16 [%0], {%1,%2,%3,%4};" ::"r"(c.a_stsm + (st & 1) * PLAN_BYTES + h * 24 * PLAN_PITCH),
                 "r"(t[4 * h]), "r"(t[4 * h + 1]), "r"(t[4 * h + 2]), "r"(t[4 * h + 3])
                 : "memory");
  NB_SYNC(NB_PLAN, 256);
  if (c.v == 0 && c.lane == 0 && s + 4 < NSTEP) {
    mbar_expect(c.sb + BAR_RAW + 8 * st, RAW_BYTES);
    tma_raw(c.sb + OFF_RAW + st * RAW_BYTES, c.tm, 48 * c.rank, c.c0 - 3, c.r0 - 3 + 2 * (s + 4), c.sb + BAR_RAW + 8 * st);
  }
#pragma unroll
  for (int ch = 0; ch < 6; ch++) {
    uint32_t a = c.a_frag + (st & 1) * PLAN_BYTES + ch * PLAN_PITCH;
    asm volatile("ld.shared.v2.b32 {%0,%1}, [%2];" : "=r"(A[4 * ch]), "=r"(A[4 * ch + 1]) : "r"(a) : "memory");
    asm volatile("ld.shared.b32 %0, [%1];" : "=r"(A[4 * ch + 3]) : "r"(a + 8) : "memory");
    A[4 * ch + 2] = A[4 * ch + 1] ^ c.zero;
  }
}

template <int BETA>
__device__ __forceinline__ void conv_step(const ConvCtx& c, int s, float (&acc)[6][2][4], const uint32_t (&B)[6][4][2],
                                          uint32_t (&A)[24]) {
  if (s >= SIGMA) NB_SYNC(NB_OPEN, 512);
#pragma unroll
  for (int ch = 0; ch < 6; ch++)
#pragma unroll
    for (int X = 0; X < 2; X++) {
      const int b = (BETA - 2 * X) & 3;
      asm volatile("mma.sync.aligned.m16n8k16.row.col.f32.bf16.bf16.f32 {%0,%1,%2,%3}, {%4,%5,%6,%7}, {%8,%9}, {%0,%1,%2,%3};"
                   : "+f"(acc[ch][X][0]), "+f"(acc[ch][X][1]), "+f"(acc[ch][X][2]), "+f"(acc[ch][X][3])
                   : "r"(A[4 * ch]), "r"(A[4 * ch + 1]), "r"(A[4 * ch + 2]), "r"(A[4 * ch + 3]), "r"(B[ch][b][0]), "r"(B[ch][b][1]));
    }
  if (s >= SIGMA) NB_ARRIVE(NB_CLOSE, 512);
  uint32_t t[8];
  const bool more = s + 1 < NSTEP;
  if (more) conv_ldsm(c, s + 1, (BETA + 1) & 3, t);
  constexpr int TM = (BETA + 1) & 3;
  constexpr int X = TM >> 1, E = TM & 1;
  if (s >= 3) {
    const int tau = s - 3;
    if (tau >= 4) mbar_wait(c.sb + BAR_CEMPTY + 8 * (2 * E + X), ((tau >> 2) - 1) & 1);
    const uint32_t off = (E == c.rank) ? 0u : c.peer_off;
    const uint32_t dst = c.a_c + off + X * C_BYTES, bar = c.sb + off + BAR_CFULL + 8 * X;
#pragma unroll
    for (int q = 0; q < 3; q++) {
      uint32_t p0 = pack_bf16(acc[2 * q][X][E], acc[2 * q + 1][X][E]);
      uint32_t p1 = pack_bf16(acc[2 * q][X][E + 2], acc[2 * q + 1][X][E + 2]);
      asm volatile("st.async.weak.shared::cluster.mbarrier::complete_tx::bytes.v2.b32 [%0], {%1,%2}, [%3];" ::"r"(dst + q * 256),
                   "r"(p0), "r"(p1), "r"(bar)
                   : "memory");
    }
  }
#pragma unroll
  for (int ch = 0; ch < 6; ch++) acc[ch][X][E] = acc[ch][X][E + 2] = 0.f;
  if (more) conv_stage(c, s + 1, (BETA + 1) & 3, t, A);
}

__device__ __forceinline__ void conv_role(const ConvCtx& c, const __nv_bfloat16* dw) {
  const int lane = c.lane, g = lane >> 2, t = lane & 3;
  uint32_t B[6][4][2];
  {
    const int e = g & 1, dc = (g >> 1) & 1, ro = g >> 2, rk = t >> 1;
    const uint32_t* dwp = reinterpret_cast<const uint32_t*>(dw) + 24 * c.rank + 3 * c.v;
#pragma unroll
    for (int b = 0; b < 4; b++) {
      const int i = 2 * ((b - e) & 3) + rk - ro;
      uint32_t w[4][3];
#pragma unroll
      for (int k = 0; k < 4; k++) {
        const int j = 4 * (t & 1) + k - dc;
        const bool ok = i >= 0 && i < 7 && j >= 0 && j < 7;
#pragma unroll
        for (int q = 0; q < 3; q++) w[k][q] = ok ? __ldg(dwp + (i * 7 + j) * 48 + q) : 0u;
      }
#pragma unroll
      for (int q = 0; q < 3; q++) {
        B[2 * q][b][0] = __byte_perm(w[0][q], w[1][q], 0x5410);
        B[2 * q][b][1] = __byte_perm(w[2][q], w[3][q], 0x5410);
        B[2 * q + 1][b][0] = __byte_perm(w[0][q], w[1][q], 0x7632);
        B[2 * q + 1][b][1] = __byte_perm(w[2][q], w[3][q], 0x7632);
      }
    }
  }
  float acc[6][2][4];
#pragma unroll
  for (int ch = 0; ch < 6; ch++)
#pragma unroll
    for (int k = 0; k < 8; k++) acc[ch][k >> 2][k & 3] = 0.f;
  uint32_t A[24];
  {
    uint32_t tt[8];
    conv_ldsm(c, 0, 0, tt);
    conv_stage(c, 0, 0, tt, A);
  }
#pragma unroll 1
  for (int s = 0; s < NSTEP; s += 4) {
    conv_step<0>(c, s, acc, B, A);
    conv_step<1>(c, s + 1, acc, B, A);
    conv_step<2>(c, s + 2, acc, B, A);
    if (s + 3 < NSTEP) conv_step<3>(c, s + 3, acc, B, A);
  }
}

__global__ void __cluster_dims__(2, 1, 1) __launch_bounds__(512, 1)
convnext_kernel(const __grid_constant__ CUtensorMap tm, const __nv_bfloat16* __restrict__ x, const __nv_bfloat16* __restrict__ dw,
                const __nv_bfloat16* __restrict__ w1, const __nv_bfloat16* __restrict__ w2, __nv_bfloat16* __restrict__ out,
                int zero) {
  extern __shared__ __align__(1024) uint8_t smem[];
  const uint32_t sb = (uint32_t)__cvta_generic_to_shared(smem);
  const int tid = threadIdx.x, lane = tid & 31;
  const int wid = __shfl_sync(0xffffffffu, tid >> 5, 0);
  const int rank = blockIdx.x & 1, cl = blockIdx.x >> 1;
  const int c0 = (cl & 15) * 32, r0 = (cl >> 4) * 128;
  const uint32_t peer_off = mapa(sb, rank ^ 1) - sb;

  if (tid == 256) {
    for (int i = 0; i < 4; i++) mbar_init(sb + BAR_RAW + 8 * i, 1);
    for (int i = 0; i < 2; i++) mbar_init(sb + BAR_CFULL + 8 * i, 1);
    for (int i = 0; i < 4; i++) mbar_init(sb + BAR_CEMPTY + 8 * i, 4);
    for (int i = 0; i < 8; i++) mbar_init(sb + BAR_XFULL + 8 * i, 1);
    asm volatile("st.shared.v2.b32 [%0], {%1,%1};" ::"r"(sb + OFF_MAX), "r"(0) : "memory");
    asm volatile("fence.mbarrier_init.release.cluster;" ::: "memory");
    asm volatile("fence.proxy.async.shared::cta;" ::: "memory");
    for (int i = 0; i < 4; i++) {
      mbar_expect(sb + BAR_RAW + 8 * i, RAW_BYTES);
      tma_raw(sb + OFF_RAW + i * RAW_BYTES, &tm, 48 * rank, c0 - 3, r0 - 3 + 2 * i, sb + BAR_RAW + 8 * i);
    }
    for (int i = 0; i < 2; i++) mbar_expect(sb + BAR_CFULL + 8 * i, 12288);
  }
  __syncwarp();
  asm volatile("barrier.cluster.arrive.aligned;\nbarrier.cluster.wait.aligned;" ::: "memory");

  if (wid < 8) {
    MlpCtx m;
    m.sb = sb; m.wg = wid >> 2; m.warp = wid & 3; m.lane = lane; m.rank = rank; m.peer_off = peer_off;
    const int g = lane >> 2, t = lane & 3;
    m.caddr = sb + OFF_C + m.wg * C_BYTES + t * (12 * 256 + 32) + (8 * m.warp + g) * 8;
    const int row = (g >> 1) & 1, col = 4 * (g >> 2) + (g & 1);
    m.xaddr = sb + OFF_XRES + m.warp * 3072 + row * 1536 + col * 192 + t * 16;
    m.xsrc = reinterpret_cast<const uint8_t*>(x) + ((size_t)r0 * IMG + c0 + 8 * m.warp) * (CH * 2);
    m.optr = reinterpret_cast<uint8_t*>(out) + ((size_t)(r0 + row) * IMG + c0 + 8 * m.warp + col) * (CH * 2) + t * 16;
    m.unscale = 0;
    mlp_role(m, w1, w2);
  } else {
    ConvCtx c;
    c.sb = sb; c.rank = rank; c.v = wid - 8; c.lane = lane; c.c0 = c0; c.r0 = r0; c.zero = zero; c.tm = &tm;
    c.peer_off = peer_off;
    const int b = min(4 * c.v + (lane >> 3), 29), cg = b / 10, rb = b % 10;
    c.a_ldsm = sb + OFF_RAW + ((rb / 5) * 38 + (rb % 5) * 8 + (lane & 7)) * 96 + cg * 16;
    c.a_stsm = sb + OFF_PLAN + (cg * 8 + (lane & 7)) * PLAN_PITCH + rb * 16;
    const int g = lane >> 2, t = lane & 3;
    c.a_frag = sb + OFF_PLAN + 6 * c.v * PLAN_PITCH + (t >> 1) * 80 + (g + (t & 1)) * 8;
    const int p0 = 24 * rank + 3 * c.v;
    c.a_c = sb + OFF_C + p0 * 256 + (p0 / 12) * 32 + lane * 8;
    conv_role(c, dw);
  }
  __syncwarp();
  asm volatile("barrier.cluster.arrive.aligned;\nbarrier.cluster.wait.aligned;" ::: "memory");
}

typedef CUresult (*EncodeFn)(CUtensorMap*, CUtensorMapDataType, cuuint32_t, void*, const cuuint64_t*, const cuuint64_t*,
                             const cuuint32_t*, const cuuint32_t*, CUtensorMapInterleave, CUtensorMapSwizzle,
                             CUtensorMapL2promotion, CUtensorMapFloatOOBfill);

}

extern "C" void kernel_launch(void* const* d_in, const int* in_sizes, int n_in, void* d_out, int out_size) {
  const __nv_bfloat16* x = (const __nv_bfloat16*)d_in[0];
  const __nv_bfloat16* dw = (const __nv_bfloat16*)d_in[1];
  const __nv_bfloat16* w1 = (const __nv_bfloat16*)d_in[2];
  const __nv_bfloat16* w2 = (const __nv_bfloat16*)d_in[3];
  __nv_bfloat16* out = (__nv_bfloat16*)d_out;

  static EncodeFn encode = nullptr;
  if (!encode) {
    cudaDriverEntryPointQueryResult st;
    void* fn = nullptr;
    cudaGetDriverEntryPoint("cuTensorMapEncodeTiled", &fn, cudaEnableDefault, &st);
    encode = (EncodeFn)fn;
    cudaFuncSetAttribute(convnext_kernel, cudaFuncAttributeMaxDynamicSharedMemorySize, SMEM_BYTES);
  }
  CUtensorMap tm;
  cuuint64_t dims[3] = {CH, IMG, IMG};
  cuuint64_t strides[2] = {CH * 2, (cuuint64_t)IMG * CH * 2};
  cuuint32_t box[3] = {48, 38, 2};
  cuuint32_t es[3] = {1, 1, 1};
  encode(&tm, CU_TENSOR_MAP_DATA_TYPE_BFLOAT16, 3, (void*)x, dims, strides, box, es, CU_TENSOR_MAP_INTERLEAVE_NONE,
         CU_TENSOR_MAP_SWIZZLE_NONE, CU_TENSOR_MAP_L2_PROMOTION_L2_128B, CU_TENSOR_MAP_FLOAT_OOB_FILL_NONE);
  convnext_kernel<<<128, 512, SMEM_BYTES>>>(tm, x, dw, w1, w2, out, 0);
}
```

```cpp
#include <cuda_runtime.h>
#include <cuda_bf16.h>
#include <cuda.h>
#include <stdint.h>

namespace {

constexpr int IMG = 512, CH = 96;
constexpr int NSTEP = 67;
constexpr int SIGMA = 5;
constexpr int NGATED = NSTEP - SIGMA;

constexpr uint32_t OFF_W1 = 0;
constexpr uint32_t OFF_W2 = 73728;
constexpr uint32_t OFF_RAW = 147456;
constexpr uint32_t RAW_BYTES = 2 * 38 * 96;
constexpr uint32_t OFF_XRES = OFF_RAW + 4 * RAW_BYTES;
constexpr uint32_t OFF_C = OFF_XRES + 12288;
constexpr uint32_t C_BYTES = 12416;
constexpr uint32_t OFF_PLAN = OFF_C + 2 * C_BYTES;
constexpr uint32_t PLAN_PITCH = 176;
constexpr uint32_t PLAN_BYTES = 48 * PLAN_PITCH;
constexpr uint32_t OFF_BAR = OFF_PLAN + 2 * PLAN_BYTES;
constexpr uint32_t BAR_RAW = OFF_BAR;
constexpr uint32_t BAR_CFULL = OFF_BAR + 32;
constexpr uint32_t BAR_CEMPTY = OFF_BAR + 48;
constexpr uint32_t BAR_XFULL = OFF_BAR + 80;
constexpr uint32_t OFF_MAX = OFF_BAR + 144;
constexpr uint32_t SMEM_BYTES = OFF_BAR + 160;

constexpr float GELU_A = 0.32918364f;
constexpr uint32_t GELU_K2 = 0x40d940d9u;

constexpr int NB_OPEN = 1, NB_CLOSE = 2, NB_PLAN = 3, NB_PREP = 4;

#define WG_FENCE() asm volatile("wgmma.fence.sync.aligned;" ::: "memory")
#define WG_COMMIT() asm volatile("wgmma.commit_group.sync.aligned;" ::: "memory")
#define WG_WAIT0() asm volatile("wgmma.wait_group.sync.aligned 0;" ::: "memory")
#define PIN() asm volatile("pmevent 0;" ::: "memory")
#define NB_SYNC(id, n) asm volatile("bar.sync %0, %1;" ::"n"(id), "n"(n) : "memory")
#define NB_ARRIVE(id, n) asm volatile("bar.arrive %0, %1;" ::"n"(id), "n"(n) : "memory")

#define R24(c, d)                                                                                        \
  c(d[0]), c(d[1]), c(d[2]), c(d[3]), c(d[4]), c(d[5]), c(d[6]), c(d[7]), c(d[8]), c(d[9]), c(d[10]),    \
      c(d[11]), c(d[12]), c(d[13]), c(d[14]), c(d[15]), c(d[16]), c(d[17]), c(d[18]), c(d[19]), c(d[20]), \
      c(d[21]), c(d[22]), c(d[23])
#define WG_TXT(sd)                                                                             \
  "wgmma.mma_async.sync.aligned.m64n96k16.f16.f16.f16 "                                        \
  "{%0,%1,%2,%3,%4,%5,%6,%7,%8,%9,%10,%11,%12,%13,%14,%15,%16,%17,%18,%19,%20,%21,%22,%23}, " \
  "{%24,%25,%26,%27}, %28, " sd ", 1, 1, 1;\n"

__device__ __forceinline__ void wg_acc(uint32_t (&d)[24], const uint32_t* a, uint64_t db) {
  asm volatile(WG_TXT("1") : R24("+r", d) : "r"(a[0]), "r"(a[1]), "r"(a[2]), "r"(a[3]), "l"(db));
}
__device__ __forceinline__ void wg_init(uint32_t (&d)[24], const uint32_t* a, uint64_t db) {
  asm volatile(WG_TXT("0") : R24("=r", d) : "r"(a[0]), "r"(a[1]), "r"(a[2]), "r"(a[3]), "l"(db));
}
__device__ __forceinline__ void wg_pred(uint32_t (&d)[24], const uint32_t* a, uint64_t db, int acc) {
  asm volatile("{\n.reg .pred p;\nsetp.ne.b32 p, %29, 0;\n" WG_TXT("p") "}\n"
               : R24("+r", d)
               : "r"(a[0]), "r"(a[1]), "r"(a[2]), "r"(a[3]), "l"(db), "r"(acc));
}
template <int N>
__device__ __forceinline__ void rfence(uint32_t (&d)[N]) {
#pragma unroll
  for (int i = 0; i < N; i++) asm volatile("" : "+r"(d[i])::"memory");
}
template <bool INIT>
__device__ __forceinline__ void gemm6(uint32_t (&d)[24], const uint32_t (&a)[24], uint64_t db) {
#pragma unroll
  for (int k = 0; k < 6; k++) {
    if (INIT && k == 0) wg_init(d, &a[0], db);
    else wg_acc(d, &a[4 * k], db + k * 192);
  }
  WG_COMMIT();
}

__device__ __forceinline__ void gemm6p(uint32_t (&d)[24], const uint32_t (&a)[24], uint64_t db, int acc) {
  wg_pred(d, &a[0], db, acc);
#pragma unroll
  for (int k = 1; k < 6; k++) wg_acc(d, &a[4 * k], db + k * 192);
  WG_COMMIT();
}

__device__ __forceinline__ void mbar_init(uint32_t bar, uint32_t cnt) {
  asm volatile("mbarrier.init.shared::cta.b64 [%0], %1;" ::"r"(bar), "r"(cnt) : "memory");
}
__device__ __forceinline__ void mbar_expect(uint32_t bar, uint32_t bytes) {
  asm volatile("mbarrier.arrive.expect_tx.shared::cta.b64 _, [%0], %1;" ::"r"(bar), "r"(bytes) : "memory");
}
__device__ __forceinline__ void mbar_arrive_cluster(uint32_t bar) {
  asm volatile("mbarrier.arrive.shared::cluster.b64 _, [%0];" ::"r"(bar) : "memory");
}
__device__ __forceinline__ void mbar_wait(uint32_t bar, uint32_t parity) {
  uint32_t ok, n = 0;
  do {
    asm volatile(
        "{\n.reg .pred p;\nmbarrier.try_wait.parity.shared::cta.b64 p, [%1], %2;\nselp.u32 %0, 1, 0, p;\n}\n"
        : "=r"(ok)
        : "r"(bar), "r"(parity)
        : "memory");
    if (++n > (1u << 22)) __trap();
  } while (!ok);
}
__device__ __forceinline__ uint32_t mapa(uint32_t addr, uint32_t rank) {
  uint32_t r;
  asm("mapa.shared::cluster.u32 %0, %1, %2;" : "=r"(r) : "r"(addr), "r"(rank));
  return r;
}
__device__ __forceinline__ void tma_raw(uint32_t dst, const CUtensorMap* tm, int c, int w, int h, uint32_t bar) {
  asm volatile(
      "cp.async.bulk.tensor.3d.shared::cluster.global.mbarrier::complete_tx::bytes [%0], [%1, {%2, %3, %4}], [%5];"
      ::"r"(dst), "l"(tm), "r"(c), "r"(w), "r"(h), "r"(bar)
      : "memory");
}
__device__ __forceinline__ void bulk_load(uint32_t dst, const void* src, uint32_t bytes, uint32_t bar) {
  asm volatile("cp.async.bulk.shared::cluster.global.mbarrier::complete_tx::bytes [%0], [%1], %2, [%3];" ::"r"(dst),
               "l"(src), "r"(bytes), "r"(bar)
               : "memory");
}
__device__ __forceinline__ uint32_t pack_bf16(float lo, float hi) {
  uint32_t r;
  asm("cvt.rn.bf16x2.f32 %0, %1, %2;" : "=r"(r) : "f"(hi), "f"(lo));
  return r;
}
__device__ __forceinline__ uint32_t pack_f16(float lo, float hi) {
  uint32_t r;
  asm("cvt.rn.f16x2.f32 %0, %1, %2;" : "=r"(r) : "f"(hi), "f"(lo));
  return r;
}
__device__ __forceinline__ float bf_lo(uint32_t v) { return __uint_as_float(v << 16); }
__device__ __forceinline__ float bf_hi(uint32_t v) { return __uint_as_float(v & 0xffff0000u); }
__device__ __forceinline__ uint32_t bf_add(uint32_t a, uint32_t b) {
  uint32_t r;
  asm("add.rn.bf16x2 %0, %1, %2;" : "=r"(r) : "r"(a), "r"(b));
  return r;
}
__device__ __forceinline__ uint32_t bf_mul(uint32_t a, uint32_t b) {
  uint32_t r;
  asm("mul.rn.bf16x2 %0, %1, %2;" : "=r"(r) : "r"(a), "r"(b));
  return r;
}
__device__ __forceinline__ uint32_t bf_fma(uint32_t a, uint32_t b, uint32_t c) {
  uint32_t r;
  asm("fma.rn.bf16x2 %0, %1, %2, %3;" : "=r"(r) : "r"(a), "r"(b), "r"(c));
  return r;
}

template <int LO, int HI>
__device__ __forceinline__ void gelu(uint32_t (&o)[24], const uint32_t (&d)[24]) {
#pragma unroll
  for (int q = LO; q < HI; q++) {
    uint32_t t, u;
    asm("fma.rn.f16x2 %0, %1, %1, %2;" : "=r"(t) : "r"(d[q]), "r"(GELU_K2));
    asm("mul.rn.f16x2 %0, %1, %2;" : "=r"(u) : "r"(d[q]), "r"(t));
    asm("tanh.approx.f16x2 %0, %1;" : "=r"(t) : "r"(u));
    asm("fma.rn.f16x2 %0, %1, %2, %1;" : "=r"(o[q]) : "r"(d[q]), "r"(t));
  }
}

__device__ __forceinline__ uint32_t laneid() {
  uint32_t l;
  asm volatile("mov.u32 %0, %%laneid;" : "=r"(l));
  return l;
}

__device__ __forceinline__ bool elect_one() {
  uint32_t p;
  asm volatile("{\n.reg .pred p;\nelect.sync _|p, 0xffffffff;\nselp.u32 %0, 1, 0, p;\n}\n" : "=r"(p));
  return p;
}

struct MlpCtx {
  uint32_t sb;
  uint32_t unscale;
  uint32_t peer_off;
  int wg, warp, rank;
  const uint8_t* xsrc;
  uint8_t* optr;
};

__device__ __forceinline__ void layernorm(const MlpCtx& m, uint32_t (&a)[24], int i) {
  const uint32_t lane = laneid();
  const uint32_t caddr = m.sb + OFF_C + m.wg * C_BYTES + m.warp * 64 + (lane & 3) * (12 * 256 + 32) + (lane >> 2) * 8;
  mbar_wait(m.sb + BAR_CFULL + 8 * m.wg, i & 1);
  uint32_t c[24];
#pragma unroll
  for (int p = 0; p < 12; p++)
    asm volatile("ld.shared.v2.b32 {%0,%1}, [%2];" : "=r"(c[2 * p]), "=r"(c[2 * p + 1]) : "r"(caddr + p * 256) : "memory");
  float mean[2];
#pragma unroll
  for (int r = 0; r < 2; r++) {
    uint32_t s0 = bf_add(c[r], c[r + 2]), s1 = bf_add(c[r + 4], c[r + 6]), s2 = bf_add(c[r + 8], c[r + 10]);
    uint32_t s3 = bf_add(c[r + 12], c[r + 14]), s4 = bf_add(c[r + 16], c[r + 18]), s5 = bf_add(c[r + 20], c[r + 22]);
    s0 = bf_add(s0, s1); s2 = bf_add(s2, s3); s4 = bf_add(s4, s5);
    s0 = bf_add(bf_add(s0, s2), s4);
    mean[r] = bf_lo(s0) + bf_hi(s0);
  }
  __syncwarp();
  if (lane == 0) {
    if (m.warp == 0) mbar_expect(m.sb + BAR_CFULL + 8 * m.wg, 12288);
    uint32_t e = m.sb + BAR_CEMPTY + 8 * (2 * m.rank + m.wg);
    mbar_arrive_cluster(e);
    mbar_arrive_cluster(e + m.peer_off);
  }
#pragma unroll
  for (int r = 0; r < 2; r++) {
    mean[r] += __shfl_xor_sync(0xffffffffu, mean[r], 1);
    mean[r] += __shfl_xor_sync(0xffffffffu, mean[r], 2);
  }
  float var[2];
#pragma unroll
  for (int r = 0; r < 2; r++) {
    float nm = mean[r] * (-1.0f / 96.0f);
    uint32_t nm2 = pack_bf16(nm, nm);
#pragma unroll
    for (int p = 0; p < 12; p++) c[2 * p + r] = bf_add(c[2 * p + r], nm2);
    uint32_t q0 = bf_mul(c[r], c[r]), q1 = bf_mul(c[r + 2], c[r + 2]), q2 = bf_mul(c[r + 4], c[r + 4]);
#pragma unroll
    for (int p = 3; p < 12; p += 3) {
      q0 = bf_fma(c[2 * p + r], c[2 * p + r], q0);
      q1 = bf_fma(c[2 * p + 2 + r], c[2 * p + 2 + r], q1);
      q2 = bf_fma(c[2 * p + 4 + r], c[2 * p + 4 + r], q2);
    }
    q0 = bf_add(bf_add(q0, q1), q2);
    var[r] = bf_lo(q0) + bf_hi(q0);
  }
#pragma unroll
  for (int r = 0; r < 2; r++) {
    var[r] += __shfl_xor_sync(0xffffffffu, var[r], 1);
    var[r] += __shfl_xor_sync(0xffffffffu, var[r], 2);
  }
  float rs[2];
#pragma unroll
  for (int r = 0; r < 2; r++) rs[r] = rsqrtf(fmaf(var[r], 1.0f / 96.0f, 1e-5f)) * GELU_A;
  if (__builtin_expect(fminf(rs[0], rs[1]) < 0x1p-13f, 0)) {
#pragma unroll
    for (int r = 0; r < 2; r++) {
      uint32_t e = __float_as_uint(rs[r]) & 0x7f800000u;
      uint32_t e2 = (e >> 16) | e;
#pragma unroll
      for (int p = 0; p < 12; p++) c[2 * p + r] = bf_mul(c[2 * p + r], e2);
      rs[r] = __uint_as_float((__float_as_uint(rs[r]) & 0x007fffffu) | 0x3f800000u);
    }
  }
#pragma unroll
  for (int r = 0; r < 2; r++) {
    float rr = rs[r] * 0x1p-112f;
    uint32_t r2 = pack_bf16(rr, rr);
#pragma unroll
    for (int p = 0; p < 12; p++) {
      uint32_t v = bf_mul(c[2 * p + r], r2);
      a[2 * p + r] = (v & 0x7fff7fffu) * 7u + v;
    }
  }
}

__device__ __forceinline__ void issue_xres(const MlpCtx& m, int u, int wg_dst) {
  if (laneid() == 0) {
    uint32_t bar = m.sb + BAR_XFULL + 8 * (4 * wg_dst + m.warp);
    uint32_t dst = m.sb + OFF_XRES + m.warp * 3072;
    const uint8_t* src = m.xsrc + (size_t)(2 * (2 * u + m.rank)) * (IMG * CH * 2);
    mbar_expect(bar, 3072);
    bulk_load(dst, src, 1536, bar);
    bulk_load(dst + 1536, src + IMG * CH * 2, 1536, bar);
  }
}

__device__ __forceinline__ void epilogue(const MlpCtx& m, const uint32_t (&d)[24], int i) {
  const int u = 2 * i + m.wg;
  mbar_wait(m.sb + BAR_XFULL + 8 * (4 * m.wg + m.warp), i & 1);
  const uint32_t lane = laneid();
  const uint32_t row = (lane >> 3) & 1, coff = ((lane >> 4) * 4 + ((lane >> 2) & 1)) * 192 + (lane & 3) * 16;
  const uint32_t xaddr = m.sb + OFF_XRES + m.warp * 3072 + row * 1536 + coff;
  uint8_t* o = m.optr + (size_t)(2 * (2 * u + m.rank)) * (IMG * CH * 2) + (row * (IMG * CH * 2) + coff);
#pragma unroll
  for (int r = 0; r < 2; r++) {
#pragma unroll
    for (int q = 0; q < 3; q++) {
      uint32_t x[4], y[4];
      asm volatile("ld.shared.v4.b32 {%0,%1,%2,%3}, [%4];"
                   : "=r"(x[0]), "=r"(x[1]), "=r"(x[2]), "=r"(x[3])
                   : "r"(xaddr + r * 384 + q * 64)
                   : "memory");
#pragma unroll
      for (int j = 0; j < 4; j++) {
        uint32_t v = d[2 * (4 * q + j) + r];
        float lo, hi;
        asm("{\n.reg .b16 l, h;\nmov.b32 {l, h}, %2;\ncvt.f32.f16 %0, l;\ncvt.f32.f16 %1, h;\n}\n" : "=f"(lo), "=f"(hi) : "r"(v));
        y[j] = bf_fma(pack_bf16(lo, hi), m.unscale, x[j]);
      }
      asm volatile("st.global.v4.b32 [%0], {%1,%2,%3,%4};" ::"l"(o + r * 384 + q * 64), "r"(y[0]), "r"(y[1]), "r"(y[2]), "r"(y[3])
                   : "memory");
    }
  }
  __syncwarp();
  if (u + 1 < 32) issue_xres(m, u + 1, m.wg ^ 1);
}

__device__ __forceinline__ void gate_close(int rho) {
  if (rho > 0 && rho <= NGATED) NB_SYNC(NB_CLOSE, 512);
}
__device__ __forceinline__ void gate_open(int rho) {
  if (rho < NGATED) NB_ARRIVE(NB_OPEN, 512);
}

constexpr int GS = 12;

constexpr uint64_t CHK = 1152;

__device__ __forceinline__ void mlp_role(const MlpCtx& m0, const __nv_bfloat16* w1, const __nv_bfloat16* w2) {
  MlpCtx m = m0;
  const int lane = threadIdx.x & 31, wid = m.wg * 4 + m.warp;
  if (m.wg == 0) issue_xres(m, 0, 0);
  {
    uint32_t mx = 0;
    const int k7 = lane & 7;
#pragma unroll 6
    for (int it = 0; it < 18; it++) {
      int item = wid * 18 + it, kb = item / 12, ng = item % 12;
      int ch = 24 * (k7 >> 1) + 2 * kb + (k7 & 1);
      int n8 = ng * 4 + (lane >> 3);
      uint4 v = __ldg(reinterpret_cast<const uint4*>(w1 + ch * 384 + n8 * 8));
      mx = __vmaxu2(mx, __vmaxu2(__vmaxu2(v.x & 0x7fff7fffu, v.y & 0x7fff7fffu), __vmaxu2(v.z & 0x7fff7fffu, v.w & 0x7fff7fffu)));
      uint32_t dst = m.sb + OFF_W1 + ((n8 / 12) * 6 + (kb >> 1)) * 3072 + (kb & 1) * 128 + (n8 % 12) * 256 + k7 * 16;
      asm volatile("st.shared.v4.b32 [%0], {%1,%2,%3,%4};" ::"r"(dst), "r"(pack_f16(bf_lo(v.x), bf_hi(v.x))),
                   "r"(pack_f16(bf_lo(v.y), bf_hi(v.y))), "r"(pack_f16(bf_lo(v.z), bf_hi(v.z))),
                   "r"(pack_f16(bf_lo(v.w), bf_hi(v.w)))
                   : "memory");
    }
    uint32_t v2[5][16];
    uint32_t mx2 = 0;
#pragma unroll
    for (int it = 0; it < 5; it++) {
      int item = (it * 8 + wid) * 4 + (lane >> 3);
      if (item > 143) item = 143;
      int kb = item / 3, q = item % 3;
      const uint4* src = reinterpret_cast<const uint4*>(w2 + (kb * 8 + k7) * 96 + q * 32);
#pragma unroll
      for (int t = 0; t < 4; t++) {
        uint4 v = __ldg(src + t);
        v2[it][4 * t] = v.x; v2[it][4 * t + 1] = v.y; v2[it][4 * t + 2] = v.z; v2[it][4 * t + 3] = v.w;
      }
    }
#pragma unroll
    for (int it = 0; it < 5; it++)
#pragma unroll
      for (int t = 0; t < 16; t++) mx2 = __vmaxu2(mx2, v2[it][t] & 0x7fff7fffu);
    mx = __reduce_max_sync(0xffffffffu, max(mx & 0xffffu, mx >> 16));
    mx2 = __reduce_max_sync(0xffffffffu, max(mx2 & 0xffffu, mx2 >> 16));
    if (lane == 0) {
      asm volatile("red.shared.max.u32 [%0], %1;" ::"r"(m.sb + OFF_MAX), "r"(mx) : "memory");
      asm volatile("red.shared.max.u32 [%0], %1;" ::"r"(m.sb + OFF_MAX + 4), "r"(mx2) : "memory");
    }
    NB_SYNC(NB_PREP, 256);
    asm volatile("ld.shared.v2.b32 {%0,%1}, [%2];" : "=r"(mx), "=r"(mx2) : "r"(m.sb + OFF_MAX) : "memory");
    int e1 = (int)(mx >> 7) - 126, e2 = (int)(mx2 >> 7) - 126;
    int s = min(-1 - e1 - e2, 14 - e2);
    s = max(-120, min(120, s));
    float sc = __uint_as_float((uint32_t)(127 + s) << 23) * (0.5f / GELU_A);
    m.unscale = __shfl_sync(0xffffffffu, ((uint32_t)(127 - s) << 7) * 0x10001u, 0);
#pragma unroll
    for (int it = 0; it < 5; it++) {
      int item = (it * 8 + wid) * 4 + (lane >> 3);
      if (item > 143) item = 143;
      int kb = item / 3, q = item % 3;
      uint32_t dst = m.sb + OFF_W2 + (kb >> 1) * 3072 + (kb & 1) * 128 + q * 1024 + k7 * 16;
#pragma unroll
      for (int j = 0; j < 4; j++) {
        uint32_t o[4];
#pragma unroll
        for (int t = 0; t < 4; t++) o[t] = pack_f16(bf_lo(v2[it][4 * t + j]) * sc, bf_hi(v2[it][4 * t + j]) * sc);
        asm volatile("st.shared.v4.b32 [%0], {%1,%2,%3,%4};" ::"r"(dst + j * 256), "r"(o[0]), "r"(o[1]), "r"(o[2]), "r"(o[3]) : "memory");
      }
    }
    asm volatile("fence.proxy.async.shared::cta;" ::: "memory");
    NB_SYNC(NB_PREP, 256);
  }
  const uint64_t dW1 = (uint64_t)(((m.sb + OFF_W1) & 0x3FFFF) >> 4) | ((uint64_t)8 << 16) | ((uint64_t)16 << 32);
  const uint64_t dW2 = dW1 + (OFF_W2 >> 4);

  int rho = 0;
  for (; rho < 2 * m.wg + m.rank; rho++) { gate_close(rho); gate_open(rho); }

  uint32_t A1[24], g[24], d[24];
  {
    uint32_t d0[24];
    layernorm(m, A1, 0);
    WG_FENCE();
    gate_close(rho);
    gemm6<true>(d0, A1, dW1);
    gate_open(rho++); PIN();
    PIN(); WG_WAIT0(); rfence(d0);
    WG_FENCE();
    gate_close(rho);
    gemm6<true>(d, A1, dW1 + CHK);
    gate_open(rho++); PIN();
    gelu<0, 24>(g, d0);
    PIN(); WG_WAIT0(); rfence(d);
  }
  uint32_t D2[24];
#pragma unroll
  for (int k = 0; k < 24; k++) D2[k] = 0;
#pragma unroll 1
  for (int h = 0; h < 31; h++) {
    const int odd = h & 1;
    const uint64_t w2d = dW2 + odd * 2 * CHK, w1d = dW1 + (odd ^ 1) * 2 * CHK;
    uint32_t g1[24], d2[24];
    WG_FENCE();
    gate_close(rho);
    gemm6p(D2, g, w2d, odd); PIN();
    if (odd) layernorm(m, A1, (h + 1) >> 1);
    PIN(); WG_WAIT0(); rfence(D2);
    WG_FENCE();
    gemm6<true>(d2, A1, w1d);
    gate_open(rho++); PIN();
    gelu<0, 24>(g1, d);
    PIN(); WG_WAIT0(); rfence(d2);

    WG_FENCE();
    gate_close(rho);
    gemm6<false>(D2, g1, w2d + CHK); PIN();
    gelu<0, GS>(g, d2);
    PIN(); WG_WAIT0(); rfence(D2);
    WG_FENCE();
    gemm6<true>(d, A1, w1d + CHK);
    gate_open(rho++); PIN();
    if (odd) epilogue(m, D2, h >> 1);
    gelu<GS, 24>(g, d2);
    PIN(); WG_WAIT0(); rfence(d);
  }
  {
    uint32_t g1[24];
    WG_FENCE();
    gemm6<false>(D2, g, dW2 + 2 * CHK); PIN();
    gelu<0, 24>(g1, d);
    PIN(); WG_WAIT0(); rfence(D2);
    WG_FENCE();
    gemm6<false>(D2, g1, dW2 + 3 * CHK);
    WG_WAIT0(); rfence(D2);
    epilogue(m, D2, 15);
  }
}

struct ConvCtx {
  uint32_t sb;
  uint32_t a_ldsm, a_stsm, a_frag, a_c;
  uint32_t peer_off;
  int rank, v, c0, r0, zero;
  const CUtensorMap* tm;
};

__device__ __forceinline__ void conv_ldsm(const ConvCtx& c, int s, uint32_t (&t)[8]) {
  const int st = s & 3;
  mbar_wait(c.sb + BAR_RAW + 8 * st, (s >> 2) & 1);
#pragma unroll
  for (int h = 0; h < 2; h++)
    asm volatile("ldmatrix.sync.aligned.m8n8.x4.trans.shared.b16 {%0,%1,%2,%3}, [%4];"
                 : "=r"(t[4 * h]), "=r"(t[4 * h + 1]), "=r"(t[4 * h + 2]), "=r"(t[4 * h + 3])
                 : "r"(c.a_ldsm + st * RAW_BYTES + h * 48)
                 : "memory");
}
__device__ __forceinline__ void conv_stage(const ConvCtx& c, int s, const uint32_t (&t)[8], uint32_t (&A)[24]) {
  const int st = s & 3;
  const uint32_t pl = (s & 1) * PLAN_BYTES;
#pragma unroll
  for (int h = 0; h < 2; h++)
    asm volatile("stmatrix.sync.aligned.m8n8.x4.shared.b16 [%0], {%1,%2,%3,%4};" ::"r"(c.a_stsm + pl + h * 24 * PLAN_PITCH),
                 "r"(t[4 * h]), "r"(t[4 * h + 1]), "r"(t[4 * h + 2]), "r"(t[4 * h + 3])
                 : "memory");
  NB_SYNC(NB_PLAN, 256);
  if (c.v == 0 && s + 4 < NSTEP && elect_one()) {
    mbar_expect(c.sb + BAR_RAW + 8 * st, RAW_BYTES);
    tma_raw(c.sb + OFF_RAW + st * RAW_BYTES, c.tm, 48 * c.rank, c.c0 - 3, c.r0 - 3 + 2 * (s + 4), c.sb + BAR_RAW + 8 * st);
  }
#pragma unroll
  for (int ch = 0; ch < 6; ch++) {
    uint32_t a = c.a_frag + pl + ch * PLAN_PITCH;
    asm volatile("ld.shared.v2.b32 {%0,%1}, [%2];" : "=r"(A[4 * ch]), "=r"(A[4 * ch + 1]) : "r"(a) : "memory");
    asm volatile("ld.shared.b32 %0, [%1];" : "=r"(A[4 * ch + 3]) : "r"(a + 8) : "memory");
    A[4 * ch + 2] = A[4 * ch + 1] ^ c.zero;
  }
}

__device__ __forceinline__ void hmma(float (&d)[4], const uint32_t* a, const uint32_t* b, const float (&cc)[4]) {
  asm volatile("mma.sync.aligned.m16n8k16.row.col.f32.bf16.bf16.f32 {%0,%1,%2,%3}, {%4,%5,%6,%7}, {%8,%9}, {%10,%11,%12,%13};"
               : "=f"(d[0]), "=f"(d[1]), "=f"(d[2]), "=f"(d[3])
               : "r"(a[0]), "r"(a[1]), "r"(a[2]), "r"(a[3]), "r"(b[0]), "r"(b[1]), "f"(cc[0]), "f"(cc[1]), "f"(cc[2]), "f"(cc[3]));
}

template <bool MORE>
__device__ __forceinline__ void conv_step(const ConvCtx& c, int s, float (&U)[6][4], float (&V)[6][4], const uint32_t (&B)[6][4],
                                          uint32_t (&A)[24]) {
  float T[6][4];
  if (s >= SIGMA) NB_SYNC(NB_OPEN, 512);
  PIN();
#pragma unroll
  for (int ch = 0; ch < 6; ch++) {
    hmma(T[ch], &A[4 * ch], &B[ch][2], V[ch]);
    hmma(V[ch], &A[4 * ch], &B[ch][0], U[ch]);
  }
  PIN();
  if (s >= SIGMA) NB_ARRIVE(NB_CLOSE, 512);
  uint32_t t[8];
  if (MORE) conv_ldsm(c, s + 1, t);
  if (s >= 3) {
    const int tau = s - 3, owner = tau & 1, slot = (tau >> 1) & 1;
    if (tau >= 4) mbar_wait(c.sb + BAR_CEMPTY + 8 * (2 * owner + slot), ((tau >> 2) - 1) & 1);
    const uint32_t off = (owner == c.rank) ? 0u : c.peer_off;
    const uint32_t dst = c.a_c + off + slot * C_BYTES, bar = c.sb + off + BAR_CFULL + 8 * slot;
#pragma unroll
    for (int q = 0; q < 3; q++) {
      uint32_t p0 = pack_bf16(T[2 * q][1], T[2 * q + 1][1]);
      uint32_t p1 = pack_bf16(T[2 * q][3], T[2 * q + 1][3]);
      asm volatile("st.async.weak.shared::cluster.mbarrier::complete_tx::bytes.v2.b32 [%0], {%1,%2}, [%3];" ::"r"(dst + q * 256),
                   "r"(p0), "r"(p1), "r"(bar)
                   : "memory");
    }
  }
#pragma unroll
  for (int ch = 0; ch < 6; ch++) {
    U[ch][1] = T[ch][0];
    U[ch][3] = T[ch][2];
  }
  if (MORE) conv_stage(c, s + 1, t, A);
}

__device__ __forceinline__ void conv_role(const ConvCtx& c, const __nv_bfloat16* dw) {
  const int lane = threadIdx.x & 31, g = lane >> 2, t = lane & 3;
  uint32_t B[6][4];
  {
    const int e = g & 1, dc = (g >> 1) & 1, ro = g >> 2, rk = t >> 1;
    const uint32_t* dwp = reinterpret_cast<const uint32_t*>(dw) + 24 * c.rank + 3 * c.v;
#pragma unroll
    for (int b = 0; b < 2; b++) {
      const int i = 2 * (2 * e + b) + rk - ro;
      uint32_t w[4][3];
#pragma unroll
      for (int k = 0; k < 4; k++) {
        const int j = 4 * (t & 1) + k - dc;
        const bool ok = i >= 0 && i < 7 && j >= 0 && j < 7;
#pragma unroll
        for (int q = 0; q < 3; q++) w[k][q] = ok ? __ldg(dwp + (i * 7 + j) * 48 + q) : 0u;
      }
#pragma unroll
      for (int q = 0; q < 3; q++) {
        B[2 * q][2 * b] = __byte_perm(w[0][q], w[1][q], 0x5410);
        B[2 * q][2 * b + 1] = __byte_perm(w[2][q], w[3][q], 0x5410);
        B[2 * q + 1][2 * b] = __byte_perm(w[0][q], w[1][q], 0x7632);
        B[2 * q + 1][2 * b + 1] = __byte_perm(w[2][q], w[3][q], 0x7632);
      }
    }
  }
  float U[6][4], V[6][4];
#pragma unroll
  for (int ch = 0; ch < 6; ch++)
#pragma unroll
    for (int k = 0; k < 4; k++) {
      U[ch][k] = __uint_as_float(B[ch][k] & c.zero);
      V[ch][k] = 0.f;
    }
  uint32_t A[24];
  {
    uint32_t tt[8];
    conv_ldsm(c, 0, tt);
    conv_stage(c, 0, tt, A);
  }
#pragma unroll 1
  for (int s = 0; s < NSTEP - 1; s++) conv_step<true>(c, s, U, V, B, A);
  conv_step<false>(c, NSTEP - 1, U, V, B, A);
}

__global__ void __cluster_dims__(2, 1, 1) __launch_bounds__(512, 1)
convnext_kernel(const __grid_constant__ CUtensorMap tm, const __nv_bfloat16* __restrict__ x, const __nv_bfloat16* __restrict__ dw,
                const __nv_bfloat16* __restrict__ w1, const __nv_bfloat16* __restrict__ w2, __nv_bfloat16* __restrict__ out,
                int zero) {
  extern __shared__ __align__(1024) uint8_t smem[];
  const uint32_t sb = (uint32_t)__cvta_generic_to_shared(smem);
  const int tid = threadIdx.x, lane = tid & 31;
  const int wid = __shfl_sync(0xffffffffu, tid >> 5, 0);
  const int rank = blockIdx.x & 1, cl = blockIdx.x >> 1;
  const int c0 = (cl & 15) * 32, r0 = (cl >> 4) * 128;
  const uint32_t peer_off = mapa(sb, rank ^ 1) - sb;

  if (tid == 256) {
    for (int i = 0; i < 4; i++) mbar_init(sb + BAR_RAW + 8 * i, 1);
    for (int i = 0; i < 2; i++) mbar_init(sb + BAR_CFULL + 8 * i, 1);
    for (int i = 0; i < 4; i++) mbar_init(sb + BAR_CEMPTY + 8 * i, 4);
    for (int i = 0; i < 8; i++) mbar_init(sb + BAR_XFULL + 8 * i, 1);
    asm volatile("st.shared.v2.b32 [%0], {%1,%1};" ::"r"(sb + OFF_MAX), "r"(0) : "memory");
    asm volatile("fence.mbarrier_init.release.cluster;" ::: "memory");
    asm volatile("fence.proxy.async.shared::cta;" ::: "memory");
    for (int i = 0; i < 4; i++) {
      mbar_expect(sb + BAR_RAW + 8 * i, RAW_BYTES);
      tma_raw(sb + OFF_RAW + i * RAW_BYTES, &tm, 48 * rank, c0 - 3, r0 - 3 + 2 * i, sb + BAR_RAW + 8 * i);
    }
    for (int i = 0; i < 2; i++) mbar_expect(sb + BAR_CFULL + 8 * i, 12288);
  }
  __syncwarp();
  asm volatile("barrier.cluster.arrive.aligned;\nbarrier.cluster.wait.aligned;" ::: "memory");

  if (wid < 8) {
    MlpCtx m;
    m.sb = sb; m.wg = wid >> 2; m.warp = wid & 3; m.rank = rank; m.peer_off = peer_off;
    m.xsrc = reinterpret_cast<const uint8_t*>(x) + ((size_t)r0 * IMG + c0 + 8 * m.warp) * (CH * 2);
    m.optr = reinterpret_cast<uint8_t*>(out) + ((size_t)r0 * IMG + c0 + 8 * m.warp) * (CH * 2);
    m.unscale = 0;
    mlp_role(m, w1, w2);
  } else {
    ConvCtx c;
    c.sb = sb; c.rank = rank; c.v = wid - 8; c.c0 = c0; c.r0 = r0; c.zero = zero; c.tm = &tm;
    c.peer_off = peer_off;
    const int b = min(4 * c.v + (lane >> 3), 29), cg = b / 10, rb = b % 10;
    c.a_ldsm = sb + OFF_RAW + ((rb / 5) * 38 + (rb % 5) * 8 + (lane & 7)) * 96 + cg * 16;
    c.a_stsm = sb + OFF_PLAN + (cg * 8 + (lane & 7)) * PLAN_PITCH + rb * 16;
    const int g = lane >> 2, t = lane & 3;
    c.a_frag = sb + OFF_PLAN + 6 * c.v * PLAN_PITCH + (t >> 1) * 80 + (g + (t & 1)) * 8;
    const int p0 = 24 * rank + 3 * c.v;
    c.a_c = sb + OFF_C + p0 * 256 + (p0 / 12) * 32 + lane * 8;
    conv_role(c, dw);
  }
  __syncwarp();
  asm volatile("barrier.cluster.arrive.aligned;\nbarrier.cluster.wait.aligned;" ::: "memory");
}

typedef CUresult (*EncodeFn)(CUtensorMap*, CUtensorMapDataType, cuuint32_t, void*, const cuuint64_t*, const cuuint64_t*,
                             const cuuint32_t*, const cuuint32_t*, CUtensorMapInterleave, CUtensorMapSwizzle,
                             CUtensorMapL2promotion, CUtensorMapFloatOOBfill);

}

extern "C" void kernel_launch(void* const* d_in, const int* in_sizes, int n_in, void* d_out, int out_size) {
  const __nv_bfloat16* x = (const __nv_bfloat16*)d_in[0];
  const __nv_bfloat16* dw = (const __nv_bfloat16*)d_in[1];
  const __nv_bfloat16* w1 = (const __nv_bfloat16*)d_in[2];
  const __nv_bfloat16* w2 = (const __nv_bfloat16*)d_in[3];
  __nv_bfloat16* out = (__nv_bfloat16*)d_out;

  static EncodeFn encode = nullptr;
  if (!encode) {
    cudaDriverEntryPointQueryResult st;
    void* fn = nullptr;
    cudaGetDriverEntryPoint("cuTensorMapEncodeTiled", &fn, cudaEnableDefault, &st);
    encode = (EncodeFn)fn;
    cudaFuncSetAttribute(convnext_kernel, cudaFuncAttributeMaxDynamicSharedMemorySize, SMEM_BYTES);
  }
  CUtensorMap tm;
  cuuint64_t dims[3] = {CH, IMG, IMG};
  cuuint64_t strides[2] = {CH * 2, (cuuint64_t)IMG * CH * 2};
  cuuint32_t box[3] = {48, 38, 2};
  cuuint32_t es[3] = {1, 1, 1};
  encode(&tm, CU_TENSOR_MAP_DATA_TYPE_BFLOAT16, 3, (void*)x, dims, strides, box, es, CU_TENSOR_MAP_INTERLEAVE_NONE,
         CU_TENSOR_MAP_SWIZZLE_NONE, CU_TENSOR_MAP_L2_PROMOTION_L2_128B, CU_TENSOR_MAP_FLOAT_OOB_FILL_NONE);
  convnext_kernel<<<128, 512, SMEM_BYTES>>>(tm, x, dw, w1, w2, out, 0);
}
```

```cpp
#include <cuda_runtime.h>
#include <cuda_bf16.h>
#include <cuda.h>
#include <stdint.h>

namespace {

constexpr int IMG = 512, CH = 96;
constexpr int NSTEP = 67;
constexpr int SIGMA = 6;
constexpr int NGATED = NSTEP - SIGMA;

constexpr uint32_t OFF_W1 = 0;
constexpr uint32_t OFF_W2 = 73728;
constexpr uint32_t OFF_RAW = 147456;
constexpr uint32_t RAW_BYTES = 2 * 38 * 96;
constexpr uint32_t OFF_XRES = OFF_RAW + 4 * RAW_BYTES;
constexpr uint32_t OFF_C = OFF_XRES + 12288;
constexpr uint32_t C_BYTES = 12416;
constexpr uint32_t OFF_PLAN = OFF_C + 2 * C_BYTES;
constexpr uint32_t PLAN_PITCH = 176;
constexpr uint32_t PLAN_BYTES = 48 * PLAN_PITCH;
constexpr uint32_t OFF_BAR = OFF_PLAN + 2 * PLAN_BYTES;
constexpr uint32_t BAR_RAW = OFF_BAR;
constexpr uint32_t BAR_CFULL = OFF_BAR + 32;
constexpr uint32_t BAR_CEMPTY = OFF_BAR + 48;
constexpr uint32_t BAR_XFULL = OFF_BAR + 80;
constexpr uint32_t OFF_MAX = OFF_BAR + 144;
constexpr uint32_t SMEM_BYTES = OFF_BAR + 160;

constexpr float GELU_A = 0.32918364f;
constexpr uint32_t GELU_K2 = 0x40d940d9u;

constexpr int NB_OPEN = 1, NB_CLOSE = 2  , NB_PLAN = 4, NB_PREP = 5;
#define REG_MLP 144
constexpr int REG_CONV = 256 - REG_MLP;

#define WG_FENCE() asm volatile("wgmma.fence.sync.aligned;" ::: "memory")
#define WG_COMMIT() asm volatile("wgmma.commit_group.sync.aligned;" ::: "memory")
#define WG_WAIT0() asm volatile("wgmma.wait_group.sync.aligned 0;" ::: "memory")
#define PIN() asm volatile("pmevent 0;" ::: "memory")
#define NB_SYNC(id, n) asm volatile("bar.sync %0, %1;" ::"n"(id), "n"(n) : "memory")
#define NB_ARRIVE(id, n) asm volatile("bar.arrive %0, %1;" ::"n"(id), "n"(n) : "memory")

#define TR(who, idx)
#define TRG(idx)

#define R24(c, d)                                                                                        \
  c(d[0]), c(d[1]), c(d[2]), c(d[3]), c(d[4]), c(d[5]), c(d[6]), c(d[7]), c(d[8]), c(d[9]), c(d[10]),    \
      c(d[11]), c(d[12]), c(d[13]), c(d[14]), c(d[15]), c(d[16]), c(d[17]), c(d[18]), c(d[19]), c(d[20]), \
      c(d[21]), c(d[22]), c(d[23])
#define WG_TXT(sd)                                                                             \
  "wgmma.mma_async.sync.aligned.m64n96k16.f16.f16.f16 "                                        \
  "{%0,%1,%2,%3,%4,%5,%6,%7,%8,%9,%10,%11,%12,%13,%14,%15,%16,%17,%18,%19,%20,%21,%22,%23}, " \
  "{%24,%25,%26,%27}, %28, " sd ", 1, 1, 1;\n"

__device__ __forceinline__ void wg_acc(uint32_t (&d)[24], const uint32_t* a, uint64_t db) {
  asm volatile(WG_TXT("1") : R24("+r", d) : "r"(a[0]), "r"(a[1]), "r"(a[2]), "r"(a[3]), "l"(db));
}
__device__ __forceinline__ void wg_init(uint32_t (&d)[24], const uint32_t* a, uint64_t db) {
  asm volatile(WG_TXT("0") : R24("=r", d) : "r"(a[0]), "r"(a[1]), "r"(a[2]), "r"(a[3]), "l"(db));
}
__device__ __forceinline__ void wg_pred(uint32_t (&d)[24], const uint32_t* a, uint64_t db, int acc) {
  asm volatile("{\n.reg .pred p;\nsetp.ne.b32 p, %29, 0;\n" WG_TXT("p") "}\n"
               : R24("+r", d)
               : "r"(a[0]), "r"(a[1]), "r"(a[2]), "r"(a[3]), "l"(db), "r"(acc));
}
template <int N>
__device__ __forceinline__ void rfence(uint32_t (&d)[N]) {
#pragma unroll
  for (int i = 0; i < N; i++) asm volatile("" : "+r"(d[i])::"memory");
}
template <bool INIT>
__device__ __forceinline__ void gemm6(uint32_t (&d)[24], const uint32_t (&a)[24], uint64_t db) {
#pragma unroll
  for (int k = 0; k < 6; k++) {
    if (INIT && k == 0) wg_init(d, &a[0], db);
    else wg_acc(d, &a[4 * k], db + k * 192);
  }
  WG_COMMIT();
}

__device__ __forceinline__ void gemm6p(uint32_t (&d)[24], const uint32_t (&a)[24], uint64_t db, int acc) {
  wg_pred(d, &a[0], db, acc);
#pragma unroll
  for (int k = 1; k < 6; k++) wg_acc(d, &a[4 * k], db + k * 192);
  WG_COMMIT();
}

__device__ __forceinline__ void mbar_init(uint32_t bar, uint32_t cnt) {
  asm volatile("mbarrier.init.shared::cta.b64 [%0], %1;" ::"r"(bar), "r"(cnt) : "memory");
}
__device__ __forceinline__ void mbar_expect(uint32_t bar, uint32_t bytes) {
  asm volatile("mbarrier.arrive.expect_tx.shared::cta.b64 _, [%0], %1;" ::"r"(bar), "r"(bytes) : "memory");
}
__device__ __forceinline__ void mbar_arrive_cluster(uint32_t bar) {
  asm volatile("mbarrier.arrive.shared::cluster.b64 _, [%0];" ::"r"(bar) : "memory");
}
__device__ __forceinline__ void mbar_wait(uint32_t bar, uint32_t parity) {
  uint32_t ok, n = 0;
  do {
    asm volatile(
        "{\n.reg .pred p;\nmbarrier.try_wait.parity.shared::cta.b64 p, [%1], %2;\nselp.u32 %0, 1, 0, p;\n}\n"
        : "=r"(ok)
        : "r"(bar), "r"(parity)
        : "memory");
    if (++n > (1u << 22)) __trap();
  } while (!ok);
}
__device__ __forceinline__ uint32_t mapa(uint32_t addr, uint32_t rank) {
  uint32_t r;
  asm("mapa.shared::cluster.u32 %0, %1, %2;" : "=r"(r) : "r"(addr), "r"(rank));
  return r;
}
__device__ __forceinline__ void tma_raw(uint32_t dst, const CUtensorMap* tm, int c, int w, int h, uint32_t bar) {
  asm volatile(
      "cp.async.bulk.tensor.3d.shared::cluster.global.mbarrier::complete_tx::bytes [%0], [%1, {%2, %3, %4}], [%5];"
      ::"r"(dst), "l"(tm), "r"(c), "r"(w), "r"(h), "r"(bar)
      : "memory");
}
__device__ __forceinline__ void bulk_load(uint32_t dst, const void* src, uint32_t bytes, uint32_t bar) {
  asm volatile("cp.async.bulk.shared::cluster.global.mbarrier::complete_tx::bytes [%0], [%1], %2, [%3];" ::"r"(dst),
               "l"(src), "r"(bytes), "r"(bar)
               : "memory");
}
__device__ __forceinline__ uint32_t pack_bf16(float lo, float hi) {
  uint32_t r;
  asm("cvt.rn.bf16x2.f32 %0, %1, %2;" : "=r"(r) : "f"(hi), "f"(lo));
  return r;
}
__device__ __forceinline__ uint32_t pack_f16(float lo, float hi) {
  uint32_t r;
  asm("cvt.rn.f16x2.f32 %0, %1, %2;" : "=r"(r) : "f"(hi), "f"(lo));
  return r;
}
__device__ __forceinline__ float bf_lo(uint32_t v) { return __uint_as_float(v << 16); }
__device__ __forceinline__ float bf_hi(uint32_t v) { return __uint_as_float(v & 0xffff0000u); }
__device__ __forceinline__ uint32_t bf_add(uint32_t a, uint32_t b) {
  uint32_t r;
  asm("add.rn.bf16x2 %0, %1, %2;" : "=r"(r) : "r"(a), "r"(b));
  return r;
}
__device__ __forceinline__ uint32_t bf_mul(uint32_t a, uint32_t b) {
  uint32_t r;
  asm("mul.rn.bf16x2 %0, %1, %2;" : "=r"(r) : "r"(a), "r"(b));
  return r;
}
__device__ __forceinline__ uint32_t bf_fma(uint32_t a, uint32_t b, uint32_t c) {
  uint32_t r;
  asm("fma.rn.bf16x2 %0, %1, %2, %3;" : "=r"(r) : "r"(a), "r"(b), "r"(c));
  return r;
}

template <int LO, int HI>
__device__ __forceinline__ void gelu(uint32_t (&o)[24], const uint32_t (&d)[24]) {
#pragma unroll
  for (int q = LO; q < HI; q++) {
    uint32_t t, u;
    asm("fma.rn.f16x2 %0, %1, %1, %2;" : "=r"(t) : "r"(d[q]), "r"(GELU_K2));
    asm("mul.rn.f16x2 %0, %1, %2;" : "=r"(u) : "r"(d[q]), "r"(t));
    asm("tanh.approx.f16x2 %0, %1;" : "=r"(t) : "r"(u));
    asm("fma.rn.f16x2 %0, %1, %2, %1;" : "=r"(o[q]) : "r"(d[q]), "r"(t));
  }
}

__device__ __forceinline__ uint32_t laneid() {
  uint32_t l;
  asm volatile("mov.u32 %0, %%laneid;" : "=r"(l));
  return l;
}

__device__ __forceinline__ bool elect_one() {
  uint32_t p;
  asm volatile("{\n.reg .pred p;\nelect.sync _|p, 0xffffffff;\nselp.u32 %0, 1, 0, p;\n}\n" : "=r"(p));
  return p;
}

struct MlpCtx {
  uint32_t sb;
  uint32_t unscale;
  uint32_t peer_off;
  int wg, warp, rank;
  const uint8_t* xsrc;
  uint8_t* optr;
};

__device__ __forceinline__ void ln_center(const MlpCtx& m, uint32_t (&c)[24], int i) {
  const uint32_t lane = laneid();
  const uint32_t caddr = m.sb + OFF_C + m.wg * C_BYTES + m.warp * 64 + (lane & 3) * (12 * 256 + 32) + (lane >> 2) * 8;
  mbar_wait(m.sb + BAR_CFULL + 8 * m.wg, i & 1);
#pragma unroll
  for (int p = 0; p < 12; p++)
    asm volatile("ld.shared.v2.b32 {%0,%1}, [%2];" : "=r"(c[2 * p]), "=r"(c[2 * p + 1]) : "r"(caddr + p * 256) : "memory");
  float mean[2];
#pragma unroll
  for (int r = 0; r < 2; r++) {
    uint32_t s0 = bf_add(c[r], c[r + 2]), s1 = bf_add(c[r + 4], c[r + 6]), s2 = bf_add(c[r + 8], c[r + 10]);
    uint32_t s3 = bf_add(c[r + 12], c[r + 14]), s4 = bf_add(c[r + 16], c[r + 18]), s5 = bf_add(c[r + 20], c[r + 22]);
    s0 = bf_add(s0, s1); s2 = bf_add(s2, s3); s4 = bf_add(s4, s5);
    s0 = bf_add(bf_add(s0, s2), s4);
    mean[r] = bf_lo(s0) + bf_hi(s0);
  }
#pragma unroll
  for (int r = 0; r < 2; r++) mean[r] += __shfl_xor_sync(0xffffffffu, mean[r], 1);
  if (elect_one()) {
    if (m.warp == 0) mbar_expect(m.sb + BAR_CFULL + 8 * m.wg, 12288);
    uint32_t e = m.sb + BAR_CEMPTY + 8 * (2 * m.rank + m.wg);
    mbar_arrive_cluster(e);
    mbar_arrive_cluster(e + m.peer_off);
  }
#pragma unroll
  for (int r = 0; r < 2; r++) mean[r] += __shfl_xor_sync(0xffffffffu, mean[r], 2);
#pragma unroll
  for (int r = 0; r < 2; r++) {
    float nm = mean[r] * (-1.0f / 96.0f);
    uint32_t nm2 = pack_bf16(nm, nm);
#pragma unroll
    for (int p = 0; p < 12; p++) c[2 * p + r] = bf_add(c[2 * p + r], nm2);
  }
}
__device__ __forceinline__ void ln_rstd(uint32_t (&c)[24], uint32_t (&r2)[2]) {
  float var[2];
#pragma unroll
  for (int r = 0; r < 2; r++) {
    uint32_t q0 = bf_mul(c[r], c[r]), q1 = bf_mul(c[r + 2], c[r + 2]), q2 = bf_mul(c[r + 4], c[r + 4]);
#pragma unroll
    for (int p = 3; p < 12; p += 3) {
      q0 = bf_fma(c[2 * p + r], c[2 * p + r], q0);
      q1 = bf_fma(c[2 * p + 2 + r], c[2 * p + 2 + r], q1);
      q2 = bf_fma(c[2 * p + 4 + r], c[2 * p + 4 + r], q2);
    }
    q0 = bf_add(bf_add(q0, q1), q2);
    var[r] = bf_lo(q0) + bf_hi(q0);
  }
#pragma unroll
  for (int r = 0; r < 2; r++) var[r] += __shfl_xor_sync(0xffffffffu, var[r], 1);
#pragma unroll
  for (int r = 0; r < 2; r++) var[r] += __shfl_xor_sync(0xffffffffu, var[r], 2);
  float rs[2];
#pragma unroll
  for (int r = 0; r < 2; r++) {
    asm("rsqrt.approx.ftz.f32 %0, %1;" : "=f"(rs[r]) : "f"(fmaf(var[r], 1.0f / 96.0f, 1e-5f)));
    rs[r] *= GELU_A;
  }
  if (__builtin_expect(fminf(rs[0], rs[1]) < 0x1p-13f, 0)) {
#pragma unroll
    for (int r = 0; r < 2; r++) {
      uint32_t e = __float_as_uint(rs[r]) & 0x7f800000u;
      uint32_t e2 = (e >> 16) | e;
#pragma unroll
      for (int p = 0; p < 12; p++) asm volatile("mul.rn.bf16x2 %0, %0, %1;" : "+r"(c[2 * p + r]) : "r"(e2));
      rs[r] = __uint_as_float((__float_as_uint(rs[r]) & 0x007fffffu) | 0x3f800000u);
    }
  }
#pragma unroll
  for (int r = 0; r < 2; r++) {
    float rr = rs[r] * 0x1p-112f;
    r2[r] = pack_bf16(rr, rr);
  }
}
__device__ __forceinline__ void ln_final(uint32_t (&a)[24], const uint32_t (&c)[24], const uint32_t (&r2)[2]) {
#pragma unroll
  for (int p = 0; p < 24; p++) {
    uint32_t v = bf_mul(c[p], r2[p & 1]);
    a[p] = (v & 0x7fff7fffu) * 7u + v;
  }
}

__device__ __forceinline__ void issue_xres(const MlpCtx& m, int u, int wg_dst) {
  if (laneid() == 0) {
    uint32_t bar = m.sb + BAR_XFULL + 8 * (4 * wg_dst + m.warp);
    uint32_t dst = m.sb + OFF_XRES + m.warp * 3072;
    const uint8_t* src = m.xsrc + (size_t)(2 * (2 * u + m.rank)) * (IMG * CH * 2);
    mbar_expect(bar, 3072);
    bulk_load(dst, src, 1536, bar);
    bulk_load(dst + 1536, src + IMG * CH * 2, 1536, bar);
  }
}

__device__ __forceinline__ void epilogue(const MlpCtx& m, const uint32_t (&d)[24], int i) {
  const int u = 2 * i + m.wg;
  mbar_wait(m.sb + BAR_XFULL + 8 * (4 * m.wg + m.warp), i & 1);
  const uint32_t lane = laneid();
  const uint32_t row = (lane >> 3) & 1, coff = ((lane >> 4) * 4 + ((lane >> 2) & 1)) * 192 + (lane & 3) * 16;
  const uint32_t xaddr = m.sb + OFF_XRES + m.warp * 3072 + row * 1536 + coff;
  uint8_t* o = m.optr + (size_t)(2 * (2 * u + m.rank)) * (IMG * CH * 2) + (row * (IMG * CH * 2) + coff);
#pragma unroll
  for (int r = 0; r < 2; r++) {
#pragma unroll
    for (int q = 0; q < 3; q++) {
      uint32_t x[4], y[4];
      asm volatile("ld.shared.v4.b32 {%0,%1,%2,%3}, [%4];"
                   : "=r"(x[0]), "=r"(x[1]), "=r"(x[2]), "=r"(x[3])
                   : "r"(xaddr + r * 384 + q * 64)
                   : "memory");
#pragma unroll
      for (int j = 0; j < 4; j++) {
        uint32_t v = d[2 * (4 * q + j) + r];
        float lo, hi;
        asm("{\n.reg .b16 l, h;\nmov.b32 {l, h}, %2;\ncvt.f32.f16 %0, l;\ncvt.f32.f16 %1, h;\n}\n" : "=f"(lo), "=f"(hi) : "r"(v));
        y[j] = bf_fma(pack_bf16(lo, hi), m.unscale, x[j]);
      }
      asm volatile("st.global.v4.b32 [%0], {%1,%2,%3,%4};" ::"l"(o + r * 384 + q * 64), "r"(y[0]), "r"(y[1]), "r"(y[2]), "r"(y[3])
                   : "memory");
    }
  }
  __syncwarp();
  if (u + 1 < 32) issue_xres(m, u + 1, m.wg ^ 1);
}

__device__ __forceinline__ void gate_close(int rho, int wg) {
  if (rho > 0 && rho <= NGATED) {
    if (wg == 0) NB_SYNC(NB_CLOSE, 384);
    else NB_SYNC(NB_CLOSE + 1, 384);
  }
}
__device__ __forceinline__ void gate_open(int rho) {
  if (rho < NGATED) NB_ARRIVE(NB_OPEN, 512);
}

#define GS1 12
#define GS 16

constexpr uint64_t CHK = 1152;

__device__ __forceinline__ void mlp_role(const MlpCtx& m0, const __nv_bfloat16* w1, const __nv_bfloat16* w2) {
  MlpCtx m = m0;
  const int lane = threadIdx.x & 31, wid = m.wg * 4 + m.warp;
  if (m.wg == 0) issue_xres(m, 0, 0);
  {
    uint32_t mx = 0;
    const int k7 = lane & 7;
#pragma unroll 6
    for (int it = 0; it < 18; it++) {
      int item = wid * 18 + it, kb = item / 12, ng = item % 12;
      int ch = 24 * (k7 >> 1) + 2 * kb + (k7 & 1);
      int n8 = ng * 4 + (lane >> 3);
      uint4 v = __ldg(reinterpret_cast<const uint4*>(w1 + ch * 384 + n8 * 8));
      mx = __vmaxu2(mx, __vmaxu2(__vmaxu2(v.x & 0x7fff7fffu, v.y & 0x7fff7fffu), __vmaxu2(v.z & 0x7fff7fffu, v.w & 0x7fff7fffu)));
      uint32_t dst = m.sb + OFF_W1 + ((n8 / 12) * 6 + (kb >> 1)) * 3072 + (kb & 1) * 128 + (n8 % 12) * 256 + k7 * 16;
      asm volatile("st.shared.v4.b32 [%0], {%1,%2,%3,%4};" ::"r"(dst), "r"(pack_f16(bf_lo(v.x), bf_hi(v.x))),
                   "r"(pack_f16(bf_lo(v.y), bf_hi(v.y))), "r"(pack_f16(bf_lo(v.z), bf_hi(v.z))),
                   "r"(pack_f16(bf_lo(v.w), bf_hi(v.w)))
                   : "memory");
    }
    TR(m.wg, 1004);
    uint32_t v2[5][16];
    uint32_t mx2 = 0;
#pragma unroll
    for (int it = 0; it < 5; it++) {
      int item = (it * 8 + wid) * 4 + (lane >> 3);
      if (item > 143) item = 143;
      int kb = item / 3, q = item % 3;
      const uint4* src = reinterpret_cast<const uint4*>(w2 + (kb * 8 + k7) * 96 + q * 32);
#pragma unroll
      for (int t = 0; t < 4; t++) {
        uint4 v = __ldg(src + t);
        v2[it][4 * t] = v.x; v2[it][4 * t + 1] = v.y; v2[it][4 * t + 2] = v.z; v2[it][4 * t + 3] = v.w;
      }
    }
#pragma unroll
    for (int it = 0; it < 5; it++)
#pragma unroll
      for (int t = 0; t < 16; t++) mx2 = __vmaxu2(mx2, v2[it][t] & 0x7fff7fffu);
    TR(m.wg, 1005);
    mx = __reduce_max_sync(0xffffffffu, max(mx & 0xffffu, mx >> 16));
    mx2 = __reduce_max_sync(0xffffffffu, max(mx2 & 0xffffu, mx2 >> 16));
    if (lane == 0) {
      asm volatile("red.shared.max.u32 [%0], %1;" ::"r"(m.sb + OFF_MAX), "r"(mx) : "memory");
      asm volatile("red.shared.max.u32 [%0], %1;" ::"r"(m.sb + OFF_MAX + 4), "r"(mx2) : "memory");
    }
    NB_SYNC(NB_PREP, 256);
    asm volatile("ld.shared.v2.b32 {%0,%1}, [%2];" : "=r"(mx), "=r"(mx2) : "r"(m.sb + OFF_MAX) : "memory");
    TR(m.wg, 1006);
    int e1 = (int)(mx >> 7) - 126, e2 = (int)(mx2 >> 7) - 126;
    int s = min(-1 - e1 - e2, 14 - e2);
    s = max(-120, min(120, s));
    float sc = __uint_as_float((uint32_t)(127 + s) << 23) * (0.5f / GELU_A);
    m.unscale = __shfl_sync(0xffffffffu, ((uint32_t)(127 - s) << 7) * 0x10001u, 0);
#pragma unroll
    for (int it = 0; it < 5; it++) {
      int item = (it * 8 + wid) * 4 + (lane >> 3);
      if (item > 143) item = 143;
      int kb = item / 3, q = item % 3;
      uint32_t dst = m.sb + OFF_W2 + (kb >> 1) * 3072 + (kb & 1) * 128 + q * 1024 + k7 * 16;
#pragma unroll
      for (int j = 0; j < 4; j++) {
        uint32_t o[4];
#pragma unroll
        for (int t = 0; t < 4; t++) o[t] = pack_f16(bf_lo(v2[it][4 * t + j]) * sc, bf_hi(v2[it][4 * t + j]) * sc);
        asm volatile("st.shared.v4.b32 [%0], {%1,%2,%3,%4};" ::"r"(dst + j * 256), "r"(o[0]), "r"(o[1]), "r"(o[2]), "r"(o[3]) : "memory");
      }
    }
    asm volatile("fence.proxy.async.shared::cta;" ::: "memory");
    NB_SYNC(NB_PREP, 256);
  }
  const uint64_t dW1 = (uint64_t)(((m.sb + OFF_W1) & 0x3FFFF) >> 4) | ((uint64_t)8 << 16) | ((uint64_t)16 << 32);
  const uint64_t dW2 = dW1 + (OFF_W2 >> 4);

  TR(m.wg, 1000);
  int rho = 0;
  for (; rho < 2 * m.wg + m.rank; rho++) { gate_close(rho, m.wg); gate_open(rho); }

  uint32_t A1[24], g[24], d[24], cn[24], r2[2];
  {
    uint32_t d0[24];
    ln_center(m, cn, 0);
    ln_rstd(cn, r2);
    ln_final(A1, cn, r2);
    WG_FENCE();
    gate_close(rho, m.wg);
    gemm6<true>(d0, A1, dW1);
    gate_open(rho++); PIN();
    PIN(); WG_WAIT0(); rfence(d0);
    WG_FENCE();
    gate_close(rho, m.wg);
    gemm6<true>(d, A1, dW1 + CHK);
    gate_open(rho++); PIN();
    gelu<0, 24>(g, d0);
    PIN(); WG_WAIT0(); rfence(d);
  }
  uint32_t D2[24];
#pragma unroll
  for (int k = 0; k < 24; k++) D2[k] = 0;
#pragma unroll 1
  for (int h = 0; h < 31; h++) {
    const int odd = h & 1;
    const uint64_t w2d = dW2 + odd * 2 * CHK, w1d = dW1 + (odd ^ 1) * 2 * CHK;
    uint32_t g1[24], d2[24];
    WG_FENCE();
    gate_close(rho, m.wg);
    TR(m.wg, rho * 8);
    gemm6p(D2, g, w2d, odd); PIN();
    TR(m.wg, rho * 8 + 1);
    if (odd) ln_final(A1, cn, r2);
    gelu<0, GS1>(g1, d);
    TR(m.wg, rho * 8 + 2);
    PIN(); WG_WAIT0(); rfence(D2);
    WG_FENCE();
    TR(m.wg, rho * 8 + 3);
    gemm6<true>(d2, A1, w1d);
    gate_open(rho++); PIN();
    TR(m.wg, rho * 8 - 4);
    gelu<GS1, 24>(g1, d);
    if (!odd && h < 30) ln_center(m, cn, (h >> 1) + 1);
    TR(m.wg, rho * 8 - 3);
    PIN(); WG_WAIT0(); rfence(d2);
    TR(m.wg, rho * 8 - 2);

    WG_FENCE();
    gate_close(rho, m.wg);
    TR(m.wg, rho * 8);
    gemm6<false>(D2, g1, w2d + CHK); PIN();
    TR(m.wg, rho * 8 + 1);
    gelu<0, GS>(g, d2);
    TR(m.wg, rho * 8 + 2);
    PIN(); WG_WAIT0(); rfence(D2);
    WG_FENCE();
    TR(m.wg, rho * 8 + 3);
    gemm6<true>(d, A1, w1d + CHK);
    gate_open(rho++); PIN();
    TR(m.wg, rho * 8 - 4);
    gelu<GS, 24>(g, d2);
    if (odd) epilogue(m, D2, h >> 1);
    else ln_rstd(cn, r2);
    TR(m.wg, rho * 8 - 3);
    PIN(); WG_WAIT0(); rfence(d);
    TR(m.wg, rho * 8 - 2);
  }
  {
    uint32_t g1[24];
    WG_FENCE();
    gemm6<false>(D2, g, dW2 + 2 * CHK); PIN();
    gelu<0, 24>(g1, d);
    PIN(); WG_WAIT0(); rfence(D2);
    WG_FENCE();
    gemm6<false>(D2, g1, dW2 + 3 * CHK);
    WG_WAIT0(); rfence(D2);
    epilogue(m, D2, 15);
    TR(m.wg, 1001);
    TRG(1021);
  }
}

struct ConvCtx {
  uint32_t sb;
  uint32_t a_ldsm, a_stsm, a_frag, a_c;
  uint32_t peer_off;
  int rank, v, c0, r0, zero;
  const CUtensorMap* tm;
};

__device__ __forceinline__ void conv_ldsm(const ConvCtx& c, int s, uint32_t (&t)[8]) {
  const int st = s & 3;
  mbar_wait(c.sb + BAR_RAW + 8 * st, (s >> 2) & 1);
#pragma unroll
  for (int h = 0; h < 2; h++)
    asm volatile("ldmatrix.sync.aligned.m8n8.x4.trans.shared.b16 {%0,%1,%2,%3}, [%4];"
                 : "=r"(t[4 * h]), "=r"(t[4 * h + 1]), "=r"(t[4 * h + 2]), "=r"(t[4 * h + 3])
                 : "r"(c.a_ldsm + st * RAW_BYTES + h * 48)
                 : "memory");
}
__device__ __forceinline__ void conv_stage(const ConvCtx& c, int s, const uint32_t (&t)[8], uint32_t (&A)[24]) {
  const int st = s & 3;
  const uint32_t pl = (s & 1) * PLAN_BYTES;
#pragma unroll
  for (int h = 0; h < 2; h++)
    asm volatile("stmatrix.sync.aligned.m8n8.x4.shared.b16 [%0], {%1,%2,%3,%4};" ::"r"(c.a_stsm + pl + h * 24 * PLAN_PITCH),
                 "r"(t[4 * h]), "r"(t[4 * h + 1]), "r"(t[4 * h + 2]), "r"(t[4 * h + 3])
                 : "memory");
  NB_SYNC(NB_PLAN, 256);
  TR(2 + (c.v >> 2), s * 8 + 5);
  if (c.v == 0 && s + 4 < NSTEP && elect_one()) {
    mbar_expect(c.sb + BAR_RAW + 8 * st, RAW_BYTES);
    tma_raw(c.sb + OFF_RAW + st * RAW_BYTES, c.tm, 48 * c.rank, c.c0 - 3, c.r0 - 3 + 2 * (s + 4), c.sb + BAR_RAW + 8 * st);
  }
#pragma unroll
  for (int ch = 0; ch < 6; ch++) {
    uint32_t a = c.a_frag + pl + ch * PLAN_PITCH;
    asm volatile("ld.shared.v2.b32 {%0,%1}, [%2];" : "=r"(A[4 * ch]), "=r"(A[4 * ch + 1]) : "r"(a) : "memory");
    asm volatile("ld.shared.b32 %0, [%1];" : "=r"(A[4 * ch + 3]) : "r"(a + 8) : "memory");
    A[4 * ch + 2] = A[4 * ch + 1] ^ c.zero;
  }
}

__device__ __forceinline__ void hmma(float (&d)[4], const uint32_t* a, const uint32_t* b, const float (&cc)[4]) {
  asm volatile("mma.sync.aligned.m16n8k16.row.col.f32.bf16.bf16.f32 {%0,%1,%2,%3}, {%4,%5,%6,%7}, {%8,%9}, {%10,%11,%12,%13};"
               : "=f"(d[0]), "=f"(d[1]), "=f"(d[2]), "=f"(d[3])
               : "r"(a[0]), "r"(a[1]), "r"(a[2]), "r"(a[3]), "r"(b[0]), "r"(b[1]), "f"(cc[0]), "f"(cc[1]), "f"(cc[2]), "f"(cc[3]));
}

template <bool MORE>
__device__ __forceinline__ void conv_step(const ConvCtx& c, int s, float (&U)[6][4], float (&V)[6][4], const uint32_t (&B)[6][4],
                                          uint32_t (&A)[24]) {
  float T[6][4];
  TR(2 + (c.v >> 2), s * 8);
  if (s >= SIGMA) NB_SYNC(NB_OPEN, 512);
  PIN();
  TR(2 + (c.v >> 2), s * 8 + 1);
#pragma unroll
  for (int ch = 0; ch < 6; ch++) {
    hmma(T[ch], &A[4 * ch], &B[ch][2], V[ch]);
    hmma(V[ch], &A[4 * ch], &B[ch][0], U[ch]);
  }
  PIN();
  if (s >= SIGMA) { NB_ARRIVE(NB_CLOSE, 384); NB_ARRIVE(NB_CLOSE + 1, 384); }
  TR(2 + (c.v >> 2), s * 8 + 2);
  uint32_t t[8], pk[6];
#pragma unroll
  for (int q = 0; q < 3; q++) {
    pk[2 * q] = pack_bf16(T[2 * q][1], T[2 * q + 1][1]);
    pk[2 * q + 1] = pack_bf16(T[2 * q][3], T[2 * q + 1][3]);
  }
#pragma unroll
  for (int ch = 0; ch < 6; ch++) {
    U[ch][1] = __uint_as_float(__float_as_uint(T[ch][0]) ^ c.zero);
    U[ch][3] = __uint_as_float(__float_as_uint(T[ch][2]) ^ c.zero);
  }
  PIN();
  if (MORE) conv_ldsm(c, s + 1, t);
  TR(2 + (c.v >> 2), s * 8 + 3);
  if (s >= 3) {
    const int tau = s - 3, owner = tau & 1, slot = (tau >> 1) & 1;
    if (tau >= 4) mbar_wait(c.sb + BAR_CEMPTY + 8 * (2 * owner + slot), ((tau >> 2) - 1) & 1);
    const uint32_t off = (owner == c.rank) ? 0u : c.peer_off;
    const uint32_t dst = c.a_c + off + slot * C_BYTES, bar = c.sb + off + BAR_CFULL + 8 * slot;
#pragma unroll
    for (int q = 0; q < 3; q++)
      asm volatile("st.async.weak.shared::cluster.mbarrier::complete_tx::bytes.v2.b32 [%0], {%1,%2}, [%3];" ::"r"(dst + q * 256),
                   "r"(pk[2 * q]), "r"(pk[2 * q + 1]), "r"(bar)
                   : "memory");
  }
  TR(2 + (c.v >> 2), s * 8 + 4);
  if (MORE) conv_stage(c, s + 1, t, A);
}

__device__ __forceinline__ void conv_role(const ConvCtx& c, const __nv_bfloat16* dw) {
  const int lane = threadIdx.x & 31, g = lane >> 2, t = lane & 3;
  uint32_t B[6][4];
  {
    const int e = g & 1, dc = (g >> 1) & 1, ro = g >> 2, rk = t >> 1;
    const uint32_t* dwp = reinterpret_cast<const uint32_t*>(dw) + 24 * c.rank + 3 * c.v;
#pragma unroll
    for (int b = 0; b < 2; b++) {
      const int i = 2 * (2 * e + b) + rk - ro;
      uint32_t w[4][3];
#pragma unroll
      for (int k = 0; k < 4; k++) {
        const int j = 4 * (t & 1) + k - dc;
        const bool ok = i >= 0 && i < 7 && j >= 0 && j < 7;
#pragma unroll
        for (int q = 0; q < 3; q++) w[k][q] = ok ? __ldg(dwp + (i * 7 + j) * 48 + q) : 0u;
      }
#pragma unroll
      for (int q = 0; q < 3; q++) {
        B[2 * q][2 * b] = __byte_perm(w[0][q], w[1][q], 0x5410);
        B[2 * q][2 * b + 1] = __byte_perm(w[2][q], w[3][q], 0x5410);
        B[2 * q + 1][2 * b] = __byte_perm(w[0][q], w[1][q], 0x7632);
        B[2 * q + 1][2 * b + 1] = __byte_perm(w[2][q], w[3][q], 0x7632);
      }
    }
  }
  TR(2 + (c.v >> 2), 1004);
  float U[6][4], V[6][4];
#pragma unroll
  for (int ch = 0; ch < 6; ch++)
#pragma unroll
    for (int k = 0; k < 4; k++) {
      U[ch][k] = __uint_as_float(B[ch][k] & c.zero);
      V[ch][k] = 0.f;
    }
  uint32_t A[24];
  {
    uint32_t tt[8];
    conv_ldsm(c, 0, tt);
    TR(2 + (c.v >> 2), 1005);
    conv_stage(c, 0, tt, A);
  }
#pragma unroll 1
  for (int s = 0; s < NSTEP - 1; s++) conv_step<true>(c, s, U, V, B, A);
  conv_step<false>(c, NSTEP - 1, U, V, B, A);
}

__global__ void __cluster_dims__(2, 1, 1) __launch_bounds__(512, 1)
convnext_kernel(const __grid_constant__ CUtensorMap tm, const __nv_bfloat16* __restrict__ x, const __nv_bfloat16* __restrict__ dw,
                const __nv_bfloat16* __restrict__ w1, const __nv_bfloat16* __restrict__ w2, __nv_bfloat16* __restrict__ out,
                int zero) {
  extern __shared__ __align__(1024) uint8_t smem[];
  const uint32_t sb = (uint32_t)__cvta_generic_to_shared(smem);
  const int tid = threadIdx.x, lane = tid & 31;
  const int wid = __shfl_sync(0xffffffffu, tid >> 5, 0);
  const int rank = blockIdx.x & 1, cl = blockIdx.x >> 1;
  const int c0 = (cl & 15) * 32, r0 = (cl >> 4) * 128;
  const uint32_t peer_off = mapa(sb, rank ^ 1) - sb;

  TR(wid >> 2, 1002);
  TRG(1020);
  if (tid == 256) {
    for (int i = 0; i < 4; i++) mbar_init(sb + BAR_RAW + 8 * i, 1);
    for (int i = 0; i < 2; i++) mbar_init(sb + BAR_CFULL + 8 * i, 1);
    for (int i = 0; i < 4; i++) mbar_init(sb + BAR_CEMPTY + 8 * i, 4);
    for (int i = 0; i < 8; i++) mbar_init(sb + BAR_XFULL + 8 * i, 1);
    asm volatile("st.shared.v2.b32 [%0], {%1,%1};" ::"r"(sb + OFF_MAX), "r"(0) : "memory");
    asm volatile("fence.mbarrier_init.release.cluster;" ::: "memory");
    asm volatile("fence.proxy.async.shared::cta;" ::: "memory");
    TR(2, 1006);
    for (int i = 0; i < 4; i++) {
      mbar_expect(sb + BAR_RAW + 8 * i, RAW_BYTES);
      tma_raw(sb + OFF_RAW + i * RAW_BYTES, &tm, 48 * rank, c0 - 3, r0 - 3 + 2 * i, sb + BAR_RAW + 8 * i);
    }
    for (int i = 0; i < 2; i++) mbar_expect(sb + BAR_CFULL + 8 * i, 12288);
    TR(2, 1007);
  }
  __syncwarp();
  asm volatile("barrier.cluster.arrive.aligned;\nbarrier.cluster.wait.aligned;" ::: "memory");

  TR(wid >> 2, 1003);
  if (wid < 8) {
    MlpCtx m;
    m.sb = sb; m.wg = wid >> 2; m.warp = wid & 3; m.rank = rank; m.peer_off = peer_off;
    m.xsrc = reinterpret_cast<const uint8_t*>(x) + ((size_t)r0 * IMG + c0 + 8 * m.warp) * (CH * 2);
    m.optr = reinterpret_cast<uint8_t*>(out) + ((size_t)r0 * IMG + c0 + 8 * m.warp) * (CH * 2);
    m.unscale = 0;
    asm volatile("setmaxnreg.inc.sync.aligned.u32 %0;" ::"n"(REG_MLP));
    mlp_role(m, w1, w2);
  } else {
    ConvCtx c;
    c.sb = sb; c.rank = rank; c.v = wid - 8; c.c0 = c0; c.r0 = r0; c.zero = zero; c.tm = &tm;
    c.peer_off = peer_off;
    const int b = min(4 * c.v + (lane >> 3), 29), cg = b / 10, rb = b % 10;
    c.a_ldsm = sb + OFF_RAW + ((rb / 5) * 38 + (rb % 5) * 8 + (lane & 7)) * 96 + cg * 16;
    c.a_stsm = sb + OFF_PLAN + (cg * 8 + (lane & 7)) * PLAN_PITCH + rb * 16;
    const int g = lane >> 2, t = lane & 3;
    c.a_frag = sb + OFF_PLAN + 6 * c.v * PLAN_PITCH + (t >> 1) * 80 + (g + (t & 1)) * 8;
    const int p0 = 24 * rank + 3 * c.v;
    c.a_c = sb + OFF_C + p0 * 256 + (p0 / 12) * 32 + lane * 8;
    asm volatile("setmaxnreg.dec.sync.aligned.u32 %0;" ::"n"(REG_CONV));
    conv_role(c, dw);
  }
  __syncwarp();
  asm volatile("barrier.cluster.arrive.relaxed.aligned;\nbarrier.cluster.wait.aligned;" ::: "memory");
}

typedef CUresult (*EncodeFn)(CUtensorMap*, CUtensorMapDataType, cuuint32_t, void*, const cuuint64_t*, const cuuint64_t*,
                             const cuuint32_t*, const cuuint32_t*, CUtensorMapInterleave, CUtensorMapSwizzle,
                             CUtensorMapL2promotion, CUtensorMapFloatOOBfill);

}

extern "C" void kernel_launch(void* const* d_in, const int* in_sizes, int n_in, void* d_out, int out_size) {
  const __nv_bfloat16* x = (const __nv_bfloat16*)d_in[0];
  const __nv_bfloat16* dw = (const __nv_bfloat16*)d_in[1];
  const __nv_bfloat16* w1 = (const __nv_bfloat16*)d_in[2];
  const __nv_bfloat16* w2 = (const __nv_bfloat16*)d_in[3];
  __nv_bfloat16* out = (__nv_bfloat16*)d_out;

  static EncodeFn encode = nullptr;
  if (!encode) {
    cudaDriverEntryPointQueryResult st;
    void* fn = nullptr;
    cudaGetDriverEntryPoint("cuTensorMapEncodeTiled", &fn, cudaEnableDefault, &st);
    encode = (EncodeFn)fn;
    cudaFuncSetAttribute(convnext_kernel, cudaFuncAttributeMaxDynamicSharedMemorySize, SMEM_BYTES);
  }
  CUtensorMap tm;
  cuuint64_t dims[3] = {CH, IMG, IMG};
  cuuint64_t strides[2] = {CH * 2, (cuuint64_t)IMG * CH * 2};
  cuuint32_t box[3] = {48, 38, 2};
  cuuint32_t es[3] = {1, 1, 1};
  encode(&tm, CU_TENSOR_MAP_DATA_TYPE_BFLOAT16, 3, (void*)x, dims, strides, box, es, CU_TENSOR_MAP_INTERLEAVE_NONE,
         CU_TENSOR_MAP_SWIZZLE_NONE, CU_TENSOR_MAP_L2_PROMOTION_L2_128B, CU_TENSOR_MAP_FLOAT_OOB_FILL_NONE);
  convnext_kernel<<<128, 512, SMEM_BYTES>>>(tm, x, dw, w1, w2, out, 0);
}
```

```cpp
#include <cuda_runtime.h>
#include <cuda_bf16.h>
#include <cuda.h>
#include <stdint.h>

namespace {

constexpr int IMG = 512, CH = 96;
constexpr int NSTEP = 67;
constexpr int SIGMA = 8;
constexpr int NROUND = 67;

constexpr uint32_t OFF_W1 = 0;
constexpr uint32_t OFF_W2 = 73728;
constexpr uint32_t OFF_RAW = 147456;
constexpr uint32_t RAW_BYTES = 2 * 38 * 96;
constexpr uint32_t OFF_XRES = OFF_RAW + 4 * RAW_BYTES;
constexpr uint32_t OFF_C = OFF_XRES + 12288;
constexpr uint32_t C_BYTES = 12416;
constexpr uint32_t OFF_PLAN = OFF_C + 2 * C_BYTES;
constexpr uint32_t PLAN_PITCH = 176;
constexpr uint32_t PLAN_BYTES = 48 * PLAN_PITCH;
constexpr uint32_t OFF_BAR = OFF_PLAN + 2 * PLAN_BYTES;
constexpr uint32_t BAR_RAW = OFF_BAR;
constexpr uint32_t BAR_CFULL = OFF_BAR + 32;
constexpr uint32_t BAR_CEMPTY = OFF_BAR + 48;
constexpr uint32_t BAR_XFULL = OFF_BAR + 80;
constexpr uint32_t OFF_MAX = OFF_BAR + 144;
constexpr uint32_t SMEM_BYTES = OFF_BAR + 160;

constexpr float GELU_A = 0.32918364f;
constexpr uint32_t GELU_K2 = 0x40d940d9u;

constexpr int NB_TOK = 1, NB_PLAN = 4, NB_PREP = 5;
#define REG_MLP 144
constexpr int REG_CONV = 256 - REG_MLP;

#define WG_FENCE() asm volatile("wgmma.fence.sync.aligned;" ::: "memory")
#define WG_COMMIT() asm volatile("wgmma.commit_group.sync.aligned;" ::: "memory")
#define WG_WAIT0() asm volatile("wgmma.wait_group.sync.aligned 0;" ::: "memory")
#define WG_WAIT1() asm volatile("wgmma.wait_group.sync.aligned 1;" ::: "memory")
#define PIN() asm volatile("pmevent 0;" ::: "memory")
#define NB_SYNC(id, n) asm volatile("bar.sync %0, %1;" ::"n"(id), "n"(n) : "memory")
#define NB_ARRIVE(id, n) asm volatile("bar.arrive %0, %1;" ::"n"(id), "n"(n) : "memory")

#define TR(who, idx)
#define TRG(idx)

#define R24(c, d)                                                                                        \
  c(d[0]), c(d[1]), c(d[2]), c(d[3]), c(d[4]), c(d[5]), c(d[6]), c(d[7]), c(d[8]), c(d[9]), c(d[10]),    \
      c(d[11]), c(d[12]), c(d[13]), c(d[14]), c(d[15]), c(d[16]), c(d[17]), c(d[18]), c(d[19]), c(d[20]), \
      c(d[21]), c(d[22]), c(d[23])
#define WG_TXT(sd)                                                                             \
  "wgmma.mma_async.sync.aligned.m64n96k16.f16.f16.f16 "                                        \
  "{%0,%1,%2,%3,%4,%5,%6,%7,%8,%9,%10,%11,%12,%13,%14,%15,%16,%17,%18,%19,%20,%21,%22,%23}, " \
  "{%24,%25,%26,%27}, %28, " sd ", 1, 1, 1;\n"

__device__ __forceinline__ void wg_acc(uint32_t (&d)[24], const uint32_t* a, uint64_t db) {
  asm volatile(WG_TXT("1") : R24("+r", d) : "r"(a[0]), "r"(a[1]), "r"(a[2]), "r"(a[3]), "l"(db));
}
__device__ __forceinline__ void wg_init(uint32_t (&d)[24], const uint32_t* a, uint64_t db) {
  asm volatile(WG_TXT("0") : R24("=r", d) : "r"(a[0]), "r"(a[1]), "r"(a[2]), "r"(a[3]), "l"(db));
}
template <int N>
__device__ __forceinline__ void rfence(uint32_t (&d)[N]) {
#pragma unroll
  for (int i = 0; i < N; i++) asm volatile("" : "+r"(d[i])::"memory");
}
template <bool INIT>
__device__ __forceinline__ void gemm6(uint32_t (&d)[24], const uint32_t (&a)[24], uint64_t db) {
#pragma unroll
  for (int k = 0; k < 6; k++) {
    if (INIT && k == 0) wg_init(d, &a[0], db);
    else wg_acc(d, &a[4 * k], db + k * 192);
  }
  WG_COMMIT();
}

__device__ __forceinline__ void mbar_init(uint32_t bar, uint32_t cnt) {
  asm volatile("mbarrier.init.shared::cta.b64 [%0], %1;" ::"r"(bar), "r"(cnt) : "memory");
}
__device__ __forceinline__ void mbar_expect(uint32_t bar, uint32_t bytes) {
  asm volatile("mbarrier.arrive.expect_tx.shared::cta.b64 _, [%0], %1;" ::"r"(bar), "r"(bytes) : "memory");
}
__device__ __forceinline__ void mbar_arrive_cluster(uint32_t bar) {
  asm volatile("mbarrier.arrive.shared::cluster.b64 _, [%0];" ::"r"(bar) : "memory");
}
__device__ __forceinline__ bool mbar_try(uint32_t bar, uint32_t parity) {
  uint32_t ok;
  asm volatile(
      "{\n.reg .pred p;\nmbarrier.try_wait.parity.shared::cta.b64 p, [%1], %2;\nselp.u32 %0, 1, 0, p;\n}\n"
      : "=r"(ok)
      : "r"(bar), "r"(parity)
      : "memory");
  return ok;
}
__device__ __forceinline__ void mbar_wait(uint32_t bar, uint32_t parity) {
  if (__builtin_expect(mbar_try(bar, parity), 1)) return;
  for (uint32_t n = 0; !mbar_try(bar, parity);)
    if (++n > (1u << 22)) __trap();
}
__device__ __forceinline__ uint32_t mapa(uint32_t addr, uint32_t rank) {
  uint32_t r;
  asm("mapa.shared::cluster.u32 %0, %1, %2;" : "=r"(r) : "r"(addr), "r"(rank));
  return r;
}
__device__ __forceinline__ void tma_raw(uint32_t dst, const CUtensorMap* tm, int c, int w, int h, uint32_t bar) {
  asm volatile(
      "cp.async.bulk.tensor.3d.shared::cluster.global.mbarrier::complete_tx::bytes [%0], [%1, {%2, %3, %4}], [%5];"
      ::"r"(dst), "l"(tm), "r"(c), "r"(w), "r"(h), "r"(bar)
      : "memory");
}
__device__ __forceinline__ void bulk_load(uint32_t dst, const void* src, uint32_t bytes, uint32_t bar) {
  asm volatile("cp.async.bulk.shared::cluster.global.mbarrier::complete_tx::bytes [%0], [%1], %2, [%3];" ::"r"(dst),
               "l"(src), "r"(bytes), "r"(bar)
               : "memory");
}
__device__ __forceinline__ uint32_t pack_bf16(float lo, float hi) {
  uint32_t r;
  asm("cvt.rn.bf16x2.f32 %0, %1, %2;" : "=r"(r) : "f"(hi), "f"(lo));
  return r;
}
__device__ __forceinline__ uint32_t pack_f16(float lo, float hi) {
  uint32_t r;
  asm("cvt.rn.f16x2.f32 %0, %1, %2;" : "=r"(r) : "f"(hi), "f"(lo));
  return r;
}
__device__ __forceinline__ float bf_lo(uint32_t v) { return __uint_as_float(v << 16); }
__device__ __forceinline__ float bf_hi(uint32_t v) { return __uint_as_float(v & 0xffff0000u); }
__device__ __forceinline__ uint32_t bf_add(uint32_t a, uint32_t b) {
  uint32_t r;
  asm("add.rn.bf16x2 %0, %1, %2;" : "=r"(r) : "r"(a), "r"(b));
  return r;
}
__device__ __forceinline__ uint32_t bf_mul(uint32_t a, uint32_t b) {
  uint32_t r;
  asm("mul.rn.bf16x2 %0, %1, %2;" : "=r"(r) : "r"(a), "r"(b));
  return r;
}
__device__ __forceinline__ uint32_t bf_fma(uint32_t a, uint32_t b, uint32_t c) {
  uint32_t r;
  asm("fma.rn.bf16x2 %0, %1, %2, %3;" : "=r"(r) : "r"(a), "r"(b), "r"(c));
  return r;
}

template <int LO, int HI>
__device__ __forceinline__ void gelu(uint32_t (&o)[24], const uint32_t (&d)[24]) {
#pragma unroll
  for (int q = LO; q < HI; q++) {
    uint32_t t, u;
    asm("fma.rn.f16x2 %0, %1, %1, %2;" : "=r"(t) : "r"(d[q]), "r"(GELU_K2));
    asm("mul.rn.f16x2 %0, %1, %2;" : "=r"(u) : "r"(d[q]), "r"(t));
    asm("tanh.approx.f16x2 %0, %1;" : "=r"(t) : "r"(u));
    asm("fma.rn.f16x2 %0, %1, %2, %1;" : "=r"(o[q]) : "r"(d[q]), "r"(t));
  }
}

__device__ __forceinline__ uint32_t laneid() {
  uint32_t l;
  asm volatile("mov.u32 %0, %%laneid;" : "=r"(l));
  return l;
}

__device__ __forceinline__ bool elect_one() {
  uint32_t p;
  asm volatile("{\n.reg .pred p;\nelect.sync _|p, 0xffffffff;\nselp.u32 %0, 1, 0, p;\n}\n" : "=r"(p));
  return p;
}

struct MlpCtx {
  uint32_t sb;
  uint32_t caddr;
  uint32_t ooff;
  uint32_t unscale;
  uint32_t peer_off;
  int wg, warp, rank;
  const uint8_t* xsrc;
  uint8_t* optr;
};

__device__ __forceinline__ void ln_load(const MlpCtx& m, uint32_t (&c)[24], int i) {
  mbar_wait(m.sb + BAR_CFULL + 8 * m.wg, i & 1);
#pragma unroll
  for (int p = 0; p < 12; p++)
    asm volatile("ld.shared.v2.b32 {%0,%1}, [%2];" : "=r"(c[2 * p]), "=r"(c[2 * p + 1]) : "r"(m.caddr + p * 256) : "memory");
}
__device__ __forceinline__ void ln_shfl(float (&st)[4], int mask) {
  st[2] = __shfl_xor_sync(0xffffffffu, st[0], mask);
  st[3] = __shfl_xor_sync(0xffffffffu, st[1], mask);
}
__device__ __forceinline__ void ln_sum(const uint32_t (&c)[24], float (&st)[4]) {
#pragma unroll
  for (int r = 0; r < 2; r++) {
    uint32_t s0 = bf_add(c[r], c[r + 2]), s1 = bf_add(c[r + 4], c[r + 6]), s2 = bf_add(c[r + 8], c[r + 10]);
    uint32_t s3 = bf_add(c[r + 12], c[r + 14]), s4 = bf_add(c[r + 16], c[r + 18]), s5 = bf_add(c[r + 20], c[r + 22]);
    s0 = bf_add(s0, s1); s2 = bf_add(s2, s3); s4 = bf_add(s4, s5);
    s0 = bf_add(bf_add(s0, s2), s4);
    st[r] = bf_lo(s0) + bf_hi(s0);
  }
  ln_shfl(st, 1);
}
__device__ __forceinline__ void ln_release(const MlpCtx& m) {
  const uint32_t e = m.sb + BAR_CEMPTY + 8 * (2 * m.rank + m.wg);
  asm volatile(
      "{\n.reg .pred p, q;\nelect.sync _|p, 0xffffffff;\nsetp.eq.and.s32 q, %3, 0, p;\n"
      "@q mbarrier.arrive.expect_tx.shared::cta.b64 _, [%0], 12288;\n"
      "@p mbarrier.arrive.shared::cluster.b64 _, [%1];\n"
      "@p mbarrier.arrive.shared::cluster.b64 _, [%2];\n}\n" ::"r"(m.sb + BAR_CFULL + 8 * m.wg),
      "r"(e), "r"(e + m.peer_off), "r"(m.warp)
      : "memory");
}
__device__ __forceinline__ void ln_hop(float (&st)[4]) {
  st[0] += st[2]; st[1] += st[3];
  ln_shfl(st, 2);
}
__device__ __forceinline__ void ln_center(uint32_t (&c)[24], float (&st)[4], float (&dl)[2]) {
#pragma unroll
  for (int r = 0; r < 2; r++) {
    float nm = (st[r] + st[r + 2]) * (-1.0f / 96.0f);
    uint32_t nm2 = pack_bf16(nm, nm);
    dl[r] = nm - bf_hi(nm2);
#pragma unroll
    for (int p = 0; p < 12; p++) c[2 * p + r] = bf_add(c[2 * p + r], nm2);
    uint32_t q0 = bf_mul(c[r], c[r]), q1 = bf_mul(c[r + 2], c[r + 2]);
#pragma unroll
    for (int p = 2; p < 12; p += 2) {
      q0 = bf_fma(c[2 * p + r], c[2 * p + r], q0);
      q1 = bf_fma(c[2 * p + 2 + r], c[2 * p + 2 + r], q1);
    }
    q0 = bf_add(q0, q1);
    st[r] = bf_lo(q0) + bf_hi(q0);
  }
  ln_shfl(st, 1);
}
__device__ __forceinline__ void ln_rstd(uint32_t (&c)[24], float (&st)[4], float (&dl)[2]) {
#pragma unroll
  for (int r = 0; r < 2; r++) {
    asm("rsqrt.approx.ftz.f32 %0, %1;" : "=f"(st[r]) : "f"(fmaf(st[r] + st[r + 2], 1.0f / 96.0f, 1e-5f)));
    dl[r] *= st[r];
  }
  if (__builtin_expect(fminf(st[0], st[1]) < 0x1p-11f, 0)) {
#pragma unroll
    for (int r = 0; r < 2; r++) {
      uint32_t e = __float_as_uint(st[r]) & 0x7f800000u;
      uint32_t e2 = (e >> 16) | e;
#pragma unroll
      for (int p = 0; p < 12; p++) asm volatile("mul.rn.bf16x2 %0, %0, %1;" : "+r"(c[2 * p + r]) : "r"(e2));
      st[r] = __uint_as_float((__float_as_uint(st[r]) & 0x007fffffu) | 0x3f800000u);
    }
  }
}
__device__ __forceinline__ void ln_scale(uint32_t (&c)[24], const float (&st)[4], const float (&dl)[2]) {
#pragma unroll
  for (int r = 0; r < 2; r++) {
    float rr = st[r] * (GELU_A * 0x1p-112f), dd = dl[r] * (GELU_A * 0x1p-112f);
    uint32_t r2 = pack_bf16(rr, rr), d2 = pack_bf16(dd, dd);
#pragma unroll
    for (int p = 0; p < 12; p++) c[2 * p + r] = bf_fma(c[2 * p + r], r2, d2);
  }
}
__device__ __forceinline__ void ln_final(uint32_t (&a)[24], const uint32_t (&c)[24]) {
#pragma unroll
  for (int p = 0; p < 24; p++) a[p] = (c[p] & 0x7fff7fffu) * 7u + c[p];
}

__device__ __forceinline__ void issue_xres(const MlpCtx& m, int u, int wg_dst) {
  if (elect_one()) {
    uint32_t bar = m.sb + BAR_XFULL + 8 * (4 * wg_dst + m.warp);
    uint32_t dst = m.sb + OFF_XRES + m.warp * 3072;
    const uint8_t* src = m.xsrc + (size_t)(2 * (2 * u + m.rank)) * (IMG * CH * 2);
    mbar_expect(bar, 3072);
    bulk_load(dst, src, 1536, bar);
    bulk_load(dst + 1536, src + IMG * CH * 2, 1536, bar);
  }
}
__device__ __forceinline__ void x_load(const MlpCtx& m, uint32_t (&x)[24], int i) {
  const uint32_t xaddr = m.sb + OFF_XRES + m.warp * 3072 + (m.ooff >= IMG * CH * 2 ? m.ooff - (IMG * CH * 2 - 1536) : m.ooff);
  mbar_wait(m.sb + BAR_XFULL + 8 * (4 * m.wg + m.warp), i & 1);
#pragma unroll
  for (int k = 0; k < 6; k++)
    asm volatile("ld.shared.v4.b32 {%0,%1,%2,%3}, [%4];"
                 : "=r"(x[4 * k]), "=r"(x[4 * k + 1]), "=r"(x[4 * k + 2]), "=r"(x[4 * k + 3])
                 : "r"(xaddr + (k / 3) * 384 + (k % 3) * 64)
                 : "memory");
}
__device__ __forceinline__ void epilogue(const MlpCtx& m, const uint32_t (&d)[24], uint32_t (&x)[24], int i) {
  const int u = 2 * i + m.wg;
  uint8_t* o = m.optr + ((uint32_t)(2 * (2 * u + m.rank)) * (IMG * CH * 2) + m.ooff);
#pragma unroll
  for (int r = 0; r < 2; r++) {
#pragma unroll
    for (int q = 0; q < 3; q++) {
      uint32_t* y = &x[12 * r + 4 * q];
#pragma unroll
      for (int j = 0; j < 4; j++) {
        uint32_t v = d[2 * (4 * q + j) + r];
        float lo, hi;
        asm("{\n.reg .b16 l, h;\nmov.b32 {l, h}, %2;\ncvt.f32.f16 %0, l;\ncvt.f32.f16 %1, h;\n}\n" : "=f"(lo), "=f"(hi) : "r"(v));
        asm("fma.rn.bf16x2 %0, %1, %2, %0;" : "+r"(y[j]) : "r"(pack_bf16(lo, hi)), "r"(m.unscale));
      }
      asm volatile("st.global.v4.b32 [%0], {%1,%2,%3,%4};" ::"l"(o + r * 384 + q * 64), "r"(y[0]), "r"(y[1]), "r"(y[2]), "r"(y[3])
                   : "memory");
    }
  }
}

__device__ __forceinline__ void tok_wait(int wg) {
  asm volatile("{\n.reg .pred p;\nsetp.eq.s32 p, %0, 0;\n@p bar.sync %1, 384;\n@!p bar.sync %2, 256;\n}\n" ::"r"(wg), "n"(NB_TOK), "n"(NB_TOK + 1) : "memory");
}
__device__ __forceinline__ void tok_pass(int wg) {
  asm volatile("{\n.reg .pred p;\nsetp.eq.s32 p, %0, 0;\n@p bar.arrive %1, 256;\n@!p bar.arrive %2, 384;\n}\n" ::"r"(wg), "n"(NB_TOK + 1), "n"(NB_TOK + 2) : "memory");
}

constexpr uint64_t CHK = 1152;

__device__ __forceinline__ void mlp_role(const MlpCtx& m0, const __nv_bfloat16* w1, const __nv_bfloat16* w2) {
  MlpCtx m = m0;
  const int lane = threadIdx.x & 31, wid = m.wg * 4 + m.warp;
  if (m.wg == 0) issue_xres(m, 0, 0);
  {
    uint32_t mx = 0;
    const int k7 = lane & 7;
#pragma unroll 6
    for (int it = 0; it < 18; it++) {
      int item = wid * 18 + it, kb = item / 12, ng = item % 12;
      int ch = 24 * (k7 >> 1) + 2 * kb + (k7 & 1);
      int n8 = ng * 4 + (lane >> 3);
      uint4 v = __ldg(reinterpret_cast<const uint4*>(w1 + ch * 384 + n8 * 8));
      mx = __vmaxu2(mx, __vmaxu2(__vmaxu2(v.x & 0x7fff7fffu, v.y & 0x7fff7fffu), __vmaxu2(v.z & 0x7fff7fffu, v.w & 0x7fff7fffu)));
      uint32_t dst = m.sb + OFF_W1 + ((n8 / 12) * 6 + (kb >> 1)) * 3072 + (kb & 1) * 128 + (n8 % 12) * 256 + k7 * 16;
      asm volatile("st.shared.v4.b32 [%0], {%1,%2,%3,%4};" ::"r"(dst), "r"(pack_f16(bf_lo(v.x), bf_hi(v.x))),
                   "r"(pack_f16(bf_lo(v.y), bf_hi(v.y))), "r"(pack_f16(bf_lo(v.z), bf_hi(v.z))),
                   "r"(pack_f16(bf_lo(v.w), bf_hi(v.w)))
                   : "memory");
    }
    TR(m.wg, 1004);
    uint32_t v2[5][16];
    uint32_t mx2 = 0;
#pragma unroll
    for (int it = 0; it < 5; it++) {
      int item = (it * 8 + wid) * 4 + (lane >> 3);
      if (item > 143) item = 143;
      int kb = item / 3, q = item % 3;
      const uint4* src = reinterpret_cast<const uint4*>(w2 + (kb * 8 + k7) * 96 + q * 32);
#pragma unroll
      for (int t = 0; t < 4; t++) {
        uint4 v = __ldg(src + t);
        v2[it][4 * t] = v.x; v2[it][4 * t + 1] = v.y; v2[it][4 * t + 2] = v.z; v2[it][4 * t + 3] = v.w;
      }
    }
#pragma unroll
    for (int it = 0; it < 5; it++)
#pragma unroll
      for (int t = 0; t < 16; t++) mx2 = __vmaxu2(mx2, v2[it][t] & 0x7fff7fffu);
    TR(m.wg, 1005);
    mx = __reduce_max_sync(0xffffffffu, max(mx & 0xffffu, mx >> 16));
    mx2 = __reduce_max_sync(0xffffffffu, max(mx2 & 0xffffu, mx2 >> 16));
    if (lane == 0) {
      asm volatile("red.shared.max.u32 [%0], %1;" ::"r"(m.sb + OFF_MAX), "r"(mx) : "memory");
      asm volatile("red.shared.max.u32 [%0], %1;" ::"r"(m.sb + OFF_MAX + 4), "r"(mx2) : "memory");
    }
    NB_SYNC(NB_PREP, 256);
    asm volatile("ld.shared.v2.b32 {%0,%1}, [%2];" : "=r"(mx), "=r"(mx2) : "r"(m.sb + OFF_MAX) : "memory");
    TR(m.wg, 1006);
    int e1 = (int)(mx >> 7) - 126, e2 = (int)(mx2 >> 7) - 126;
    int s = min(-1 - e1 - e2, 14 - e2);
    s = max(-120, min(120, s));
    float sc = __uint_as_float((uint32_t)(127 + s) << 23) * (0.5f / GELU_A);
    m.unscale = __shfl_sync(0xffffffffu, ((uint32_t)(127 - s) << 7) * 0x10001u, 0);
#pragma unroll
    for (int it = 0; it < 5; it++) {
      int item = (it * 8 + wid) * 4 + (lane >> 3);
      if (item > 143) item = 143;
      int kb = item / 3, q = item % 3;
      uint32_t dst = m.sb + OFF_W2 + (kb >> 1) * 3072 + (kb & 1) * 128 + q * 1024 + k7 * 16;
#pragma unroll
      for (int j = 0; j < 4; j++) {
        uint32_t o[4];
#pragma unroll
        for (int t = 0; t < 4; t++) o[t] = pack_f16(bf_lo(v2[it][4 * t + j]) * sc, bf_hi(v2[it][4 * t + j]) * sc);
        asm volatile("st.shared.v4.b32 [%0], {%1,%2,%3,%4};" ::"r"(dst + j * 256), "r"(o[0]), "r"(o[1]), "r"(o[2]), "r"(o[3]) : "memory");
      }
    }
    asm volatile("fence.proxy.async.shared::cta;" ::: "memory");
    NB_SYNC(NB_PREP, 256);
  }
  const uint64_t dW1 = (uint64_t)(((m.sb + OFF_W1) & 0x3FFFF) >> 4) | ((uint64_t)8 << 16) | ((uint64_t)16 << 32);
  const uint64_t dW2 = dW1 + (OFF_W2 >> 4);

  TR(m.wg, 1000);
  uint32_t A1[24], g[24], cn[24], D2[24];
  float st[4], dl[2];
  ln_load(m, cn, 0);
  ln_sum(cn, st);
  ln_release(m);
  ln_hop(st);
  ln_center(cn, st, dl);
  ln_hop(st);
  ln_rstd(cn, st, dl);
  ln_scale(cn, st, dl);
  ln_final(A1, cn);
  [[maybe_unused]] int rho = 2 * m.wg + m.rank;
  for (int r = 0; r < 2 * m.wg + m.rank; r++) { tok_wait(m.wg); tok_pass(m.wg); }
  {
    uint32_t d[24];
    WG_FENCE();
    tok_wait(m.wg);
    gemm6<true>(d, A1, dW1);
    tok_pass(m.wg); PIN();
    WG_WAIT0(); rfence(d);
    gelu<0, 24>(g, d);
    PIN();
    rho++;
  }
#define SLOT(INIT, j2, j1)                  \
  uint32_t d[24];                           \
  WG_FENCE();                               \
  tok_wait(m.wg);                           \
  TR(m.wg, rho * 8);                        \
  gemm6<INIT>(D2, g, dW2 + (j2) * CHK);     \
  WG_FENCE();                               \
  gemm6<true>(d, A1, dW1 + (j1) * CHK);     \
  tok_pass(m.wg); PIN();                    \
  TR(m.wg, rho * 8 + 1);
#define SLOT_END()                          \
  TR(m.wg, rho * 8 + 2);                    \
  PIN(); WG_WAIT0(); rfence(d); rfence(D2); \
  TR(m.wg, rho * 8 + 3);
#define ROUND_END()                         \
  TR(m.wg, rho * 8 + 4);                    \
  PIN(); rho++;
#pragma unroll 1
  for (int i = 0;; i++) {
    {
      SLOT(true, 0, 1)
      if (i < 15) {
        ln_load(m, cn, i + 1);
        ln_sum(cn, st);
        ln_release(m);
        ln_hop(st);
      }
      SLOT_END()
      gelu<0, 24>(g, d);
      ROUND_END()
    }
    {
      SLOT(false, 1, 2)
      ln_center(cn, st, dl);
      ln_hop(st);
      SLOT_END()
      gelu<0, 24>(g, d);
      ROUND_END()
    }
    {
      SLOT(false, 2, 3)
      ln_rstd(cn, st, dl);
      ln_scale(cn, st, dl);
      SLOT_END()
      gelu<0, 24>(g, d);
      ln_final(A1, cn);
      ROUND_END()
    }
    if (i == 15) break;
    {
      SLOT(false, 3, 0)
      x_load(m, cn, i);
      WG_WAIT1(); rfence(D2);
      epilogue(m, D2, cn, i);
      issue_xres(m, 2 * i + m.wg + 1, m.wg ^ 1);
      SLOT_END()
      gelu<0, 24>(g, d);
      ROUND_END()
    }
  }
  WG_FENCE();
  tok_wait(m.wg);
  gemm6<false>(D2, g, dW2 + 3 * CHK);
  tok_pass(m.wg); PIN();
  x_load(m, cn, 15);
  WG_WAIT0(); rfence(D2);
  epilogue(m, D2, cn, 15);
  if (m.wg == 0) {
    issue_xres(m, 31, 1);
    for (int r = 0; r < 2; r++) { tok_wait(0); tok_pass(0); }
  }
  TR(m.wg, 1001);
  TRG(1021);
}

struct ConvCtx {
  uint32_t sb;
  uint32_t a_ldsm, a_stsm, a_frag, a_c;
  uint32_t peer_off;
  int rank, v, c0, r0, zero;
  const CUtensorMap* tm;
};

__device__ __forceinline__ void conv_ldsm(const ConvCtx& c, int s, uint32_t (&t)[8]) {
  const int st = s & 3;
  mbar_wait(c.sb + BAR_RAW + 8 * st, (s >> 2) & 1);
#pragma unroll
  for (int h = 0; h < 2; h++)
    asm volatile("ldmatrix.sync.aligned.m8n8.x4.trans.shared.b16 {%0,%1,%2,%3}, [%4];"
                 : "=r"(t[4 * h]), "=r"(t[4 * h + 1]), "=r"(t[4 * h + 2]), "=r"(t[4 * h + 3])
                 : "r"(c.a_ldsm + st * RAW_BYTES + h * 48)
                 : "memory");
}
__device__ __forceinline__ void conv_stage(const ConvCtx& c, int s, const uint32_t (&t)[8], uint32_t (&A)[24]) {
  const int st = s & 3;
  const uint32_t pl = (s & 1) * PLAN_BYTES;
#pragma unroll
  for (int h = 0; h < 2; h++)
    asm volatile("stmatrix.sync.aligned.m8n8.x4.shared.b16 [%0], {%1,%2,%3,%4};" ::"r"(c.a_stsm + pl + h * 24 * PLAN_PITCH),
                 "r"(t[4 * h]), "r"(t[4 * h + 1]), "r"(t[4 * h + 2]), "r"(t[4 * h + 3])
                 : "memory");
  NB_SYNC(NB_PLAN, 256);
  TR(2 + (c.v >> 2), s * 8 + 5);
  if (c.v == 0 && s + 4 < NSTEP && elect_one()) {
    mbar_expect(c.sb + BAR_RAW + 8 * st, RAW_BYTES);
    tma_raw(c.sb + OFF_RAW + st * RAW_BYTES, c.tm, 48 * c.rank, c.c0 - 3, c.r0 - 3 + 2 * (s + 4), c.sb + BAR_RAW + 8 * st);
  }
#pragma unroll
  for (int ch = 0; ch < 6; ch++) {
    uint32_t a = c.a_frag + pl + ch * PLAN_PITCH;
    asm volatile("ld.shared.v2.b32 {%0,%1}, [%2];" : "=r"(A[4 * ch]), "=r"(A[4 * ch + 1]) : "r"(a) : "memory");
    asm volatile("ld.shared.b32 %0, [%1];" : "=r"(A[4 * ch + 3]) : "r"(a + 8) : "memory");
    A[4 * ch + 2] = A[4 * ch + 1] ^ c.zero;
  }
}

__device__ __forceinline__ void hmma(float (&d)[4], const uint32_t* a, const uint32_t* b, const float (&cc)[4]) {
  asm volatile("mma.sync.aligned.m16n8k16.row.col.f32.bf16.bf16.f32 {%0,%1,%2,%3}, {%4,%5,%6,%7}, {%8,%9}, {%10,%11,%12,%13};"
               : "=f"(d[0]), "=f"(d[1]), "=f"(d[2]), "=f"(d[3])
               : "r"(a[0]), "r"(a[1]), "r"(a[2]), "r"(a[3]), "r"(b[0]), "r"(b[1]), "f"(cc[0]), "f"(cc[1]), "f"(cc[2]), "f"(cc[3]));
}

template <bool MORE>
__device__ __forceinline__ void conv_step(const ConvCtx& c, int s, float (&U)[6][4], float (&V)[6][4], const uint32_t (&B)[6][4],
                                          uint32_t (&A)[24]) {
  float T[6][4];
  TR(2 + (c.v >> 2), s * 8);
  if (s >= SIGMA) NB_SYNC(NB_TOK + 2, 384);
  PIN();
  TR(2 + (c.v >> 2), s * 8 + 1);
#pragma unroll
  for (int ch = 0; ch < 6; ch++) {
    hmma(T[ch], &A[4 * ch], &B[ch][2], V[ch]);
    hmma(V[ch], &A[4 * ch], &B[ch][0], U[ch]);
  }
  PIN();
  if (s >= SIGMA) NB_ARRIVE(NB_TOK, 384);
  TR(2 + (c.v >> 2), s * 8 + 2);
  uint32_t t[8], pk[6];
#pragma unroll
  for (int q = 0; q < 3; q++) {
    pk[2 * q] = pack_bf16(T[2 * q][1], T[2 * q + 1][1]);
    pk[2 * q + 1] = pack_bf16(T[2 * q][3], T[2 * q + 1][3]);
  }
#pragma unroll
  for (int ch = 0; ch < 6; ch++) {
    U[ch][1] = __uint_as_float(__float_as_uint(T[ch][0]) ^ c.zero);
    U[ch][3] = __uint_as_float(__float_as_uint(T[ch][2]) ^ c.zero);
  }
  PIN();
  if (MORE) conv_ldsm(c, s + 1, t);
  TR(2 + (c.v >> 2), s * 8 + 3);
  if (s >= 3) {
    const int tau = s - 3, owner = tau & 1, slot = (tau >> 1) & 1;
    if (tau >= 4) mbar_wait(c.sb + BAR_CEMPTY + 8 * (2 * owner + slot), ((tau >> 2) - 1) & 1);
    const uint32_t off = (owner == c.rank) ? 0u : c.peer_off;
    const uint32_t dst = c.a_c + off + slot * C_BYTES, bar = c.sb + off + BAR_CFULL + 8 * slot;
#pragma unroll
    for (int q = 0; q < 3; q++)
      asm volatile("st.async.weak.shared::cluster.mbarrier::complete_tx::bytes.v2.b32 [%0], {%1,%2}, [%3];" ::"r"(dst + q * 256),
                   "r"(pk[2 * q]), "r"(pk[2 * q + 1]), "r"(bar)
                   : "memory");
  }
  TR(2 + (c.v >> 2), s * 8 + 4);
  if (MORE) conv_stage(c, s + 1, t, A);
}

__device__ __forceinline__ void conv_role(const ConvCtx& c, const __nv_bfloat16* dw) {
  const int lane = threadIdx.x & 31, g = lane >> 2, t = lane & 3;
  uint32_t B[6][4];
  {
    const int e = g & 1, dc = (g >> 1) & 1, ro = g >> 2, rk = t >> 1;
    const uint32_t* dwp = reinterpret_cast<const uint32_t*>(dw) + 24 * c.rank + 3 * c.v;
#pragma unroll
    for (int b = 0; b < 2; b++) {
      const int i = 2 * (2 * e + b) + rk - ro;
      uint32_t w[4][3];
#pragma unroll
      for (int k = 0; k < 4; k++) {
        const int j = 4 * (t & 1) + k - dc;
        const bool ok = i >= 0 && i < 7 && j >= 0 && j < 7;
#pragma unroll
        for (int q = 0; q < 3; q++) w[k][q] = ok ? __ldg(dwp + (i * 7 + j) * 48 + q) : 0u;
      }
#pragma unroll
      for (int q = 0; q < 3; q++) {
        B[2 * q][2 * b] = __byte_perm(w[0][q], w[1][q], 0x5410);
        B[2 * q][2 * b + 1] = __byte_perm(w[2][q], w[3][q], 0x5410);
        B[2 * q + 1][2 * b] = __byte_perm(w[0][q], w[1][q], 0x7632);
        B[2 * q + 1][2 * b + 1] = __byte_perm(w[2][q], w[3][q], 0x7632);
      }
    }
  }
  TR(2 + (c.v >> 2), 1004);
  float U[6][4], V[6][4];
#pragma unroll
  for (int ch = 0; ch < 6; ch++)
#pragma unroll
    for (int k = 0; k < 4; k++) {
      U[ch][k] = __uint_as_float(B[ch][k] & c.zero);
      V[ch][k] = 0.f;
    }
  uint32_t A[24];
  {
    uint32_t tt[8];
    conv_ldsm(c, 0, tt);
    TR(2 + (c.v >> 2), 1005);
    conv_stage(c, 0, tt, A);
  }
  NB_ARRIVE(NB_TOK, 384);
#pragma unroll 1
  for (int s = 0; s < NSTEP - 1; s++) conv_step<true>(c, s, U, V, B, A);
  conv_step<false>(c, NSTEP - 1, U, V, B, A);
  for (int r = NSTEP - SIGMA; r < NROUND - 1 + c.rank; r++) { NB_SYNC(NB_TOK + 2, 384); NB_ARRIVE(NB_TOK, 384); }
  NB_SYNC(NB_TOK + 2, 384);
}

__global__ void __cluster_dims__(2, 1, 1) __launch_bounds__(512, 1)
convnext_kernel(const __grid_constant__ CUtensorMap tm, const __nv_bfloat16* __restrict__ x, const __nv_bfloat16* __restrict__ dw,
                const __nv_bfloat16* __restrict__ w1, const __nv_bfloat16* __restrict__ w2, __nv_bfloat16* __restrict__ out,
                int zero) {
  extern __shared__ __align__(1024) uint8_t smem[];
  const uint32_t sb = (uint32_t)__cvta_generic_to_shared(smem);
  const int tid = threadIdx.x, lane = tid & 31;
  const int wid = __shfl_sync(0xffffffffu, tid >> 5, 0);
  const int rank = blockIdx.x & 1, cl = blockIdx.x >> 1;
  const int c0 = (cl & 15) * 32, r0 = (cl >> 4) * 128;
  const uint32_t peer_off = mapa(sb, rank ^ 1) - sb;

  TR(wid >> 2, 1002);
  TRG(1020);
  if (tid == 256) {
    for (int i = 0; i < 4; i++) mbar_init(sb + BAR_RAW + 8 * i, 1);
    for (int i = 0; i < 2; i++) mbar_init(sb + BAR_CFULL + 8 * i, 1);
    for (int i = 0; i < 4; i++) mbar_init(sb + BAR_CEMPTY + 8 * i, 4);
    for (int i = 0; i < 8; i++) mbar_init(sb + BAR_XFULL + 8 * i, 1);
    asm volatile("st.shared.v2.b32 [%0], {%1,%1};" ::"r"(sb + OFF_MAX), "r"(0) : "memory");
    asm volatile("fence.mbarrier_init.release.cluster;" ::: "memory");
    asm volatile("fence.proxy.async.shared::cta;" ::: "memory");
    TR(2, 1006);
    for (int i = 0; i < 4; i++) {
      mbar_expect(sb + BAR_RAW + 8 * i, RAW_BYTES);
      tma_raw(sb + OFF_RAW + i * RAW_BYTES, &tm, 48 * rank, c0 - 3, r0 - 3 + 2 * i, sb + BAR_RAW + 8 * i);
    }
    for (int i = 0; i < 2; i++) mbar_expect(sb + BAR_CFULL + 8 * i, 12288);
    TR(2, 1007);
  }
  __syncwarp();
  asm volatile("barrier.cluster.arrive.aligned;\nbarrier.cluster.wait.aligned;" ::: "memory");

  TR(wid >> 2, 1003);
  if (wid < 8) {
    MlpCtx m;
    m.sb = sb; m.wg = wid >> 2; m.warp = wid & 3; m.rank = rank; m.peer_off = peer_off;
    m.xsrc = reinterpret_cast<const uint8_t*>(x) + ((size_t)r0 * IMG + c0 + 8 * m.warp) * (CH * 2);
    m.optr = reinterpret_cast<uint8_t*>(out) + ((size_t)r0 * IMG + c0 + 8 * m.warp) * (CH * 2);
    m.caddr = sb + OFF_C + m.wg * C_BYTES + m.warp * 64 + (lane & 3) * (12 * 256 + 32) + (lane >> 2) * 8;
    m.ooff = ((lane >> 3) & 1) * (IMG * CH * 2) + ((lane >> 4) * 4 + ((lane >> 2) & 1)) * 192 + (lane & 3) * 16;
    m.unscale = 0;
    asm volatile("setmaxnreg.inc.sync.aligned.u32 %0;" ::"n"(REG_MLP));
    mlp_role(m, w1, w2);
  } else {
    ConvCtx c;
    c.sb = sb; c.rank = rank; c.v = wid - 8; c.c0 = c0; c.r0 = r0; c.zero = zero; c.tm = &tm;
    c.peer_off = peer_off;
    const int b = min(4 * c.v + (lane >> 3), 29), cg = b / 10, rb = b % 10;
    c.a_ldsm = sb + OFF_RAW + ((rb / 5) * 38 + (rb % 5) * 8 + (lane & 7)) * 96 + cg * 16;
    c.a_stsm = sb + OFF_PLAN + (cg * 8 + (lane & 7)) * PLAN_PITCH + rb * 16;
    const int g = lane >> 2, t = lane & 3;
    c.a_frag = sb + OFF_PLAN + 6 * c.v * PLAN_PITCH + (t >> 1) * 80 + (g + (t & 1)) * 8;
    const int p0 = 24 * rank + 3 * c.v;
    c.a_c = sb + OFF_C + p0 * 256 + (p0 / 12) * 32 + lane * 8;
    asm volatile("setmaxnreg.dec.sync.aligned.u32 %0;" ::"n"(REG_CONV));
    conv_role(c, dw);
  }
  __syncwarp();
  asm volatile("barrier.cluster.arrive.relaxed.aligned;\nbarrier.cluster.wait.aligned;" ::: "memory");
}

typedef CUresult (*EncodeFn)(CUtensorMap*, CUtensorMapDataType, cuuint32_t, void*, const cuuint64_t*, const cuuint64_t*,
                             const cuuint32_t*, const cuuint32_t*, CUtensorMapInterleave, CUtensorMapSwizzle,
                             CUtensorMapL2promotion, CUtensorMapFloatOOBfill);

}

extern "C" void kernel_launch(void* const* d_in, const int* in_sizes, int n_in, void* d_out, int out_size) {
  const __nv_bfloat16* x = (const __nv_bfloat16*)d_in[0];
  const __nv_bfloat16* dw = (const __nv_bfloat16*)d_in[1];
  const __nv_bfloat16* w1 = (const __nv_bfloat16*)d_in[2];
  const __nv_bfloat16* w2 = (const __nv_bfloat16*)d_in[3];
  __nv_bfloat16* out = (__nv_bfloat16*)d_out;

  static EncodeFn encode = nullptr;
  if (!encode) {
    cudaDriverEntryPointQueryResult st;
    void* fn = nullptr;
    cudaGetDriverEntryPoint("cuTensorMapEncodeTiled", &fn, cudaEnableDefault, &st);
    encode = (EncodeFn)fn;
    cudaFuncSetAttribute(convnext_kernel, cudaFuncAttributeMaxDynamicSharedMemorySize, SMEM_BYTES);
  }
  CUtensorMap tm;
  cuuint64_t dims[3] = {CH, IMG, IMG};
  cuuint64_t strides[2] = {CH * 2, (cuuint64_t)IMG * CH * 2};
  cuuint32_t box[3] = {48, 38, 2};
  cuuint32_t es[3] = {1, 1, 1};
  encode(&tm, CU_TENSOR_MAP_DATA_TYPE_BFLOAT16, 3, (void*)x, dims, strides, box, es, CU_TENSOR_MAP_INTERLEAVE_NONE,
         CU_TENSOR_MAP_SWIZZLE_NONE, CU_TENSOR_MAP_L2_PROMOTION_L2_128B, CU_TENSOR_MAP_FLOAT_OOB_FILL_NONE);
  convnext_kernel<<<128, 512, SMEM_BYTES>>>(tm, x, dw, w1, w2, out, 0);
}
```

```cpp
#include <cuda_runtime.h>
#include <cuda_bf16.h>
#include <cuda.h>
#include <stdint.h>

namespace {

constexpr int IMG = 512, CH = 96;
constexpr int NSTEP = 67;
constexpr int SIGMA = 7;
constexpr int NROUND = 67;

constexpr uint32_t OFF_W1 = 0;
constexpr uint32_t OFF_W2 = 73728;
constexpr uint32_t OFF_RAW = 147456;
constexpr uint32_t RAW_BYTES = 2 * 38 * 96;
constexpr uint32_t OFF_XRES = OFF_RAW + 4 * RAW_BYTES;
constexpr uint32_t OFF_C = OFF_XRES + 12288;
constexpr uint32_t C_BYTES = 12416;
constexpr uint32_t OFF_PLAN = OFF_C + 2 * C_BYTES;
constexpr uint32_t PLAN_PITCH = 176;
constexpr uint32_t PLAN_BYTES = 48 * PLAN_PITCH;
constexpr uint32_t OFF_BAR = OFF_PLAN + 2 * PLAN_BYTES;
constexpr uint32_t BAR_RAW = OFF_BAR;
constexpr uint32_t BAR_CFULL = OFF_BAR + 32;
constexpr uint32_t BAR_CEMPTY = OFF_BAR + 48;
constexpr uint32_t BAR_XFULL = OFF_BAR + 80;
constexpr uint32_t OFF_MAX = OFF_BAR + 144;
constexpr uint32_t SMEM_BYTES = OFF_BAR + 160;

constexpr float GELU_A = 0.32918364f;
constexpr uint32_t GELU_K2 = 0x40d940d9u;

constexpr int NB_TOK = 1, NB_PLAN = 4, NB_PREP = 5;
#define REG_MLP 144
constexpr int REG_CONV = 256 - REG_MLP;

#define WG_FENCE() asm volatile("wgmma.fence.sync.aligned;" ::: "memory")
#define WG_COMMIT() asm volatile("wgmma.commit_group.sync.aligned;" ::: "memory")
#define WG_WAIT0() asm volatile("wgmma.wait_group.sync.aligned 0;" ::: "memory")
#define WG_WAIT1() asm volatile("wgmma.wait_group.sync.aligned 1;" ::: "memory")
#define PIN() asm volatile("pmevent 0;" ::: "memory")
#define NB_SYNC(id, n) asm volatile("bar.sync %0, %1;" ::"n"(id), "n"(n) : "memory")
#define NB_ARRIVE(id, n) asm volatile("bar.arrive %0, %1;" ::"n"(id), "n"(n) : "memory")

#define TR(who, idx)
#define TRG(idx)

#define R24(c, d)                                                                                        \
  c(d[0]), c(d[1]), c(d[2]), c(d[3]), c(d[4]), c(d[5]), c(d[6]), c(d[7]), c(d[8]), c(d[9]), c(d[10]),    \
      c(d[11]), c(d[12]), c(d[13]), c(d[14]), c(d[15]), c(d[16]), c(d[17]), c(d[18]), c(d[19]), c(d[20]), \
      c(d[21]), c(d[22]), c(d[23])
#define WG_TXT(sd)                                                                             \
  "wgmma.mma_async.sync.aligned.m64n96k16.f16.f16.f16 "                                        \
  "{%0,%1,%2,%3,%4,%5,%6,%7,%8,%9,%10,%11,%12,%13,%14,%15,%16,%17,%18,%19,%20,%21,%22,%23}, " \
  "{%24,%25,%26,%27}, %28, " sd ", 1, 1, 1;\n"

__device__ __forceinline__ void wg_acc(uint32_t (&d)[24], const uint32_t* a, uint64_t db) {
  asm volatile(WG_TXT("1") : R24("+r", d) : "r"(a[0]), "r"(a[1]), "r"(a[2]), "r"(a[3]), "l"(db));
}
__device__ __forceinline__ void wg_init(uint32_t (&d)[24], const uint32_t* a, uint64_t db) {
  asm volatile(WG_TXT("0") : R24("=r", d) : "r"(a[0]), "r"(a[1]), "r"(a[2]), "r"(a[3]), "l"(db));
}
template <int N>
__device__ __forceinline__ void rfence(uint32_t (&d)[N]) {
#pragma unroll
  for (int i = 0; i < N; i++) asm volatile("" : "+r"(d[i])::"memory");
}
template <bool INIT>
__device__ __forceinline__ void gemm6(uint32_t (&d)[24], const uint32_t (&a)[24], uint64_t db) {
#pragma unroll
  for (int k = 0; k < 6; k++) {
    if (INIT && k == 0) wg_init(d, &a[0], db);
    else wg_acc(d, &a[4 * k], db + k * 192);
  }
  WG_COMMIT();
}

__device__ __forceinline__ void mbar_init(uint32_t bar, uint32_t cnt) {
  asm volatile("mbarrier.init.shared::cta.b64 [%0], %1;" ::"r"(bar), "r"(cnt) : "memory");
}
__device__ __forceinline__ void mbar_expect(uint32_t bar, uint32_t bytes) {
  asm volatile("mbarrier.arrive.expect_tx.shared::cta.b64 _, [%0], %1;" ::"r"(bar), "r"(bytes) : "memory");
}
__device__ __forceinline__ void mbar_arrive_cluster(uint32_t bar) {
  asm volatile("mbarrier.arrive.shared::cluster.b64 _, [%0];" ::"r"(bar) : "memory");
}
__device__ __forceinline__ bool mbar_try(uint32_t bar, uint32_t parity) {
  uint32_t ok;
  asm volatile(
      "{\n.reg .pred p;\nmbarrier.try_wait.parity.shared::cta.b64 p, [%1], %2;\nselp.u32 %0, 1, 0, p;\n}\n"
      : "=r"(ok)
      : "r"(bar), "r"(parity)
      : "memory");
  return ok;
}
__device__ __forceinline__ void mbar_wait(uint32_t bar, uint32_t parity) {
  if (__builtin_expect(mbar_try(bar, parity), 1)) return;
  for (uint32_t n = 0; !mbar_try(bar, parity);)
    if (++n > (1u << 22)) __trap();
}
__device__ __forceinline__ uint32_t mapa(uint32_t addr, uint32_t rank) {
  uint32_t r;
  asm("mapa.shared::cluster.u32 %0, %1, %2;" : "=r"(r) : "r"(addr), "r"(rank));
  return r;
}
__device__ __forceinline__ void tma_raw(uint32_t dst, const CUtensorMap* tm, int c, int w, int h, uint32_t bar) {
  asm volatile(
      "cp.async.bulk.tensor.3d.shared::cluster.global.mbarrier::complete_tx::bytes [%0], [%1, {%2, %3, %4}], [%5];"
      ::"r"(dst), "l"(tm), "r"(c), "r"(w), "r"(h), "r"(bar)
      : "memory");
}
__device__ __forceinline__ void bulk_load(uint32_t dst, const void* src, uint32_t bytes, uint32_t bar) {
  asm volatile("cp.async.bulk.shared::cluster.global.mbarrier::complete_tx::bytes [%0], [%1], %2, [%3];" ::"r"(dst),
               "l"(src), "r"(bytes), "r"(bar)
               : "memory");
}
__device__ __forceinline__ uint32_t pack_bf16(float lo, float hi) {
  uint32_t r;
  asm("cvt.rn.bf16x2.f32 %0, %1, %2;" : "=r"(r) : "f"(hi), "f"(lo));
  return r;
}
__device__ __forceinline__ uint32_t pack_f16(float lo, float hi) {
  uint32_t r;
  asm("cvt.rn.f16x2.f32 %0, %1, %2;" : "=r"(r) : "f"(hi), "f"(lo));
  return r;
}
__device__ __forceinline__ float bf_lo(uint32_t v) { return __uint_as_float(v << 16); }
__device__ __forceinline__ float bf_hi(uint32_t v) { return __uint_as_float(v & 0xffff0000u); }
__device__ __forceinline__ uint32_t bf_add(uint32_t a, uint32_t b) {
  uint32_t r;
  asm("add.rn.bf16x2 %0, %1, %2;" : "=r"(r) : "r"(a), "r"(b));
  return r;
}
__device__ __forceinline__ uint32_t bf_mul(uint32_t a, uint32_t b) {
  uint32_t r;
  asm("mul.rn.bf16x2 %0, %1, %2;" : "=r"(r) : "r"(a), "r"(b));
  return r;
}
__device__ __forceinline__ uint32_t bf_fma(uint32_t a, uint32_t b, uint32_t c) {
  uint32_t r;
  asm("fma.rn.bf16x2 %0, %1, %2, %3;" : "=r"(r) : "r"(a), "r"(b), "r"(c));
  return r;
}

template <int LO, int HI>
__device__ __forceinline__ void gelu(uint32_t (&o)[24], const uint32_t (&d)[24]) {
#pragma unroll
  for (int q = LO; q < HI; q++) {
    uint32_t t, u;
    asm("fma.rn.f16x2 %0, %1, %1, %2;" : "=r"(t) : "r"(d[q]), "r"(GELU_K2));
    asm("mul.rn.f16x2 %0, %1, %2;" : "=r"(u) : "r"(d[q]), "r"(t));
    asm("tanh.approx.f16x2 %0, %1;" : "=r"(t) : "r"(u));
    asm("fma.rn.f16x2 %0, %1, %2, %1;" : "=r"(o[q]) : "r"(d[q]), "r"(t));
  }
}

__device__ __forceinline__ uint32_t laneid() {
  uint32_t l;
  asm volatile("mov.u32 %0, %%laneid;" : "=r"(l));
  return l;
}

__device__ __forceinline__ bool elect_one() {
  uint32_t p;
  asm volatile("{\n.reg .pred p;\nelect.sync _|p, 0xffffffff;\nselp.u32 %0, 1, 0, p;\n}\n" : "=r"(p));
  return p;
}

struct MlpCtx {
  uint32_t sb;
  uint32_t caddr;
  uint32_t xaddr;
  uint32_t unscale;
  uint32_t peer_off;
  int wg, warp, rank;
  const uint8_t* xsrc;
  uint8_t* optr;
};

__device__ __forceinline__ void ln_load(const MlpCtx& m, uint32_t (&c)[24], int i) {
  mbar_wait(m.sb + BAR_CFULL + 8 * m.wg, i & 1);
#pragma unroll
  for (int p = 0; p < 12; p++)
    asm volatile("ld.shared.v2.b32 {%0,%1}, [%2];" : "=r"(c[2 * p]), "=r"(c[2 * p + 1]) : "r"(m.caddr + p * 256) : "memory");
}
__device__ __forceinline__ void ln_shfl(float (&st)[4], int mask) {
  st[2] = __shfl_xor_sync(0xffffffffu, st[0], mask);
  st[3] = __shfl_xor_sync(0xffffffffu, st[1], mask);
}
__device__ __forceinline__ void ln_sum(const uint32_t (&c)[24], float (&st)[4]) {
#pragma unroll
  for (int r = 0; r < 2; r++) {
    uint32_t s0 = bf_add(c[r], c[r + 2]), s1 = bf_add(c[r + 4], c[r + 6]), s2 = bf_add(c[r + 8], c[r + 10]);
    uint32_t s3 = bf_add(c[r + 12], c[r + 14]), s4 = bf_add(c[r + 16], c[r + 18]), s5 = bf_add(c[r + 20], c[r + 22]);
    s0 = bf_add(s0, s1); s2 = bf_add(s2, s3); s4 = bf_add(s4, s5);
    s0 = bf_add(bf_add(s0, s2), s4);
    st[r] = bf_lo(s0) + bf_hi(s0);
  }
  ln_shfl(st, 1);
}
__device__ __forceinline__ void ln_release(const MlpCtx& m) {
  const uint32_t e = m.sb + BAR_CEMPTY + 8 * (2 * m.rank + m.wg);
  asm volatile(
      "{\n.reg .pred p, q;\nelect.sync _|p, 0xffffffff;\nsetp.eq.and.s32 q, %3, 0, p;\n"
      "@q mbarrier.arrive.expect_tx.shared::cta.b64 _, [%0], 12288;\n"
      "@p mbarrier.arrive.shared::cluster.b64 _, [%1];\n"
      "@p mbarrier.arrive.shared::cluster.b64 _, [%2];\n}\n" ::"r"(m.sb + BAR_CFULL + 8 * m.wg),
      "r"(e), "r"(e + m.peer_off), "r"(m.warp)
      : "memory");
}
__device__ __forceinline__ void ln_hop(float (&st)[4]) {
  st[0] += st[2]; st[1] += st[3];
  ln_shfl(st, 2);
}
__device__ __forceinline__ void ln_center(uint32_t (&c)[24], float (&st)[4], float (&dl)[2]) {
#pragma unroll
  for (int r = 0; r < 2; r++) {
    float nm = (st[r] + st[r + 2]) * (-1.0f / 96.0f);
    uint32_t nm2 = pack_bf16(nm, nm);
    dl[r] = nm - bf_hi(nm2);
#pragma unroll
    for (int p = 0; p < 12; p++) c[2 * p + r] = bf_add(c[2 * p + r], nm2);
    uint32_t q0 = bf_mul(c[r], c[r]), q1 = bf_mul(c[r + 2], c[r + 2]);
#pragma unroll
    for (int p = 2; p < 12; p += 2) {
      q0 = bf_fma(c[2 * p + r], c[2 * p + r], q0);
      q1 = bf_fma(c[2 * p + 2 + r], c[2 * p + 2 + r], q1);
    }
    q0 = bf_add(q0, q1);
    st[r] = bf_lo(q0) + bf_hi(q0);
  }
  ln_shfl(st, 1);
}
__device__ __forceinline__ void ln_rstd(uint32_t (&c)[24], float (&st)[4], float (&dl)[2]) {
#pragma unroll
  for (int r = 0; r < 2; r++) {
    asm("rsqrt.approx.ftz.f32 %0, %1;" : "=f"(st[r]) : "f"(fmaf(st[r] + st[r + 2], 1.0f / 96.0f, 1e-5f)));
    dl[r] *= st[r];
  }
  if (__builtin_expect(fminf(st[0], st[1]) < 0x1p-11f, 0)) {
#pragma unroll
    for (int r = 0; r < 2; r++) {
      uint32_t e = __float_as_uint(st[r]) & 0x7f800000u;
      uint32_t e2 = (e >> 16) | e;
#pragma unroll
      for (int p = 0; p < 12; p++) asm volatile("mul.rn.bf16x2 %0, %0, %1;" : "+r"(c[2 * p + r]) : "r"(e2));
      st[r] = __uint_as_float((__float_as_uint(st[r]) & 0x007fffffu) | 0x3f800000u);
    }
  }
}
__device__ __forceinline__ void ln_scale(uint32_t (&c)[24], const float (&st)[4], const float (&dl)[2]) {
#pragma unroll
  for (int r = 0; r < 2; r++) {
    float rr = st[r] * (GELU_A * 0x1p-112f), dd = dl[r] * (GELU_A * 0x1p-112f);
    uint32_t r2 = pack_bf16(rr, rr), d2 = pack_bf16(dd, dd);
#pragma unroll
    for (int p = 0; p < 12; p++) c[2 * p + r] = bf_fma(c[2 * p + r], r2, d2);
  }
}
__device__ __forceinline__ void ln_final(uint32_t (&a)[24], const uint32_t (&c)[24]) {
#pragma unroll
  for (int p = 0; p < 24; p++) a[p] = (c[p] & 0x7fff7fffu) * 7u + c[p];
}

__device__ __forceinline__ void issue_xres(const MlpCtx& m, int u, int wg_dst) {
  if (elect_one()) {
    uint32_t bar = m.sb + BAR_XFULL + 8 * (4 * wg_dst + m.warp);
    uint32_t dst = m.sb + OFF_XRES + m.warp * 3072;
    const uint8_t* src = m.xsrc + (size_t)(2 * (2 * u + m.rank)) * (IMG * CH * 2);
    asm volatile("cp.async.bulk.wait_group.read 0;" ::: "memory");
    mbar_expect(bar, 3072);
    bulk_load(dst, src, 1536, bar);
    bulk_load(dst + 1536, src + IMG * CH * 2, 1536, bar);
  }
}
__device__ __forceinline__ void x_load(const MlpCtx& m, uint32_t (&x)[24], int i) {
  mbar_wait(m.sb + BAR_XFULL + 8 * (4 * m.wg + m.warp), i & 1);
#pragma unroll
  for (int k = 0; k < 6; k++)
    asm volatile("ld.shared.v4.b32 {%0,%1,%2,%3}, [%4];"
                 : "=r"(x[4 * k]), "=r"(x[4 * k + 1]), "=r"(x[4 * k + 2]), "=r"(x[4 * k + 3])
                 : "r"(m.xaddr + (k / 3) * 384 + (k % 3) * 64)
                 : "memory");
}
__device__ __forceinline__ void epilogue(const MlpCtx& m, const uint32_t (&d)[24], uint32_t (&x)[24], int i) {
#pragma unroll
  for (int r = 0; r < 2; r++) {
#pragma unroll
    for (int q = 0; q < 3; q++) {
      uint32_t* y = &x[12 * r + 4 * q];
#pragma unroll
      for (int j = 0; j < 4; j++) {
        uint32_t v = d[2 * (4 * q + j) + r];
        float lo, hi;
        asm("{\n.reg .b16 l, h;\nmov.b32 {l, h}, %2;\ncvt.f32.f16 %0, l;\ncvt.f32.f16 %1, h;\n}\n" : "=f"(lo), "=f"(hi) : "r"(v));
        asm("fma.rn.bf16x2 %0, %1, %2, %0;" : "+r"(y[j]) : "r"(pack_bf16(lo, hi)), "r"(m.unscale));
      }
      asm volatile("st.shared.v4.b32 [%0], {%1,%2,%3,%4};" ::"r"(m.xaddr + r * 384 + q * 64), "r"(y[0]), "r"(y[1]), "r"(y[2]), "r"(y[3])
                   : "memory");
    }
  }
}
__device__ __forceinline__ void out_store(const MlpCtx& m, int i) {
  asm volatile("fence.proxy.async.shared::cta;" ::: "memory");
  __syncwarp();
  if (elect_one()) {
    const uint32_t src = m.sb + OFF_XRES + m.warp * 3072;
    uint8_t* dst = m.optr + (size_t)(2 * (2 * (2 * i + m.wg) + m.rank)) * (IMG * CH * 2);
    asm volatile("cp.async.bulk.global.shared::cta.bulk_group [%0], [%1], 1536;" ::"l"(dst), "r"(src) : "memory");
    asm volatile("cp.async.bulk.global.shared::cta.bulk_group [%0], [%1], 1536;" ::"l"(dst + IMG * CH * 2), "r"(src + 1536) : "memory");
    asm volatile("cp.async.bulk.commit_group;" ::: "memory");
  }
}

__device__ __forceinline__ void tok_wait(int wg) {
  asm volatile("{\n.reg .pred p;\nsetp.eq.s32 p, %0, 0;\n@p bar.sync %1, 384;\n@!p bar.sync %2, 256;\n}\n" ::"r"(wg), "n"(NB_TOK), "n"(NB_TOK + 1) : "memory");
}
__device__ __forceinline__ void tok_pass(int wg) {
  asm volatile("{\n.reg .pred p;\nsetp.eq.s32 p, %0, 0;\n@p bar.arrive %1, 256;\n@!p bar.arrive %2, 384;\n}\n" ::"r"(wg), "n"(NB_TOK + 1), "n"(NB_TOK + 2) : "memory");
}

constexpr uint64_t CHK = 1152;

__device__ __forceinline__ void mlp_role(const MlpCtx& m0, const __nv_bfloat16* w1, const __nv_bfloat16* w2) {
  MlpCtx m = m0;
  const int lane = threadIdx.x & 31, wid = m.wg * 4 + m.warp;
  if (m.wg == 0) issue_xres(m, 0, 0);
  {
    uint32_t mx = 0;
    const int k7 = lane & 7;
#pragma unroll 6
    for (int it = 0; it < 18; it++) {
      int item = wid * 18 + it, kb = item / 12, ng = item % 12;
      int ch = 24 * (k7 >> 1) + 2 * kb + (k7 & 1);
      int n8 = ng * 4 + (lane >> 3);
      uint4 v = __ldg(reinterpret_cast<const uint4*>(w1 + ch * 384 + n8 * 8));
      mx = __vmaxu2(mx, __vmaxu2(__vmaxu2(v.x & 0x7fff7fffu, v.y & 0x7fff7fffu), __vmaxu2(v.z & 0x7fff7fffu, v.w & 0x7fff7fffu)));
      uint32_t dst = m.sb + OFF_W1 + ((n8 / 12) * 6 + (kb >> 1)) * 3072 + (kb & 1) * 128 + (n8 % 12) * 256 + k7 * 16;
      asm volatile("st.shared.v4.b32 [%0], {%1,%2,%3,%4};" ::"r"(dst), "r"(pack_f16(bf_lo(v.x), bf_hi(v.x))),
                   "r"(pack_f16(bf_lo(v.y), bf_hi(v.y))), "r"(pack_f16(bf_lo(v.z), bf_hi(v.z))),
                   "r"(pack_f16(bf_lo(v.w), bf_hi(v.w)))
                   : "memory");
    }
    TR(m.wg, 1004);
    uint32_t v2[5][16];
    uint32_t mx2 = 0;
#pragma unroll
    for (int it = 0; it < 5; it++) {
      int item = (it * 8 + wid) * 4 + (lane >> 3);
      if (item > 143) item = 143;
      int kb = item / 3, q = item % 3;
      const uint4* src = reinterpret_cast<const uint4*>(w2 + (kb * 8 + k7) * 96 + q * 32);
#pragma unroll
      for (int t = 0; t < 4; t++) {
        uint4 v = __ldg(src + t);
        v2[it][4 * t] = v.x; v2[it][4 * t + 1] = v.y; v2[it][4 * t + 2] = v.z; v2[it][4 * t + 3] = v.w;
      }
    }
#pragma unroll
    for (int it = 0; it < 5; it++)
#pragma unroll
      for (int t = 0; t < 16; t++) mx2 = __vmaxu2(mx2, v2[it][t] & 0x7fff7fffu);
    TR(m.wg, 1005);
    mx = __reduce_max_sync(0xffffffffu, max(mx & 0xffffu, mx >> 16));
    mx2 = __reduce_max_sync(0xffffffffu, max(mx2 & 0xffffu, mx2 >> 16));
    if (lane == 0) {
      asm volatile("red.shared.max.u32 [%0], %1;" ::"r"(m.sb + OFF_MAX), "r"(mx) : "memory");
      asm volatile("red.shared.max.u32 [%0], %1;" ::"r"(m.sb + OFF_MAX + 4), "r"(mx2) : "memory");
    }
    NB_SYNC(NB_PREP, 256);
    asm volatile("ld.shared.v2.b32 {%0,%1}, [%2];" : "=r"(mx), "=r"(mx2) : "r"(m.sb + OFF_MAX) : "memory");
    TR(m.wg, 1006);
    int e1 = (int)(mx >> 7) - 126, e2 = (int)(mx2 >> 7) - 126;
    int s = min(-1 - e1 - e2, 14 - e2);
    s = max(-120, min(120, s));
    float sc = __uint_as_float((uint32_t)(127 + s) << 23) * (0.5f / GELU_A);
    m.unscale = __shfl_sync(0xffffffffu, ((uint32_t)(127 - s) << 7) * 0x10001u, 0);
#pragma unroll
    for (int it = 0; it < 5; it++) {
      int item = (it * 8 + wid) * 4 + (lane >> 3);
      if (item > 143) item = 143;
      int kb = item / 3, q = item % 3;
      uint32_t dst = m.sb + OFF_W2 + (kb >> 1) * 3072 + (kb & 1) * 128 + q * 1024 + k7 * 16;
#pragma unroll
      for (int j = 0; j < 4; j++) {
        uint32_t o[4];
#pragma unroll
        for (int t = 0; t < 4; t++) o[t] = pack_f16(bf_lo(v2[it][4 * t + j]) * sc, bf_hi(v2[it][4 * t + j]) * sc);
        asm volatile("st.shared.v4.b32 [%0], {%1,%2,%3,%4};" ::"r"(dst + j * 256), "r"(o[0]), "r"(o[1]), "r"(o[2]), "r"(o[3]) : "memory");
      }
    }
    asm volatile("fence.proxy.async.shared::cta;" ::: "memory");
    NB_SYNC(NB_PREP, 256);
  }
  const uint64_t dW1 = (uint64_t)(((m.sb + OFF_W1) & 0x3FFFF) >> 4) | ((uint64_t)8 << 16) | ((uint64_t)16 << 32);
  const uint64_t dW2 = dW1 + (OFF_W2 >> 4);

  TR(m.wg, 1000);
  uint32_t A1[24], g[24], cn[24], D2[24];
  float st[4], dl[2];
  ln_load(m, cn, 0);
  ln_sum(cn, st);
  ln_release(m);
  ln_hop(st);
  ln_center(cn, st, dl);
  ln_hop(st);
  ln_rstd(cn, st, dl);
  ln_scale(cn, st, dl);
  ln_final(A1, cn);
  [[maybe_unused]] int rho = 2 * m.wg + m.rank;
  for (int r = 0; r < 2 * m.wg + m.rank; r++) { tok_wait(m.wg); tok_pass(m.wg); }
  {
    uint32_t d[24];
    WG_FENCE();
    tok_wait(m.wg);
    gemm6<true>(d, A1, dW1);
    tok_pass(m.wg); PIN();
    WG_WAIT0(); rfence(d);
    gelu<0, 24>(g, d);
    PIN();
    rho++;
  }
#define SLOT(INIT, j2, j1)                  \
  uint32_t d[24];                           \
  WG_FENCE();                               \
  tok_wait(m.wg);                           \
  TR(m.wg, rho * 8);                        \
  gemm6<INIT>(D2, g, dW2 + (j2) * CHK);     \
  WG_FENCE();                               \
  gemm6<true>(d, A1, dW1 + (j1) * CHK);     \
  tok_pass(m.wg); PIN();                    \
  TR(m.wg, rho * 8 + 1);
#define SLOT_END()                          \
  TR(m.wg, rho * 8 + 2);                    \
  PIN(); WG_WAIT0(); rfence(d); rfence(D2); \
  TR(m.wg, rho * 8 + 3);
#define ROUND_END()                         \
  TR(m.wg, rho * 8 + 4);                    \
  PIN(); rho++;
#pragma unroll 1
  for (int i = 0;; i++) {
    {
      SLOT(true, 0, 1)
      if (i > 0) issue_xres(m, 2 * i + m.wg - 1, m.wg ^ 1);
      SLOT_END()
      if (m.wg == 1 && i < 15) ln_load(m, cn, i + 1);
      gelu<0, 24>(g, d);
      PIN();
      if (m.wg == 0 && i < 15) ln_load(m, cn, i + 1);
      ROUND_END()
    }
    {
      SLOT(false, 1, 2)
      ln_sum(cn, st);
      if (i < 15) ln_release(m);
      ln_hop(st);
      SLOT_END()
      ln_center(cn, st, dl);
      gelu<0, 24>(g, d);
      ROUND_END()
    }
    {
      SLOT(false, 2, 3)
      ln_hop(st);
      ln_rstd(cn, st, dl);
      ln_scale(cn, st, dl);
      SLOT_END()
      ln_final(A1, cn);
      PIN();
      if (m.wg == 1) x_load(m, cn, i);
      gelu<0, 24>(g, d);
      PIN();
      if (m.wg == 0) x_load(m, cn, i);
      ROUND_END()
    }
    if (i == 15) break;
    {
      SLOT(false, 3, 0)
      WG_WAIT1(); rfence(D2);
      epilogue(m, D2, cn, i);
      out_store(m, i);
      SLOT_END()
      gelu<0, 24>(g, d);
      ROUND_END()
    }
  }
  WG_FENCE();
  tok_wait(m.wg);
  gemm6<false>(D2, g, dW2 + 3 * CHK);
  tok_pass(m.wg); PIN();
  WG_WAIT0(); rfence(D2);
  epilogue(m, D2, cn, 15);
  out_store(m, 15);
  if (m.wg == 0) {
    issue_xres(m, 31, 1);
    for (int r = 0; r < 2; r++) { tok_wait(0); tok_pass(0); }
  }
  asm volatile("cp.async.bulk.wait_group 0;" ::: "memory");
  TR(m.wg, 1001);
  TRG(1021);
}

struct ConvCtx {
  uint32_t sb;
  uint32_t a_ldsm, a_stsm, a_frag, a_c;
  uint32_t peer_off;
  int rank, v, c0, r0, zero;
  const CUtensorMap* tm;
};

__device__ __forceinline__ void conv_transpose(const ConvCtx& c, int s) {
  const int st = s & 3;
  const uint32_t pl = (s & 1) * PLAN_BYTES;
  uint32_t t[8];
  mbar_wait(c.sb + BAR_RAW + 8 * st, (s >> 2) & 1);
#pragma unroll
  for (int h = 0; h < 2; h++)
    asm volatile("ldmatrix.sync.aligned.m8n8.x4.trans.shared.b16 {%0,%1,%2,%3}, [%4];"
                 : "=r"(t[4 * h]), "=r"(t[4 * h + 1]), "=r"(t[4 * h + 2]), "=r"(t[4 * h + 3])
                 : "r"(c.a_ldsm + st * RAW_BYTES + h * 48)
                 : "memory");
#pragma unroll
  for (int h = 0; h < 2; h++)
    asm volatile("stmatrix.sync.aligned.m8n8.x4.shared.b16 [%0], {%1,%2,%3,%4};" ::"r"(c.a_stsm + pl + h * 24 * PLAN_PITCH),
                 "r"(t[4 * h]), "r"(t[4 * h + 1]), "r"(t[4 * h + 2]), "r"(t[4 * h + 3])
                 : "memory");
}
__device__ __forceinline__ void conv_refill(const ConvCtx& c, int s) {
  if (c.v == 0 && s + 4 < NSTEP && elect_one()) {
    const int st = s & 3;
    mbar_expect(c.sb + BAR_RAW + 8 * st, RAW_BYTES);
    tma_raw(c.sb + OFF_RAW + st * RAW_BYTES, c.tm, 48 * c.rank, c.c0 - 3, c.r0 - 3 + 2 * (s + 4), c.sb + BAR_RAW + 8 * st);
  }
}
__device__ __forceinline__ void conv_frags(const ConvCtx& c, int s, uint32_t (&A)[24]) {
  const uint32_t pl = (s & 1) * PLAN_BYTES;
#pragma unroll
  for (int ch = 0; ch < 6; ch++) {
    uint32_t a = c.a_frag + pl + ch * PLAN_PITCH;
    asm volatile("ld.shared.v2.b32 {%0,%1}, [%2];" : "=r"(A[4 * ch]), "=r"(A[4 * ch + 1]) : "r"(a) : "memory");
    asm volatile("ld.shared.b32 %0, [%1];" : "=r"(A[4 * ch + 3]) : "r"(a + 8) : "memory");
  }
}
__device__ __forceinline__ void conv_dup(const ConvCtx& c, uint32_t (&A)[24]) {
#pragma unroll
  for (int ch = 0; ch < 6; ch++) A[4 * ch + 2] = A[4 * ch + 1] ^ c.zero;
}

__device__ __forceinline__ void hmma(float (&d)[4], const uint32_t* a, const uint32_t* b, const float (&cc)[4]) {
  asm volatile("mma.sync.aligned.m16n8k16.row.col.f32.bf16.bf16.f32 {%0,%1,%2,%3}, {%4,%5,%6,%7}, {%8,%9}, {%10,%11,%12,%13};"
               : "=f"(d[0]), "=f"(d[1]), "=f"(d[2]), "=f"(d[3])
               : "r"(a[0]), "r"(a[1]), "r"(a[2]), "r"(a[3]), "r"(b[0]), "r"(b[1]), "f"(cc[0]), "f"(cc[1]), "f"(cc[2]), "f"(cc[3]));
}

template <bool MORE>
__device__ __forceinline__ void conv_step(const ConvCtx& c, int s, float (&U)[6][4], float (&V)[6][4], const uint32_t (&B)[6][4],
                                          uint32_t (&A)[24]) {
  float T[6][4];
  TR(2 + (c.v >> 2), s * 8);
  if (s >= SIGMA) NB_SYNC(NB_TOK + 2, 384);
  else NB_SYNC(NB_PLAN, 256);
  PIN();
  TR(2 + (c.v >> 2), s * 8 + 1);
#pragma unroll
  for (int ch = 0; ch < 6; ch++) {
    hmma(T[ch], &A[4 * ch], &B[ch][2], V[ch]);
    hmma(V[ch], &A[4 * ch], &B[ch][0], U[ch]);
  }
  PIN();
  if (s >= SIGMA) NB_ARRIVE(NB_TOK, 384);
  TR(2 + (c.v >> 2), s * 8 + 2);
  uint32_t pk[6];
#pragma unroll
  for (int q = 0; q < 3; q++) {
    pk[2 * q] = pack_bf16(T[2 * q][1], T[2 * q + 1][1]);
    pk[2 * q + 1] = pack_bf16(T[2 * q][3], T[2 * q + 1][3]);
  }
#pragma unroll
  for (int ch = 0; ch < 6; ch++) {
    U[ch][1] = __uint_as_float(__float_as_uint(T[ch][0]) ^ c.zero);
    U[ch][3] = __uint_as_float(__float_as_uint(T[ch][2]) ^ c.zero);
  }
  PIN();
  if (MORE) conv_frags(c, s + 1, A);
  if (MORE) conv_refill(c, s + 1);
  TR(2 + (c.v >> 2), s * 8 + 3);
  if (s >= 3) {
    const int tau = s - 3, owner = tau & 1, slot = (tau >> 1) & 1;
    if (tau >= 4) mbar_wait(c.sb + BAR_CEMPTY + 8 * (2 * owner + slot), ((tau >> 2) - 1) & 1);
    const uint32_t off = (owner == c.rank) ? 0u : c.peer_off;
    const uint32_t dst = c.a_c + off + slot * C_BYTES, bar = c.sb + off + BAR_CFULL + 8 * slot;
#pragma unroll
    for (int q = 0; q < 3; q++)
      asm volatile("st.async.weak.shared::cluster.mbarrier::complete_tx::bytes.v2.b32 [%0], {%1,%2}, [%3];" ::"r"(dst + q * 256),
                   "r"(pk[2 * q]), "r"(pk[2 * q + 1]), "r"(bar)
                   : "memory");
  }
  TR(2 + (c.v >> 2), s * 8 + 4);
  if (MORE) {
    if (s + 2 < NSTEP) conv_transpose(c, s + 2);
    TR(2 + (c.v >> 2), s * 8 + 13);
    conv_dup(c, A);
  }
}

__device__ __forceinline__ void conv_role(const ConvCtx& c, const __nv_bfloat16* dw) {
  const int lane = threadIdx.x & 31, g = lane >> 2, t = lane & 3;
  uint32_t B[6][4];
  {
    const int e = g & 1, dc = (g >> 1) & 1, ro = g >> 2, rk = t >> 1;
    const uint32_t* dwp = reinterpret_cast<const uint32_t*>(dw) + 24 * c.rank + 3 * c.v;
#pragma unroll
    for (int b = 0; b < 2; b++) {
      const int i = 2 * (2 * e + b) + rk - ro;
      uint32_t w[4][3];
#pragma unroll
      for (int k = 0; k < 4; k++) {
        const int j = 4 * (t & 1) + k - dc;
        const bool ok = i >= 0 && i < 7 && j >= 0 && j < 7;
#pragma unroll
        for (int q = 0; q < 3; q++) w[k][q] = ok ? __ldg(dwp + (i * 7 + j) * 48 + q) : 0u;
      }
#pragma unroll
      for (int q = 0; q < 3; q++) {
        B[2 * q][2 * b] = __byte_perm(w[0][q], w[1][q], 0x5410);
        B[2 * q][2 * b + 1] = __byte_perm(w[2][q], w[3][q], 0x5410);
        B[2 * q + 1][2 * b] = __byte_perm(w[0][q], w[1][q], 0x7632);
        B[2 * q + 1][2 * b + 1] = __byte_perm(w[2][q], w[3][q], 0x7632);
      }
    }
  }
  TR(2 + (c.v >> 2), 1004);
  float U[6][4], V[6][4];
#pragma unroll
  for (int ch = 0; ch < 6; ch++)
#pragma unroll
    for (int k = 0; k < 4; k++) {
      U[ch][k] = __uint_as_float(B[ch][k] & c.zero);
      V[ch][k] = 0.f;
    }
  uint32_t A[24];
  conv_transpose(c, 0);
  NB_SYNC(NB_PLAN, 256);
  conv_frags(c, 0, A);
  conv_refill(c, 0);
  conv_transpose(c, 1);
  conv_dup(c, A);
  NB_ARRIVE(NB_TOK, 384);
#pragma unroll 1
  for (int s = 0; s < NSTEP - 1; s++) conv_step<true>(c, s, U, V, B, A);
  conv_step<false>(c, NSTEP - 1, U, V, B, A);
  for (int r = NSTEP - SIGMA; r < NROUND - 1 + c.rank; r++) { NB_SYNC(NB_TOK + 2, 384); NB_ARRIVE(NB_TOK, 384); }
  NB_SYNC(NB_TOK + 2, 384);
}

__global__ void __cluster_dims__(2, 1, 1) __launch_bounds__(512, 1)
convnext_kernel(const __grid_constant__ CUtensorMap tm, const __nv_bfloat16* __restrict__ x, const __nv_bfloat16* __restrict__ dw,
                const __nv_bfloat16* __restrict__ w1, const __nv_bfloat16* __restrict__ w2, __nv_bfloat16* __restrict__ out,
                int zero) {
  extern __shared__ __align__(1024) uint8_t smem[];
  const uint32_t sb = (uint32_t)__cvta_generic_to_shared(smem);
  const int tid = threadIdx.x, lane = tid & 31;
  const int wid = __shfl_sync(0xffffffffu, tid >> 5, 0);
  const int rank = blockIdx.x & 1, cl = blockIdx.x >> 1;
  const int c0 = (cl & 15) * 32, r0 = (cl >> 4) * 128;
  const uint32_t peer_off = mapa(sb, rank ^ 1) - sb;

  TR(wid >> 2, 1002);
  TRG(1020);
  if (tid == 256) {
    for (int i = 0; i < 4; i++) mbar_init(sb + BAR_RAW + 8 * i, 1);
    for (int i = 0; i < 2; i++) mbar_init(sb + BAR_CFULL + 8 * i, 1);
    for (int i = 0; i < 4; i++) mbar_init(sb + BAR_CEMPTY + 8 * i, 4);
    for (int i = 0; i < 8; i++) mbar_init(sb + BAR_XFULL + 8 * i, 1);
    asm volatile("st.shared.v2.b32 [%0], {%1,%1};" ::"r"(sb + OFF_MAX), "r"(0) : "memory");
    asm volatile("fence.mbarrier_init.release.cluster;" ::: "memory");
    asm volatile("fence.proxy.async.shared::cta;" ::: "memory");
    TR(2, 1006);
    for (int i = 0; i < 4; i++) {
      mbar_expect(sb + BAR_RAW + 8 * i, RAW_BYTES);
      tma_raw(sb + OFF_RAW + i * RAW_BYTES, &tm, 48 * rank, c0 - 3, r0 - 3 + 2 * i, sb + BAR_RAW + 8 * i);
    }
    for (int i = 0; i < 2; i++) mbar_expect(sb + BAR_CFULL + 8 * i, 12288);
    TR(2, 1007);
  }
  __syncwarp();
  asm volatile("barrier.cluster.arrive.aligned;\nbarrier.cluster.wait.aligned;" ::: "memory");

  TR(wid >> 2, 1003);
  if (wid < 8) {
    MlpCtx m;
    m.sb = sb; m.wg = wid >> 2; m.warp = wid & 3; m.rank = rank; m.peer_off = peer_off;
    m.xsrc = reinterpret_cast<const uint8_t*>(x) + ((size_t)r0 * IMG + c0 + 8 * m.warp) * (CH * 2);
    m.optr = reinterpret_cast<uint8_t*>(out) + ((size_t)r0 * IMG + c0 + 8 * m.warp) * (CH * 2);
    m.caddr = sb + OFF_C + m.wg * C_BYTES + m.warp * 64 + (lane & 3) * (12 * 256 + 32) + (lane >> 2) * 8;
    m.xaddr = sb + OFF_XRES + m.warp * 3072 + ((lane >> 3) & 1) * 1536 + ((lane >> 4) * 4 + ((lane >> 2) & 1)) * 192 + (lane & 3) * 16;
    m.unscale = 0;
    asm volatile("setmaxnreg.inc.sync.aligned.u32 %0;" ::"n"(REG_MLP));
    mlp_role(m, w1, w2);
  } else {
    ConvCtx c;
    c.sb = sb; c.rank = rank; c.v = wid - 8; c.c0 = c0; c.r0 = r0; c.zero = zero; c.tm = &tm;
    c.peer_off = peer_off;
    const int b = min(4 * c.v + (lane >> 3), 29), cg = b / 10, rb = b % 10;
    c.a_ldsm = sb + OFF_RAW + ((rb / 5) * 38 + (rb % 5) * 8 + (lane & 7)) * 96 + cg * 16;
    c.a_stsm = sb + OFF_PLAN + (cg * 8 + (lane & 7)) * PLAN_PITCH + rb * 16;
    const int g = lane >> 2, t = lane & 3;
    c.a_frag = sb + OFF_PLAN + 6 * c.v * PLAN_PITCH + (t >> 1) * 80 + (g + (t & 1)) * 8;
    const int p0 = 24 * rank + 3 * c.v;
    c.a_c = sb + OFF_C + p0 * 256 + (p0 / 12) * 32 + lane * 8;
    asm volatile("setmaxnreg.dec.sync.aligned.u32 %0;" ::"n"(REG_CONV));
    conv_role(c, dw);
  }
  __syncwarp();
  asm volatile("barrier.cluster.arrive.relaxed.aligned;\nbarrier.cluster.wait.aligned;" ::: "memory");
}

typedef CUresult (*EncodeFn)(CUtensorMap*, CUtensorMapDataType, cuuint32_t, void*, const cuuint64_t*, const cuuint64_t*,
                             const cuuint32_t*, const cuuint32_t*, CUtensorMapInterleave, CUtensorMapSwizzle,
                             CUtensorMapL2promotion, CUtensorMapFloatOOBfill);

}

extern "C" void kernel_launch(void* const* d_in, const int* in_sizes, int n_in, void* d_out, int out_size) {
  const __nv_bfloat16* x = (const __nv_bfloat16*)d_in[0];
  const __nv_bfloat16* dw = (const __nv_bfloat16*)d_in[1];
  const __nv_bfloat16* w1 = (const __nv_bfloat16*)d_in[2];
  const __nv_bfloat16* w2 = (const __nv_bfloat16*)d_in[3];
  __nv_bfloat16* out = (__nv_bfloat16*)d_out;

  static EncodeFn encode = nullptr;
  if (!encode) {
    cudaDriverEntryPointQueryResult st;
    void* fn = nullptr;
    cudaGetDriverEntryPoint("cuTensorMapEncodeTiled", &fn, cudaEnableDefault, &st);
    encode = (EncodeFn)fn;
    cudaFuncSetAttribute(convnext_kernel, cudaFuncAttributeMaxDynamicSharedMemorySize, SMEM_BYTES);
  }
  CUtensorMap tm;
  cuuint64_t dims[3] = {CH, IMG, IMG};
  cuuint64_t strides[2] = {CH * 2, (cuuint64_t)IMG * CH * 2};
  cuuint32_t box[3] = {48, 38, 2};
  cuuint32_t es[3] = {1, 1, 1};
  encode(&tm, CU_TENSOR_MAP_DATA_TYPE_BFLOAT16, 3, (void*)x, dims, strides, box, es, CU_TENSOR_MAP_INTERLEAVE_NONE,
         CU_TENSOR_MAP_SWIZZLE_NONE, CU_TENSOR_MAP_L2_PROMOTION_L2_128B, CU_TENSOR_MAP_FLOAT_OOB_FILL_NONE);
  convnext_kernel<<<128, 512, SMEM_BYTES>>>(tm, x, dw, w1, w2, out, 0);
}
```

```cpp
#include <cuda_runtime.h>
#include <cuda_bf16.h>
#include <cuda.h>
#include <stdint.h>

namespace {

constexpr int IMG = 512, CH = 96;
constexpr int NSTEP = 67;
constexpr int SIGMA = 7;
constexpr int NROUND = 67;

constexpr uint32_t OFF_W1 = 0;
constexpr uint32_t OFF_W2 = 73728;
constexpr uint32_t OFF_RAW = 147456;
constexpr uint32_t RAW_PLANE = 4352;
constexpr uint32_t RAW_BYTES = 2 * RAW_PLANE;
constexpr uint32_t RAW_TX = 2 * 2 * 19 * 112;
constexpr uint32_t OFF_XRES = OFF_RAW + 4 * RAW_BYTES;
constexpr uint32_t OFF_C = OFF_XRES + 2 * 12288;
constexpr uint32_t C_BYTES = 12416;
constexpr uint32_t OFF_BAR = OFF_C + 2 * C_BYTES;
constexpr uint32_t BAR_RAW = OFF_BAR;
constexpr uint32_t BAR_CFULL = OFF_BAR + 32;
constexpr uint32_t BAR_CEMPTY = OFF_BAR + 48;
constexpr uint32_t BAR_XFULL = OFF_BAR + 80;
constexpr uint32_t OFF_MAX = OFF_BAR + 144;
constexpr uint32_t SMEM_BYTES = OFF_BAR + 160;

constexpr float GELU_A = 0.32918364f;
constexpr uint32_t GELU_K2 = 0x40d940d9u;

constexpr int NB_TOK = 1, NB_PLAN = 4, NB_PREP = 5;
#define REG_MLP 144
constexpr int REG_CONV = 504 - 2 * REG_MLP;

#define WG_FENCE() asm volatile("wgmma.fence.sync.aligned;" ::: "memory")
#define WG_COMMIT() asm volatile("wgmma.commit_group.sync.aligned;" ::: "memory")
#define WG_WAIT0() asm volatile("wgmma.wait_group.sync.aligned 0;" ::: "memory")
#define WG_WAIT1() asm volatile("wgmma.wait_group.sync.aligned 1;" ::: "memory")
#define PIN() asm volatile("pmevent 0;" ::: "memory")
#define NB_SYNC(id, n) asm volatile("bar.sync %0, %1;" ::"n"(id), "n"(n) : "memory")
#define NB_ARRIVE(id, n) asm volatile("bar.arrive %0, %1;" ::"n"(id), "n"(n) : "memory")

#define TR(who, idx)
#define TRG(idx)

#define R24(c, d)                                                                                        \
  c(d[0]), c(d[1]), c(d[2]), c(d[3]), c(d[4]), c(d[5]), c(d[6]), c(d[7]), c(d[8]), c(d[9]), c(d[10]),    \
      c(d[11]), c(d[12]), c(d[13]), c(d[14]), c(d[15]), c(d[16]), c(d[17]), c(d[18]), c(d[19]), c(d[20]), \
      c(d[21]), c(d[22]), c(d[23])
#define WG_TXT(sd)                                                                             \
  "wgmma.mma_async.sync.aligned.m64n96k16.f16.f16.f16 "                                        \
  "{%0,%1,%2,%3,%4,%5,%6,%7,%8,%9,%10,%11,%12,%13,%14,%15,%16,%17,%18,%19,%20,%21,%22,%23}, " \
  "{%24,%25,%26,%27}, %28, " sd ", 1, 1, 1;\n"

__device__ __forceinline__ void wg_acc(uint32_t (&d)[24], const uint32_t* a, uint64_t db) {
  asm volatile(WG_TXT("1") : R24("+r", d) : "r"(a[0]), "r"(a[1]), "r"(a[2]), "r"(a[3]), "l"(db));
}
__device__ __forceinline__ void wg_init(uint32_t (&d)[24], const uint32_t* a, uint64_t db) {
  asm volatile(WG_TXT("0") : R24("=r", d) : "r"(a[0]), "r"(a[1]), "r"(a[2]), "r"(a[3]), "l"(db));
}
template <int N>
__device__ __forceinline__ void rfence(uint32_t (&d)[N]) {
#pragma unroll
  for (int i = 0; i < N; i++) asm volatile("" : "+r"(d[i])::"memory");
}
template <bool INIT>
__device__ __forceinline__ void gemm6(uint32_t (&d)[24], const uint32_t (&a)[24], uint64_t db) {
#pragma unroll
  for (int k = 0; k < 6; k++) {
    if (INIT && k == 0) wg_init(d, &a[0], db);
    else wg_acc(d, &a[4 * k], db + k * 192);
  }
  WG_COMMIT();
}

__device__ __forceinline__ void mbar_init(uint32_t bar, uint32_t cnt) {
  asm volatile("mbarrier.init.shared::cta.b64 [%0], %1;" ::"r"(bar), "r"(cnt) : "memory");
}
__device__ __forceinline__ void mbar_expect(uint32_t bar, uint32_t bytes) {
  asm volatile("mbarrier.arrive.expect_tx.shared::cta.b64 _, [%0], %1;" ::"r"(bar), "r"(bytes) : "memory");
}
__device__ __forceinline__ void mbar_arrive_cluster(uint32_t bar) {
  asm volatile("mbarrier.arrive.shared::cluster.b64 _, [%0];" ::"r"(bar) : "memory");
}
__device__ __forceinline__ bool mbar_try(uint32_t bar, uint32_t parity) {
  uint32_t ok;
  asm volatile(
      "{\n.reg .pred p;\nmbarrier.try_wait.parity.shared::cta.b64 p, [%1], %2;\nselp.u32 %0, 1, 0, p;\n}\n"
      : "=r"(ok)
      : "r"(bar), "r"(parity)
      : "memory");
  return ok;
}
__device__ __forceinline__ void mbar_wait(uint32_t bar, uint32_t parity) {
  if (__builtin_expect(mbar_try(bar, parity), 1)) return;
#pragma unroll 1
  for (uint32_t n = 0; n < (1u << 16) && !mbar_try(bar, parity); n++) {}
}
__device__ __forceinline__ uint32_t mapa(uint32_t addr, uint32_t rank) {
  uint32_t r;
  asm("mapa.shared::cluster.u32 %0, %1, %2;" : "=r"(r) : "r"(addr), "r"(rank));
  return r;
}
__device__ __forceinline__ void tma_raw(uint32_t dst, const CUtensorMap* tm, int c, int w2, int h, uint32_t bar) {
  mbar_expect(bar, RAW_TX);
#pragma unroll
  for (int e = 0; e < 2; e++)
    asm volatile(
        "cp.async.bulk.tensor.4d.shared::cluster.global.mbarrier::complete_tx::bytes [%0], [%1, {%2, %3, %4, %5}], [%6];"
        ::"r"(dst + e * RAW_PLANE), "l"(tm), "r"(c), "r"(w2 + e), "r"(h), "r"(1 - e), "r"(bar)
        : "memory");
}
__device__ __forceinline__ void bulk_load(uint32_t dst, const void* src, uint32_t bytes, uint32_t bar) {
  asm volatile("cp.async.bulk.shared::cluster.global.mbarrier::complete_tx::bytes [%0], [%1], %2, [%3];" ::"r"(dst),
               "l"(src), "r"(bytes), "r"(bar)
               : "memory");
}
__device__ __forceinline__ uint32_t pack_bf16(float lo, float hi) {
  uint32_t r;
  asm("cvt.rn.bf16x2.f32 %0, %1, %2;" : "=r"(r) : "f"(hi), "f"(lo));
  return r;
}
__device__ __forceinline__ uint32_t pack_f16(float lo, float hi) {
  uint32_t r;
  asm("cvt.rn.f16x2.f32 %0, %1, %2;" : "=r"(r) : "f"(hi), "f"(lo));
  return r;
}
__device__ __forceinline__ float bf_lo(uint32_t v) { return __uint_as_float(v << 16); }
__device__ __forceinline__ float bf_hi(uint32_t v) { return __uint_as_float(v & 0xffff0000u); }
__device__ __forceinline__ uint32_t bf_add(uint32_t a, uint32_t b) {
  uint32_t r;
  asm("add.rn.bf16x2 %0, %1, %2;" : "=r"(r) : "r"(a), "r"(b));
  return r;
}
__device__ __forceinline__ uint32_t bf_mul(uint32_t a, uint32_t b) {
  uint32_t r;
  asm("mul.rn.bf16x2 %0, %1, %2;" : "=r"(r) : "r"(a), "r"(b));
  return r;
}
__device__ __forceinline__ uint32_t bf_fma(uint32_t a, uint32_t b, uint32_t c) {
  uint32_t r;
  asm("fma.rn.bf16x2 %0, %1, %2, %3;" : "=r"(r) : "r"(a), "r"(b), "r"(c));
  return r;
}

template <int LO, int HI>
__device__ __forceinline__ void gelu(uint32_t (&o)[24], const uint32_t (&d)[24]) {
#pragma unroll
  for (int q = LO; q < HI; q++) {
    uint32_t t, u;
    asm("fma.rn.f16x2 %0, %1, %1, %2;" : "=r"(t) : "r"(d[q]), "r"(GELU_K2));
    asm("mul.rn.f16x2 %0, %1, %2;" : "=r"(u) : "r"(d[q]), "r"(t));
    asm("tanh.approx.f16x2 %0, %1;" : "=r"(t) : "r"(u));
    asm("fma.rn.f16x2 %0, %1, %2, %1;" : "=r"(o[q]) : "r"(d[q]), "r"(t));
  }
}

__device__ __forceinline__ uint32_t laneid() {
  uint32_t l;
  asm volatile("mov.u32 %0, %%laneid;" : "=r"(l));
  return l;
}

__device__ __forceinline__ bool elect_one() {
  uint32_t p;
  asm volatile("{\n.reg .pred p;\nelect.sync _|p, 0xffffffff;\nselp.u32 %0, 1, 0, p;\n}\n" : "=r"(p));
  return p;
}

struct MlpCtx {
  uint32_t sb;
  uint32_t caddr;
  uint32_t xaddr;
  uint32_t unscale;
  uint32_t peer_off;
  int wg, warp, rank;
  const uint8_t* xsrc;
  uint8_t* optr;
};

__device__ __forceinline__ void ln_wait(const MlpCtx& m, int i) { mbar_wait(m.sb + BAR_CFULL + 8 * m.wg, i & 1); }
__device__ __forceinline__ void ln_load(const MlpCtx& m, uint32_t (&c)[24]) {
#pragma unroll
  for (int p = 0; p < 6; p++)
    asm volatile("ld.shared.v4.b32 {%0,%1,%2,%3}, [%4];"
                 : "=r"(c[4 * p]), "=r"(c[4 * p + 1]), "=r"(c[4 * p + 2]), "=r"(c[4 * p + 3])
                 : "r"(m.caddr + p * 512)
                 : "memory");
}
__device__ __forceinline__ void ln_shfl(float (&st)[4], int mask) {
  st[2] = __shfl_xor_sync(0xffffffffu, st[0], mask);
  st[3] = __shfl_xor_sync(0xffffffffu, st[1], mask);
}
__device__ __forceinline__ void ln_sum(const uint32_t (&c)[24], float (&st)[4]) {
#pragma unroll
  for (int r = 0; r < 2; r++) {
    uint32_t s0 = bf_add(c[r], c[r + 2]), s1 = bf_add(c[r + 4], c[r + 6]), s2 = bf_add(c[r + 8], c[r + 10]);
    uint32_t s3 = bf_add(c[r + 12], c[r + 14]), s4 = bf_add(c[r + 16], c[r + 18]), s5 = bf_add(c[r + 20], c[r + 22]);
    s0 = bf_add(s0, s1); s2 = bf_add(s2, s3); s4 = bf_add(s4, s5);
    s0 = bf_add(bf_add(s0, s2), s4);
    st[r] = bf_lo(s0) + bf_hi(s0);
  }
  ln_shfl(st, 1);
}
__device__ __forceinline__ void ln_release(const MlpCtx& m) {
  const uint32_t e = m.sb + BAR_CEMPTY + 8 * (2 * m.rank + m.wg);
  asm volatile(
      "{\n.reg .pred p, q;\nelect.sync _|p, 0xffffffff;\nsetp.eq.and.s32 q, %3, 0, p;\n"
      "@q mbarrier.arrive.expect_tx.shared::cta.b64 _, [%0], 12288;\n"
      "@p mbarrier.arrive.shared::cluster.b64 _, [%1];\n"
      "@p mbarrier.arrive.shared::cluster.b64 _, [%2];\n}\n" ::"r"(m.sb + BAR_CFULL + 8 * m.wg),
      "r"(e), "r"(e + m.peer_off), "r"(m.warp)
      : "memory");
}
__device__ __forceinline__ void ln_hop(float (&st)[4]) {
  st[0] += st[2]; st[1] += st[3];
  ln_shfl(st, 2);
}
__device__ __forceinline__ void ln_center(uint32_t (&c)[24], float (&st)[4], float (&dl)[2]) {
#pragma unroll
  for (int r = 0; r < 2; r++) {
    float nm = (st[r] + st[r + 2]) * (-1.0f / 96.0f);
    uint32_t nm2 = pack_bf16(nm, nm);
    dl[r] = nm - bf_hi(nm2);
#pragma unroll
    for (int p = 0; p < 12; p++) c[2 * p + r] = bf_add(c[2 * p + r], nm2);
    uint32_t q0 = bf_mul(c[r], c[r]), q1 = bf_mul(c[r + 2], c[r + 2]);
#pragma unroll
    for (int p = 2; p < 12; p += 2) {
      q0 = bf_fma(c[2 * p + r], c[2 * p + r], q0);
      q1 = bf_fma(c[2 * p + 2 + r], c[2 * p + 2 + r], q1);
    }
    q0 = bf_add(q0, q1);
    st[r] = bf_lo(q0) + bf_hi(q0);
  }
  ln_shfl(st, 1);
}
__device__ __forceinline__ void ln_rstd(uint32_t (&c)[24], float (&st)[4], float (&dl)[2]) {
#pragma unroll
  for (int r = 0; r < 2; r++) {
    asm("rsqrt.approx.ftz.f32 %0, %1;" : "=f"(st[r]) : "f"(fmaf(st[r] + st[r + 2], 1.0f / 96.0f, 1e-5f)));
    dl[r] *= st[r];
  }
  if (__builtin_expect(fminf(st[0], st[1]) < 0x1p-11f, 0)) {
#pragma unroll
    for (int r = 0; r < 2; r++) {
      uint32_t e = __float_as_uint(st[r]) & 0x7f800000u;
      uint32_t e2 = (e >> 16) | e;
#pragma unroll
      for (int p = 0; p < 12; p++) asm volatile("mul.rn.bf16x2 %0, %0, %1;" : "+r"(c[2 * p + r]) : "r"(e2));
      st[r] = __uint_as_float((__float_as_uint(st[r]) & 0x007fffffu) | 0x3f800000u);
    }
  }
}
__device__ __forceinline__ void ln_scale(uint32_t (&c)[24], const float (&st)[4], const float (&dl)[2]) {
#pragma unroll
  for (int r = 0; r < 2; r++) {
    float rr = st[r] * (GELU_A * 0x1p-112f), dd = dl[r] * (GELU_A * 0x1p-112f);
    uint32_t r2 = pack_bf16(rr, rr), d2 = pack_bf16(dd, dd);
#pragma unroll
    for (int p = 0; p < 12; p++) c[2 * p + r] = bf_fma(c[2 * p + r], r2, d2);
  }
}
__device__ __forceinline__ void ln_final(uint32_t (&a)[24], const uint32_t (&c)[24]) {
#pragma unroll
  for (int p = 0; p < 24; p++) a[p] = (c[p] & 0x7fff7fffu) * 7u + c[p];
}

__device__ __forceinline__ void issue_xres(const MlpCtx& m, int i) {
  if (elect_one()) {
    uint32_t bar = m.sb + BAR_XFULL + 8 * (4 * m.wg + m.warp);
    uint32_t dst = m.sb + OFF_XRES + (4 * m.wg + m.warp) * 3072;
    const uint8_t* src = m.xsrc + (size_t)i * (8 * IMG * CH * 2);
    asm volatile("cp.async.bulk.wait_group.read 0;" ::: "memory");
    mbar_expect(bar, 3072);
    bulk_load(dst, src, 1536, bar);
    bulk_load(dst + 1536, src + IMG * CH * 2, 1536, bar);
  }
}
__device__ __forceinline__ void x_wait(const MlpCtx& m, int i) { mbar_wait(m.sb + BAR_XFULL + 8 * (4 * m.wg + m.warp), i & 1); }
__device__ __forceinline__ void x_load(const MlpCtx& m, uint32_t (&x)[24]) {
#pragma unroll
  for (int k = 0; k < 6; k++)
    asm volatile("ld.shared.v4.b32 {%0,%1,%2,%3}, [%4];"
                 : "=r"(x[4 * k]), "=r"(x[4 * k + 1]), "=r"(x[4 * k + 2]), "=r"(x[4 * k + 3])
                 : "r"(m.xaddr + (k / 3) * 384 + (k % 3) * 64)
                 : "memory");
}
template <int LO, int HI>
__device__ __forceinline__ void epilogue(const MlpCtx& m, const uint32_t (&d)[24], uint32_t (&x)[24]) {
#pragma unroll
  for (int k = LO; k < HI; k++) {
    const int r = k / 3, q = k % 3;
    uint32_t* y = &x[4 * k];
#pragma unroll
    for (int j = 0; j < 4; j++) {
      uint32_t v = d[2 * (4 * q + j) + r];
      float lo, hi;
      asm("{\n.reg .b16 l, h;\nmov.b32 {l, h}, %2;\ncvt.f32.f16 %0, l;\ncvt.f32.f16 %1, h;\n}\n" : "=f"(lo), "=f"(hi) : "r"(v));
      asm("fma.rn.bf16x2 %0, %1, %2, %0;" : "+r"(y[j]) : "r"(pack_bf16(lo, hi)), "r"(m.unscale));
    }
    asm volatile("st.shared.v4.b32 [%0], {%1,%2,%3,%4};" ::"r"(m.xaddr + r * 384 + q * 64), "r"(y[0]), "r"(y[1]), "r"(y[2]), "r"(y[3])
                 : "memory");
  }
}
__device__ __forceinline__ void out_store(const MlpCtx& m, int i) {
  asm volatile("fence.proxy.async.shared::cta;" ::: "memory");
  __syncwarp();
  if (elect_one()) {
    const uint32_t src = m.sb + OFF_XRES + (4 * m.wg + m.warp) * 3072;
    uint8_t* dst = m.optr + (size_t)i * (8 * IMG * CH * 2);
    asm volatile("cp.async.bulk.global.shared::cta.bulk_group [%0], [%1], 1536;" ::"l"(dst), "r"(src) : "memory");
    asm volatile("cp.async.bulk.global.shared::cta.bulk_group [%0], [%1], 1536;" ::"l"(dst + IMG * CH * 2), "r"(src + 1536) : "memory");
    asm volatile("cp.async.bulk.commit_group;" ::: "memory");
  }
}

__device__ __forceinline__ void tok_wait(int wg) {
  asm volatile("{\n.reg .pred p;\nsetp.eq.s32 p, %0, 0;\n@p bar.sync %1, 256;\n@!p bar.sync %2, 256;\n}\n" ::"r"(wg), "n"(NB_TOK), "n"(NB_TOK + 1) : "memory");
}
__device__ __forceinline__ void tok_pass(int wg) {
  asm volatile("{\n.reg .pred p;\nsetp.eq.s32 p, %0, 0;\n@p bar.arrive %1, 256;\n@!p bar.arrive %2, 256;\n}\n" ::"r"(wg), "n"(NB_TOK + 1), "n"(NB_TOK + 2) : "memory");
}

constexpr uint64_t CHK = 1152;

__device__ __forceinline__ void mlp_role(const MlpCtx& m0, const __nv_bfloat16* w1, const __nv_bfloat16* w2) {
  MlpCtx m = m0;
  const int lane = threadIdx.x & 31, wid = m.wg * 4 + m.warp;
  {
    uint32_t mx = 0;
    const int k7 = lane & 7;
#pragma unroll 6
    for (int it = 0; it < 18; it++) {
      int item = wid * 18 + it, kb = item / 12, ng = item % 12;
      int Q = 6 * (k7 >> 1) + (kb >> 1), q12 = Q % 12, v = q12 / 3, e = q12 % 3;
      int ch = 48 * (Q / 12) + (e < 2 ? 8 * v + 4 * e : 32 + 4 * v) + 2 * (kb & 1) + (k7 & 1);
      int n8 = ng * 4 + (lane >> 3);
      uint4 w = __ldg(reinterpret_cast<const uint4*>(w1 + ch * 384 + n8 * 8));
      mx = __vmaxu2(mx, __vmaxu2(__vmaxu2(w.x & 0x7fff7fffu, w.y & 0x7fff7fffu), __vmaxu2(w.z & 0x7fff7fffu, w.w & 0x7fff7fffu)));
      uint32_t dst = m.sb + OFF_W1 + ((n8 / 12) * 6 + (kb >> 1)) * 3072 + (kb & 1) * 128 + (n8 % 12) * 256 + k7 * 16;
      asm volatile("st.shared.v4.b32 [%0], {%1,%2,%3,%4};" ::"r"(dst), "r"(pack_f16(bf_lo(w.x), bf_hi(w.x))),
                   "r"(pack_f16(bf_lo(w.y), bf_hi(w.y))), "r"(pack_f16(bf_lo(w.z), bf_hi(w.z))),
                   "r"(pack_f16(bf_lo(w.w), bf_hi(w.w)))
                   : "memory");
    }
    TR(m.wg, 1004);
    uint32_t v2[5][16];
    uint32_t mx2 = 0;
#pragma unroll
    for (int it = 0; it < 5; it++) {
      int item = (it * 8 + wid) * 4 + (lane >> 3);
      if (item > 143) item = 143;
      int kb = item / 3, q = item % 3;
      const uint4* src = reinterpret_cast<const uint4*>(w2 + (kb * 8 + k7) * 96 + q * 32);
#pragma unroll
      for (int t = 0; t < 4; t++) {
        uint4 v = __ldg(src + t);
        v2[it][4 * t] = v.x; v2[it][4 * t + 1] = v.y; v2[it][4 * t + 2] = v.z; v2[it][4 * t + 3] = v.w;
      }
    }
#pragma unroll
    for (int it = 0; it < 5; it++)
#pragma unroll
      for (int t = 0; t < 16; t++) mx2 = __vmaxu2(mx2, v2[it][t] & 0x7fff7fffu);
    TR(m.wg, 1005);
    mx = __reduce_max_sync(0xffffffffu, max(mx & 0xffffu, mx >> 16));
    mx2 = __reduce_max_sync(0xffffffffu, max(mx2 & 0xffffu, mx2 >> 16));
    if (lane == 0) {
      asm volatile("red.shared.max.u32 [%0], %1;" ::"r"(m.sb + OFF_MAX), "r"(mx) : "memory");
      asm volatile("red.shared.max.u32 [%0], %1;" ::"r"(m.sb + OFF_MAX + 4), "r"(mx2) : "memory");
    }
    NB_SYNC(NB_PREP, 256);
    asm volatile("ld.shared.v2.b32 {%0,%1}, [%2];" : "=r"(mx), "=r"(mx2) : "r"(m.sb + OFF_MAX) : "memory");
    TR(m.wg, 1006);
    int e1 = (int)(mx >> 7) - 126, e2 = (int)(mx2 >> 7) - 126;
    int s = min(-1 - e1 - e2, 14 - e2);
    s = max(-120, min(120, s));
    float sc = __uint_as_float((uint32_t)(127 + s) << 23) * (0.5f / GELU_A);
    m.unscale = __shfl_sync(0xffffffffu, ((uint32_t)(127 - s) << 7) * 0x10001u, 0);
#pragma unroll
    for (int it = 0; it < 5; it++) {
      int item = (it * 8 + wid) * 4 + (lane >> 3);
      if (item > 143) item = 143;
      int kb = item / 3, q = item % 3;
      uint32_t dst = m.sb + OFF_W2 + (kb >> 1) * 3072 + (kb & 1) * 128 + q * 1024 + k7 * 16;
#pragma unroll
      for (int j = 0; j < 4; j++) {
        uint32_t o[4];
#pragma unroll
        for (int t = 0; t < 4; t++) o[t] = pack_f16(bf_lo(v2[it][4 * t + j]) * sc, bf_hi(v2[it][4 * t + j]) * sc);
        asm volatile("st.shared.v4.b32 [%0], {%1,%2,%3,%4};" ::"r"(dst + j * 256), "r"(o[0]), "r"(o[1]), "r"(o[2]), "r"(o[3]) : "memory");
      }
    }
    asm volatile("fence.proxy.async.shared::cta;" ::: "memory");
    NB_SYNC(NB_PREP, 256);
  }
  const uint64_t dW1 = (uint64_t)(((m.sb + OFF_W1) & 0x3FFFF) >> 4) | ((uint64_t)8 << 16) | ((uint64_t)16 << 32);
  const uint64_t dW2 = dW1 + (OFF_W2 >> 4);

  TR(m.wg, 1000);
  uint32_t A1[24], g[24], cn[24], D2[24];
  float st[4], dl[2];
  ln_wait(m, 0);
  ln_load(m, cn);
  ln_sum(cn, st);
  ln_release(m);
  ln_hop(st);
  ln_center(cn, st, dl);
  ln_hop(st);
  ln_rstd(cn, st, dl);
  ln_scale(cn, st, dl);
  ln_final(A1, cn);
  [[maybe_unused]] int rho = 2 * m.wg + m.rank;
  for (int r = 0; r < 2 * m.wg + m.rank; r++) { tok_wait(m.wg); tok_pass(m.wg); }
  {
    uint32_t d[24];
    WG_FENCE();
    tok_wait(m.wg);
    gemm6<true>(d, A1, dW1);
    tok_pass(m.wg); PIN();
    WG_WAIT0(); rfence(d);
    gelu<0, 24>(g, d);
    PIN();
    rho++;
  }
#define SLOT(INIT, j2, j1)                  \
  uint32_t d[24];                           \
  WG_FENCE();                               \
  tok_wait(m.wg);                           \
  TR(m.wg, rho * 8);                        \
  gemm6<INIT>(D2, g, dW2 + (j2) * CHK);     \
  WG_FENCE();                               \
  gemm6<true>(d, A1, dW1 + (j1) * CHK);     \
  tok_pass(m.wg); PIN();                    \
  TR(m.wg, rho * 8 + 1);
#define SLOT_END()                          \
  TR(m.wg, rho * 8 + 2);                    \
  PIN(); WG_WAIT0(); rfence(d); rfence(D2); \
  TR(m.wg, rho * 8 + 3);
#define ROUND_END()                         \
  TR(m.wg, rho * 8 + 4);                    \
  PIN(); rho++;
#define EP 4
#pragma unroll 1
  for (int i = 0;; i++) {
    {
      SLOT(true, 0, 1)
      if (i > 0) out_store(m, i - 1);
      if (i < 15) ln_wait(m, i + 1);
      SLOT_END()
      gelu<0, 24>(g, d);
      ROUND_END()
      ln_load(m, cn);
    }
    {
      SLOT(false, 1, 2)
      issue_xres(m, i);
      ln_sum(cn, st);
      if (i < 15) ln_release(m);
      ln_hop(st);
      SLOT_END()
      ln_center(cn, st, dl);
      gelu<0, 24>(g, d);
      ROUND_END()
    }
    {
      SLOT(false, 2, 3)
      ln_hop(st);
      x_wait(m, i);
      ln_rstd(cn, st, dl);
      ln_scale(cn, st, dl);
      SLOT_END()
      ln_final(A1, cn);
      gelu<0, 24>(g, d);
      ROUND_END()
    }
    if (i == 15) break;
    {
      x_load(m, cn);
      SLOT(false, 3, 0)
      WG_WAIT1(); rfence(D2);
      epilogue<0, EP>(m, D2, cn);
      SLOT_END()
      epilogue<EP, 6>(m, D2, cn);
      gelu<0, 24>(g, d);
      ROUND_END()
    }
  }
  x_load(m, cn);
  WG_FENCE();
  tok_wait(m.wg);
  gemm6<false>(D2, g, dW2 + 3 * CHK);
  tok_pass(m.wg); PIN();
  WG_WAIT0(); rfence(D2);
  epilogue<0, 6>(m, D2, cn);
  out_store(m, 15);
  if (m.wg == 0)
    for (int r = 0; r < 2; r++) { tok_wait(0); tok_pass(0); }
  asm volatile("cp.async.bulk.wait_group 0;" ::: "memory");
  TR(m.wg, 1001);
  TRG(1021);
}

struct ConvCtx {
  uint32_t sb;
  uint32_t a_raw, a_c;
  uint32_t peer_off;
  int rank, v, c0, r0, zero;
  const CUtensorMap* tm;
};

__device__ __forceinline__ void conv_refill(const ConvCtx& c, int s) {
  if (c.v == 0 && s + 4 < NSTEP && elect_one()) {
    const int st = s & 3;
    tma_raw(c.sb + OFF_RAW + st * RAW_BYTES, c.tm, 56 * c.rank - 8, c.c0 / 2 - 2, c.r0 - 3 + 2 * (s + 4), c.sb + BAR_RAW + 8 * st);
  }
}
__device__ __forceinline__ void conv_frags(const ConvCtx& c, int s, uint32_t (&A)[12][4]) {
  const int st = s & 3;
  const uint32_t a8 = c.a_raw + st * RAW_BYTES, a4 = a8 + 64 - 8 * c.v;
  uint32_t r[6][6];
  mbar_wait(c.sb + BAR_RAW + 8 * st, (s >> 2) & 1);
#pragma unroll
  for (int j = 0; j < 6; j++)
    asm volatile("ld.shared.v4.b32 {%0,%1,%2,%3}, [%4];"
                 : "=r"(r[j][0]), "=r"(r[j][1]), "=r"(r[j][2]), "=r"(r[j][3])
                 : "r"(a8 + (j >> 1) * 112 + (j & 1) * RAW_PLANE)
                 : "memory");
#pragma unroll
  for (int j = 0; j < 6; j++)
    asm volatile("ld.shared.v2.b32 {%0,%1}, [%2];" : "=r"(r[j][4]), "=r"(r[j][5]) : "r"(a4 + (j >> 1) * 112 + (j & 1) * RAW_PLANE) : "memory");
#pragma unroll
  for (int ch = 0; ch < 12; ch++) {
    const uint32_t sel = (ch & 1) ? 0x7632 : 0x5410;
    A[ch][0] = __byte_perm(r[0][ch >> 1], r[1][ch >> 1], sel);
    A[ch][1] = __byte_perm(r[2][ch >> 1], r[3][ch >> 1], sel);
    A[ch][2] = A[ch][1] ^ c.zero;
    A[ch][3] = __byte_perm(r[4][ch >> 1], r[5][ch >> 1], sel);
  }
}

__device__ __forceinline__ void hmma(float (&d)[4], const uint32_t* a, const uint32_t* b, const float (&cc)[4]) {
  asm volatile("mma.sync.aligned.m16n8k16.row.col.f32.bf16.bf16.f32 {%0,%1,%2,%3}, {%4,%5,%6,%7}, {%8,%9}, {%10,%11,%12,%13};"
               : "=f"(d[0]), "=f"(d[1]), "=f"(d[2]), "=f"(d[3])
               : "r"(a[0]), "r"(a[1]), "r"(a[2]), "r"(a[3]), "r"(b[0]), "r"(b[1]), "f"(cc[0]), "f"(cc[1]), "f"(cc[2]), "f"(cc[3]));
}

template <bool MORE>
__device__ __forceinline__ void conv_step(const ConvCtx& c, int s, float (&K)[12][2], float (&V)[12][4], const uint32_t (&B)[12][4],
                                          uint32_t (&A)[12][4]) {
  float T[12][4];
  const float Z[4] = {0.f, 0.f, 0.f, 0.f};
  TR(2, s * 8);
  if (s >= SIGMA) NB_SYNC(NB_TOK + 2, 256);
  else NB_SYNC(NB_PLAN, 128);
  PIN();
  TR(2, s * 8 + 1);
#pragma unroll
  for (int ch = 0; ch < 12; ch++) {
    hmma(T[ch], A[ch], &B[ch][2], V[ch]);
    hmma(V[ch], A[ch], &B[ch][0], Z);
  }
  PIN();
  if (s >= SIGMA) NB_ARRIVE(NB_TOK, 256);
  TR(2, s * 8 + 2);
  uint32_t pk[12];
#pragma unroll
  for (int q = 0; q < 6; q++) {
    pk[2 * q] = pack_bf16(T[2 * q][1], T[2 * q + 1][1]);
    pk[2 * q + 1] = pack_bf16(T[2 * q][3], T[2 * q + 1][3]);
  }
#pragma unroll
  for (int ch = 0; ch < 12; ch++) {
    V[ch][1] += K[ch][0];
    V[ch][3] += K[ch][1];
    K[ch][0] = __uint_as_float(__float_as_uint(T[ch][0]) ^ c.zero);
    K[ch][1] = __uint_as_float(__float_as_uint(T[ch][2]) ^ c.zero);
  }
  PIN();
  TR(2, s * 8 + 3);
  if (s >= 3) {
    const int tau = s - 3, owner = tau & 1, slot = (tau >> 1) & 1;
    if (tau >= 4) mbar_wait(c.sb + BAR_CEMPTY + 8 * (2 * owner + slot), ((tau >> 2) - 1) & 1);
    const uint32_t off = (owner == c.rank) ? 0u : c.peer_off;
    const uint32_t dst = c.a_c + off + slot * C_BYTES, bar = c.sb + off + BAR_CFULL + 8 * slot;
#pragma unroll
    for (int q = 0; q < 3; q++)
      asm volatile("st.async.weak.shared::cluster.mbarrier::complete_tx::bytes.v4.b32 [%0], {%1,%2,%3,%4}, [%5];" ::"r"(dst + q * 512),
                   "r"(pk[4 * q]), "r"(pk[4 * q + 1]), "r"(pk[4 * q + 2]), "r"(pk[4 * q + 3]), "r"(bar)
                   : "memory");
  }
  TR(2, s * 8 + 4);
  conv_refill(c, s);
  if (MORE) conv_frags(c, s + 1, A);
}

__device__ __forceinline__ void conv_role(const ConvCtx& c, const __nv_bfloat16* dw) {
  const int lane = threadIdx.x & 31, g = lane >> 2, t = lane & 3;
  uint32_t B[12][4];
  {
    const int e = g & 1, dc = (g >> 1) & 1, ro = g >> 2, rk = t >> 1;
    const uint8_t* dwp = reinterpret_cast<const uint8_t*>(dw) + 96 * c.rank;
#pragma unroll
    for (int b = 0; b < 2; b++) {
      const int i = 2 * (2 * e + b) + rk - ro;
      uint32_t w[4][6];
#pragma unroll
      for (int k = 0; k < 4; k++) {
        const int j = 4 * (t & 1) + k - dc;
        const bool ok = i >= 0 && i < 7 && j >= 0 && j < 7;
        uint4 w8 = make_uint4(0, 0, 0, 0);
        uint2 w4 = make_uint2(0, 0);
        if (ok) {
          w8 = __ldg(reinterpret_cast<const uint4*>(dwp + (i * 7 + j) * 192 + 16 * c.v));
          w4 = __ldg(reinterpret_cast<const uint2*>(dwp + (i * 7 + j) * 192 + 64 + 8 * c.v));
        }
        w[k][0] = w8.x; w[k][1] = w8.y; w[k][2] = w8.z; w[k][3] = w8.w; w[k][4] = w4.x; w[k][5] = w4.y;
      }
#pragma unroll
      for (int q = 0; q < 6; q++) {
        B[2 * q][2 * b] = __byte_perm(w[0][q], w[1][q], 0x5410);
        B[2 * q][2 * b + 1] = __byte_perm(w[2][q], w[3][q], 0x5410);
        B[2 * q + 1][2 * b] = __byte_perm(w[0][q], w[1][q], 0x7632);
        B[2 * q + 1][2 * b + 1] = __byte_perm(w[2][q], w[3][q], 0x7632);
      }
    }
  }
  TR(2, 1004);
  float K[12][2], V[12][4];
#pragma unroll
  for (int ch = 0; ch < 12; ch++) {
    K[ch][0] = K[ch][1] = 0.f;
#pragma unroll
    for (int k = 0; k < 4; k++) V[ch][k] = 0.f;
  }
  uint32_t A[12][4];
  conv_frags(c, 0, A);
  NB_ARRIVE(NB_TOK, 256);
#pragma unroll 1
  for (int s = 0; s < NSTEP - 1; s++) conv_step<true>(c, s, K, V, B, A);
  conv_step<false>(c, NSTEP - 1, K, V, B, A);
  for (int r = NSTEP - SIGMA; r < NROUND - 1 + c.rank; r++) { NB_SYNC(NB_TOK + 2, 256); NB_ARRIVE(NB_TOK, 256); }
  NB_SYNC(NB_TOK + 2, 256);
}

__global__ void __cluster_dims__(2, 1, 1) __launch_bounds__(384, 1)
convnext_kernel(const __grid_constant__ CUtensorMap tm, const __nv_bfloat16* __restrict__ x, const __nv_bfloat16* __restrict__ dw,
                const __nv_bfloat16* __restrict__ w1, const __nv_bfloat16* __restrict__ w2, __nv_bfloat16* __restrict__ out,
                int zero) {
  extern __shared__ __align__(1024) uint8_t smem[];
  const uint32_t sb = (uint32_t)__cvta_generic_to_shared(smem);
  const int tid = threadIdx.x, lane = tid & 31;
  const int wid = __shfl_sync(0xffffffffu, tid >> 5, 0);
  const int rank = blockIdx.x & 1, cl = blockIdx.x >> 1;
  const int c0 = (cl & 15) * 32, r0 = (cl >> 4) * 128;
  const uint32_t peer_off = mapa(sb, rank ^ 1) - sb;

  TR(wid >> 2, 1002);
  TRG(1020);
  if (tid == 256) {
    for (int i = 0; i < 4; i++) mbar_init(sb + BAR_RAW + 8 * i, 1);
    for (int i = 0; i < 2; i++) mbar_init(sb + BAR_CFULL + 8 * i, 1);
    for (int i = 0; i < 4; i++) mbar_init(sb + BAR_CEMPTY + 8 * i, 4);
    for (int i = 0; i < 8; i++) mbar_init(sb + BAR_XFULL + 8 * i, 1);
    asm volatile("st.shared.v2.b32 [%0], {%1,%1};" ::"r"(sb + OFF_MAX), "r"(0) : "memory");
    asm volatile("fence.mbarrier_init.release.cluster;" ::: "memory");
    asm volatile("fence.proxy.async.shared::cta;" ::: "memory");
    TR(2, 1006);
    for (int i = 0; i < 4; i++)
      tma_raw(sb + OFF_RAW + i * RAW_BYTES, &tm, 56 * rank - 8, c0 / 2 - 2, r0 - 3 + 2 * i, sb + BAR_RAW + 8 * i);
    for (int i = 0; i < 2; i++) mbar_expect(sb + BAR_CFULL + 8 * i, 12288);
    TR(2, 1007);
  }
  __syncwarp();
  asm volatile("barrier.cluster.arrive.aligned;\nbarrier.cluster.wait.aligned;" ::: "memory");

  TR(wid >> 2, 1003);
  if (wid < 8) {
    MlpCtx m;
    m.sb = sb; m.wg = wid >> 2; m.warp = wid & 3; m.rank = rank; m.peer_off = peer_off;
    m.xsrc = reinterpret_cast<const uint8_t*>(x) + ((size_t)(r0 + 4 * m.wg + 2 * rank) * IMG + c0 + 8 * m.warp) * (CH * 2);
    m.optr = reinterpret_cast<uint8_t*>(out) + ((size_t)(r0 + 4 * m.wg + 2 * rank) * IMG + c0 + 8 * m.warp) * (CH * 2);
    m.caddr = sb + OFF_C + m.wg * C_BYTES + m.warp * 128 + (lane & 3) * (6 * 512 + 32) + (lane >> 2) * 16;
    m.xaddr = sb + OFF_XRES + wid * 3072 + ((lane >> 3) & 1) * 1536 + ((lane >> 4) * 4 + ((lane >> 2) & 1)) * 192 + (lane & 3) * 16;
    m.unscale = 0;
    asm volatile("setmaxnreg.dec.sync.aligned.u32 %0;" ::"n"(REG_MLP));
    mlp_role(m, w1, w2);
    __syncwarp();
    asm volatile("barrier.cluster.arrive.relaxed.aligned;\nbarrier.cluster.wait.aligned;" ::: "memory");
  } else {
    ConvCtx c;
    c.sb = sb; c.rank = rank; c.v = wid - 8; c.c0 = c0; c.r0 = r0; c.zero = zero; c.tm = &tm;
    c.peer_off = peer_off;
    const int g = lane >> 2, t = lane & 3;
    c.a_raw = sb + OFF_RAW + ((t >> 1) * 19 + 2 * (g + (t & 1))) * 112 + (1 - rank) * 16 + 16 * c.v;
    const int q0 = 12 * rank + 3 * c.v;
    c.a_c = sb + OFF_C + q0 * 512 + (q0 / 6) * 32 + lane * 16;
    asm volatile("setmaxnreg.inc.sync.aligned.u32 %0;" ::"n"(REG_CONV));
    conv_role(c, dw);
    __syncwarp();
    asm volatile("barrier.cluster.arrive.relaxed.aligned;\nbarrier.cluster.wait.aligned;\nexit;" ::: "memory");
  }
}

typedef CUresult (*EncodeFn)(CUtensorMap*, CUtensorMapDataType, cuuint32_t, void*, const cuuint64_t*, const cuuint64_t*,
                             const cuuint32_t*, const cuuint32_t*, CUtensorMapInterleave, CUtensorMapSwizzle,
                             CUtensorMapL2promotion, CUtensorMapFloatOOBfill);

}

extern "C" void kernel_launch(void* const* d_in, const int* in_sizes, int n_in, void* d_out, int out_size) {
  const __nv_bfloat16* x = (const __nv_bfloat16*)d_in[0];
  const __nv_bfloat16* dw = (const __nv_bfloat16*)d_in[1];
  const __nv_bfloat16* w1 = (const __nv_bfloat16*)d_in[2];
  const __nv_bfloat16* w2 = (const __nv_bfloat16*)d_in[3];
  __nv_bfloat16* out = (__nv_bfloat16*)d_out;

  static EncodeFn encode = nullptr;
  if (!encode) {
    cudaDriverEntryPointQueryResult st;
    void* fn = nullptr;
    cudaGetDriverEntryPoint("cuTensorMapEncodeTiled", &fn, cudaEnableDefault, &st);
    encode = (EncodeFn)fn;
    cudaFuncSetAttribute(convnext_kernel, cudaFuncAttributeMaxDynamicSharedMemorySize, SMEM_BYTES);
  }
  CUtensorMap tm;
  cuuint64_t dims[4] = {CH, IMG / 2, IMG, 2};
  cuuint64_t strides[3] = {CH * 4, (cuuint64_t)IMG * CH * 2, CH * 2};
  cuuint32_t box[4] = {56, 19, 2, 1};
  cuuint32_t es[4] = {1, 1, 1, 1};
  encode(&tm, CU_TENSOR_MAP_DATA_TYPE_BFLOAT16, 4, (void*)x, dims, strides, box, es, CU_TENSOR_MAP_INTERLEAVE_NONE,
         CU_TENSOR_MAP_SWIZZLE_NONE, CU_TENSOR_MAP_L2_PROMOTION_L2_128B, CU_TENSOR_MAP_FLOAT_OOB_FILL_NONE);
  convnext_kernel<<<128, 384, SMEM_BYTES>>>(tm, x, dw, w1, w2, out, 0);
}
```

```cpp
#include <cuda_runtime.h>
#include <cuda_bf16.h>
#include <cuda.h>
#include <stdint.h>

namespace {

constexpr int IMG = 512, CH = 96;
constexpr int NSTEP = 67;
constexpr int SIGMA = 7;
constexpr int NROUND = 68;

constexpr uint32_t OFF_W1 = 0;
constexpr uint32_t OFF_W2 = 73728;
constexpr uint32_t OFF_RAW = 147456;
constexpr uint32_t RAW_PLANE = 4352;
constexpr uint32_t RAW_BYTES = 2 * RAW_PLANE;
constexpr uint32_t RAW_TX = 2 * 2 * 19 * 112;
constexpr uint32_t OFF_XRES = OFF_RAW + 4 * RAW_BYTES;
constexpr uint32_t OFF_C = OFF_XRES + 2 * 12288;
constexpr uint32_t C_BYTES = 12416;
constexpr uint32_t OFF_BAR = OFF_C + 2 * C_BYTES;
constexpr uint32_t BAR_RAW = OFF_BAR;
constexpr uint32_t BAR_CFULL = OFF_BAR + 32;
constexpr uint32_t BAR_CEMPTY = OFF_BAR + 48;
constexpr uint32_t BAR_XFULL = OFF_BAR + 80;
constexpr uint32_t OFF_MAX = OFF_BAR + 144;
constexpr uint32_t SMEM_BYTES = OFF_BAR + 160;

constexpr float GELU_A = 0.32918364f;
constexpr uint32_t GELU_K2 = 0x40d940d9u;

constexpr int NB_CLOSE = 1, NB_OPEN = 3, NB_PLAN = 4, NB_PREP = 5;
#define REG_MLP 144
constexpr int REG_CONV = 504 - 2 * REG_MLP;

#define WG_FENCE() asm volatile("wgmma.fence.sync.aligned;" ::: "memory")
#define WG_COMMIT() asm volatile("wgmma.commit_group.sync.aligned;" ::: "memory")
#define WG_WAIT0() asm volatile("wgmma.wait_group.sync.aligned 0;" ::: "memory")
#define WG_WAIT1() asm volatile("wgmma.wait_group.sync.aligned 1;" ::: "memory")
#define PIN() asm volatile("pmevent 0;" ::: "memory")
#define NB_SYNC(id, n) asm volatile("bar.sync %0, %1;" ::"n"(id), "n"(n) : "memory")
#define NB_ARRIVE(id, n) asm volatile("bar.arrive %0, %1;" ::"n"(id), "n"(n) : "memory")

#define TR(who, idx)
#define TRG(idx)

#define R24(c, d)                                                                                        \
  c(d[0]), c(d[1]), c(d[2]), c(d[3]), c(d[4]), c(d[5]), c(d[6]), c(d[7]), c(d[8]), c(d[9]), c(d[10]),    \
      c(d[11]), c(d[12]), c(d[13]), c(d[14]), c(d[15]), c(d[16]), c(d[17]), c(d[18]), c(d[19]), c(d[20]), \
      c(d[21]), c(d[22]), c(d[23])
#define WG_TXT(sd)                                                                             \
  "wgmma.mma_async.sync.aligned.m64n96k16.f16.f16.f16 "                                        \
  "{%0,%1,%2,%3,%4,%5,%6,%7,%8,%9,%10,%11,%12,%13,%14,%15,%16,%17,%18,%19,%20,%21,%22,%23}, " \
  "{%24,%25,%26,%27}, %28, " sd ", 1, 1, 1;\n"

__device__ __forceinline__ void wg_acc(uint32_t (&d)[24], const uint32_t* a, uint64_t db) {
  asm volatile(WG_TXT("1") : R24("+r", d) : "r"(a[0]), "r"(a[1]), "r"(a[2]), "r"(a[3]), "l"(db));
}
__device__ __forceinline__ void wg_init(uint32_t (&d)[24], const uint32_t* a, uint64_t db) {
  asm volatile(WG_TXT("0") : R24("=r", d) : "r"(a[0]), "r"(a[1]), "r"(a[2]), "r"(a[3]), "l"(db));
}
__device__ __forceinline__ void wg_pred(uint32_t (&d)[24], const uint32_t* a, uint64_t db, int acc) {
  asm volatile("{\n.reg .pred p;\nsetp.ne.b32 p, %29, 0;\n" WG_TXT("p") "}\n"
               : R24("+r", d)
               : "r"(a[0]), "r"(a[1]), "r"(a[2]), "r"(a[3]), "l"(db), "r"(acc));
}
template <int N>
__device__ __forceinline__ void rfence(uint32_t (&d)[N]) {
#pragma unroll
  for (int i = 0; i < N; i++) asm volatile("" : "+r"(d[i])::"memory");
}
template <bool INIT>
__device__ __forceinline__ void gemm6(uint32_t (&d)[24], const uint32_t (&a)[24], uint64_t db) {
#pragma unroll
  for (int k = 0; k < 6; k++) {
    if (INIT && k == 0) wg_init(d, &a[0], db);
    else wg_acc(d, &a[4 * k], db + k * 192);
  }
  WG_COMMIT();
}

__device__ __forceinline__ void gemm6p(uint32_t (&d)[24], const uint32_t (&a)[24], uint64_t db, int acc) {
  wg_pred(d, &a[0], db, acc);
#pragma unroll
  for (int k = 1; k < 6; k++) wg_acc(d, &a[4 * k], db + k * 192);
  WG_COMMIT();
}

__device__ __forceinline__ void mbar_init(uint32_t bar, uint32_t cnt) {
  asm volatile("mbarrier.init.shared::cta.b64 [%0], %1;" ::"r"(bar), "r"(cnt) : "memory");
}
__device__ __forceinline__ void mbar_expect(uint32_t bar, uint32_t bytes) {
  asm volatile("mbarrier.arrive.expect_tx.shared::cta.b64 _, [%0], %1;" ::"r"(bar), "r"(bytes) : "memory");
}
__device__ __forceinline__ void mbar_arrive_cluster(uint32_t bar) {
  asm volatile("mbarrier.arrive.shared::cluster.b64 _, [%0];" ::"r"(bar) : "memory");
}
__device__ __forceinline__ bool mbar_try(uint32_t bar, uint32_t parity) {
  uint32_t ok;
  asm volatile(
      "{\n.reg .pred p;\nmbarrier.try_wait.parity.shared::cta.b64 p, [%1], %2;\nselp.u32 %0, 1, 0, p;\n}\n"
      : "=r"(ok)
      : "r"(bar), "r"(parity)
      : "memory");
  return ok;
}
__device__ __forceinline__ void mbar_wait(uint32_t bar, uint32_t parity) {
  if (__builtin_expect(mbar_try(bar, parity), 1)) return;
#pragma unroll 1
  for (uint32_t n = 0; n < (1u << 16) && !mbar_try(bar, parity); n++) {}
}
__device__ __forceinline__ uint32_t mapa(uint32_t addr, uint32_t rank) {
  uint32_t r;
  asm("mapa.shared::cluster.u32 %0, %1, %2;" : "=r"(r) : "r"(addr), "r"(rank));
  return r;
}
__device__ __forceinline__ void tma_raw(uint32_t dst, const CUtensorMap* tm, int c, int w2, int h, uint32_t bar) {
  mbar_expect(bar, RAW_TX);
#pragma unroll
  for (int e = 0; e < 2; e++)
    asm volatile(
        "cp.async.bulk.tensor.4d.shared::cluster.global.mbarrier::complete_tx::bytes [%0], [%1, {%2, %3, %4, %5}], [%6];"
        ::"r"(dst + e * RAW_PLANE), "l"(tm), "r"(c), "r"(w2 + e), "r"(h), "r"(1 - e), "r"(bar)
        : "memory");
}
__device__ __forceinline__ void bulk_load(uint32_t dst, const void* src, uint32_t bytes, uint32_t bar) {
  asm volatile("cp.async.bulk.shared::cluster.global.mbarrier::complete_tx::bytes [%0], [%1], %2, [%3];" ::"r"(dst),
               "l"(src), "r"(bytes), "r"(bar)
               : "memory");
}
__device__ __forceinline__ uint32_t pack_bf16(float lo, float hi) {
  uint32_t r;
  asm("cvt.rn.bf16x2.f32 %0, %1, %2;" : "=r"(r) : "f"(hi), "f"(lo));
  return r;
}
__device__ __forceinline__ uint32_t pack_f16(float lo, float hi) {
  uint32_t r;
  asm("cvt.rn.f16x2.f32 %0, %1, %2;" : "=r"(r) : "f"(hi), "f"(lo));
  return r;
}
__device__ __forceinline__ float bf_lo(uint32_t v) { return __uint_as_float(v << 16); }
__device__ __forceinline__ float bf_hi(uint32_t v) { return __uint_as_float(v & 0xffff0000u); }
__device__ __forceinline__ uint32_t bf_add(uint32_t a, uint32_t b) {
  uint32_t r;
  asm("add.rn.bf16x2 %0, %1, %2;" : "=r"(r) : "r"(a), "r"(b));
  return r;
}
__device__ __forceinline__ uint32_t bf_mul(uint32_t a, uint32_t b) {
  uint32_t r;
  asm("mul.rn.bf16x2 %0, %1, %2;" : "=r"(r) : "r"(a), "r"(b));
  return r;
}
__device__ __forceinline__ uint32_t bf_fma(uint32_t a, uint32_t b, uint32_t c) {
  uint32_t r;
  asm("fma.rn.bf16x2 %0, %1, %2, %3;" : "=r"(r) : "r"(a), "r"(b), "r"(c));
  return r;
}

template <int LO, int HI>
__device__ __forceinline__ void gelu(uint32_t (&o)[24], const uint32_t (&d)[24]) {
#pragma unroll
  for (int qq = LO; qq < HI; qq++) {
    const int q = (qq + 4) % 24;
    uint32_t t, u;
    asm("fma.rn.f16x2 %0, %1, %1, %2;" : "=r"(t) : "r"(d[q]), "r"(GELU_K2));
    asm("mul.rn.f16x2 %0, %1, %2;" : "=r"(u) : "r"(d[q]), "r"(t));
    asm("tanh.approx.f16x2 %0, %1;" : "=r"(t) : "r"(u));
    asm("fma.rn.f16x2 %0, %1, %2, %1;" : "=r"(o[q]) : "r"(d[q]), "r"(t));
  }
}

__device__ __forceinline__ uint32_t laneid() {
  uint32_t l;
  asm volatile("mov.u32 %0, %%laneid;" : "=r"(l));
  return l;
}

__device__ __forceinline__ bool elect_one() {
  uint32_t p;
  asm volatile("{\n.reg .pred p;\nelect.sync _|p, 0xffffffff;\nselp.u32 %0, 1, 0, p;\n}\n" : "=r"(p));
  return p;
}

struct MlpCtx {
  uint32_t sb;
  uint32_t caddr;
  uint32_t xaddr;
  uint32_t unscale;
  uint32_t peer_off;
  int wg, warp, rank, zero;
  const uint8_t* xsrc;
  uint8_t* optr;
};

__device__ __forceinline__ void ln_wait(const MlpCtx& m, int i) { mbar_wait(m.sb + BAR_CFULL + 8 * m.wg, i & 1); }
__device__ __forceinline__ void ln_load(const MlpCtx& m, uint32_t (&c)[24]) {
#pragma unroll
  for (int p = 0; p < 6; p++)
    asm volatile("ld.shared.v4.b32 {%0,%1,%2,%3}, [%4];"
                 : "=r"(c[4 * p]), "=r"(c[4 * p + 1]), "=r"(c[4 * p + 2]), "=r"(c[4 * p + 3])
                 : "r"(m.caddr + p * 512)
                 : "memory");
}
__device__ __forceinline__ void ln_shfl(float (&st)[8]) {
#pragma unroll
  for (int k = 1; k < 4; k++) {
    st[2 * k] = __shfl_xor_sync(0xffffffffu, st[0], k);
    st[2 * k + 1] = __shfl_xor_sync(0xffffffffu, st[1], k);
  }
}
__device__ __forceinline__ float ln_total(const float (&st)[8], int r) { return (st[r] + st[r + 2]) + (st[r + 4] + st[r + 6]); }
__device__ __forceinline__ void ln_sum(const uint32_t (&c)[24], float (&st)[8]) {
#pragma unroll
  for (int r = 0; r < 2; r++) {
    uint32_t s0 = bf_add(c[r], c[r + 2]), s1 = bf_add(c[r + 4], c[r + 6]), s2 = bf_add(c[r + 8], c[r + 10]);
    uint32_t s3 = bf_add(c[r + 12], c[r + 14]), s4 = bf_add(c[r + 16], c[r + 18]), s5 = bf_add(c[r + 20], c[r + 22]);
    s0 = bf_add(s0, s1); s2 = bf_add(s2, s3); s4 = bf_add(s4, s5);
    s0 = bf_add(bf_add(s0, s2), s4);
    st[r] = bf_lo(s0) + bf_hi(s0);
  }
}
__device__ __forceinline__ void ln_release(const MlpCtx& m, bool on) {
  const uint32_t e = m.sb + BAR_CEMPTY + 8 * (2 * m.rank + m.wg);
  asm volatile(
      "{\n.reg .pred p, q;\nelect.sync _|p, 0xffffffff;\nsetp.ne.and.s32 p, %4, 0, p;\nsetp.eq.and.s32 q, %3, 0, p;\n"
      "@q mbarrier.arrive.expect_tx.shared::cta.b64 _, [%0], 12288;\n"
      "@p mbarrier.arrive.shared::cluster.b64 _, [%1];\n"
      "@p mbarrier.arrive.shared::cluster.b64 _, [%2];\n}\n" ::"r"(m.sb + BAR_CFULL + 8 * m.wg),
      "r"(e), "r"(e + m.peer_off), "r"(m.warp), "r"((int)on)
      : "memory");
}
__device__ __forceinline__ void ln_center(uint32_t (&c)[24], float (&st)[8], float (&dl)[2]) {
#pragma unroll
  for (int r = 0; r < 2; r++) {
    float nm = ln_total(st, r) * (-1.0f / 96.0f);
    uint32_t nm2 = pack_bf16(nm, nm);
    dl[r] = nm - bf_hi(nm2);
#pragma unroll
    for (int p = 0; p < 12; p++) c[2 * p + r] = bf_add(c[2 * p + r], nm2);
    uint32_t q0 = bf_mul(c[r], c[r]), q1 = bf_mul(c[r + 2], c[r + 2]);
#pragma unroll
    for (int p = 2; p < 12; p += 2) {
      q0 = bf_fma(c[2 * p + r], c[2 * p + r], q0);
      q1 = bf_fma(c[2 * p + 2 + r], c[2 * p + 2 + r], q1);
    }
    q0 = bf_add(q0, q1);
    st[r] = bf_lo(q0) + bf_hi(q0);
  }
}
__device__ __forceinline__ void ln_guard(uint32_t (&c)[24], float (&st)[8], float (&dl)[2]) {
  if (__builtin_expect(__any_sync(0xffffffffu, fmaxf(st[0], st[1]) > 0x1p26f), 0)) {
#pragma unroll
    for (int r = 0; r < 2; r++) {
      float mx = fmaxf(st[r], __shfl_xor_sync(0xffffffffu, st[r], 1));
      mx = fmaxf(mx, __shfl_xor_sync(0xffffffffu, mx, 2));
      int k = max(0, ((int)(__float_as_uint(mx) >> 23) - (127 + 20)) >> 1);
      uint32_t e = (uint32_t)(127 - k) << 23;
      uint32_t e2 = (e >> 16) | e;
#pragma unroll
      for (int p = 0; p < 12; p++) asm volatile("mul.rn.bf16x2 %0, %0, %1;" : "+r"(c[2 * p + r]) : "r"(e2));
      st[r] = st[r] * __uint_as_float(e) * __uint_as_float(e);
      dl[r] *= __uint_as_float(e);
    }
  }
}
__device__ __forceinline__ void ln_scale(uint32_t (&c)[24], const float (&st)[8], const float (&dl)[2]) {
#pragma unroll
  for (int r = 0; r < 2; r++) {
    float rs;
    asm("rsqrt.approx.ftz.f32 %0, %1;" : "=f"(rs) : "f"(fmaf(ln_total(st, r), 1.0f / 96.0f, 1e-5f)));
    float rr = rs * (GELU_A * 0x1p-112f), dd = dl[r] * rr;
    uint32_t r2 = pack_bf16(rr, rr), d2 = pack_bf16(dd, dd);
#pragma unroll
    for (int p = 0; p < 12; p++) c[2 * p + r] = bf_fma(c[2 * p + r], r2, d2);
  }
}
__device__ __forceinline__ void ln_final(uint32_t (&a)[24], const uint32_t (&c)[24]) {
#pragma unroll
  for (int p = 0; p < 24; p++) a[p] = (c[p] & 0x7fff7fffu) * 7u + c[p];
}

__device__ __forceinline__ void issue_xres(const MlpCtx& m, int i) {
  if (elect_one()) {
    uint32_t bar = m.sb + BAR_XFULL + 8 * (4 * m.wg + m.warp);
    uint32_t dst = m.sb + OFF_XRES + (4 * m.wg + m.warp) * 3072;
    const uint8_t* src = m.xsrc + (size_t)i * (8 * IMG * CH * 2);
    asm volatile("cp.async.bulk.wait_group.read 0;" ::: "memory");
    mbar_expect(bar, 3072);
    bulk_load(dst, src, 1536, bar);
    bulk_load(dst + 1536, src + IMG * CH * 2, 1536, bar);
  }
}
__device__ __forceinline__ void x_wait(const MlpCtx& m, int i) { mbar_wait(m.sb + BAR_XFULL + 8 * (4 * m.wg + m.warp), i & 1); }
__device__ __forceinline__ void x_load(const MlpCtx& m, uint32_t (&x)[24]) {
#pragma unroll
  for (int k = 0; k < 6; k++)
    asm volatile("ld.shared.v4.b32 {%0,%1,%2,%3}, [%4];"
                 : "=r"(x[4 * k]), "=r"(x[4 * k + 1]), "=r"(x[4 * k + 2]), "=r"(x[4 * k + 3])
                 : "r"(m.xaddr + (k / 3) * 384 + (k % 3) * 64)
                 : "memory");
}
template <int LO, int HI>
__device__ __forceinline__ void epilogue(const MlpCtx& m, const uint32_t (&d)[24], uint32_t (&x)[24]) {
#pragma unroll
  for (int k = LO; k < HI; k++) {
    const int r = k / 3, q = k % 3;
    uint32_t* y = &x[4 * k];
#pragma unroll
    for (int j = 0; j < 4; j++) {
      uint32_t v = d[2 * (4 * q + j) + r];
      float lo, hi;
      asm("{\n.reg .b16 l, h;\nmov.b32 {l, h}, %2;\ncvt.f32.f16 %0, l;\ncvt.f32.f16 %1, h;\n}\n" : "=f"(lo), "=f"(hi) : "r"(v));
      asm("fma.rn.bf16x2 %0, %1, %2, %0;" : "+r"(y[j]) : "r"(pack_bf16(lo, hi)), "r"(m.unscale));
    }
    asm volatile("st.shared.v4.b32 [%0], {%1,%2,%3,%4};" ::"r"(m.xaddr + r * 384 + q * 64), "r"(y[0]), "r"(y[1]), "r"(y[2]), "r"(y[3])
                 : "memory");
  }
}
__device__ __forceinline__ void out_store(const MlpCtx& m, int i) {
  asm volatile("fence.proxy.async.shared::cta;" ::: "memory");
  __syncwarp();
  if (elect_one()) {
    const uint32_t src = m.sb + OFF_XRES + (4 * m.wg + m.warp) * 3072;
    uint8_t* dst = m.optr + (size_t)i * (8 * IMG * CH * 2);
    asm volatile("cp.async.bulk.global.shared::cta.bulk_group [%0], [%1], 1536;" ::"l"(dst), "r"(src) : "memory");
    asm volatile("cp.async.bulk.global.shared::cta.bulk_group [%0], [%1], 1536;" ::"l"(dst + IMG * CH * 2), "r"(src + 1536) : "memory");
    asm volatile("cp.async.bulk.commit_group;" ::: "memory");
  }
}

__device__ __forceinline__ void tok_wait(int wg) {
  asm volatile("{\n.reg .pred p;\nsetp.eq.s32 p, %0, 0;\n@p bar.sync %1, 256;\n@!p bar.sync %2, 256;\n}\n" ::"r"(wg), "n"(NB_CLOSE), "n"(NB_CLOSE + 1) : "memory");
}
__device__ __forceinline__ void tok_pass() { NB_ARRIVE(NB_OPEN, 384); }

constexpr uint64_t CHK = 1152;

__device__ __forceinline__ void mlp_role(const MlpCtx& m0, const __nv_bfloat16* w1, const __nv_bfloat16* w2) {
  MlpCtx m = m0;
  const int lane = threadIdx.x & 31, wid = m.wg * 4 + m.warp;
  {
    uint32_t mx = 0;
    const int k7 = lane & 7;
#pragma unroll 6
    for (int it = 0; it < 18; it++) {
      int item = wid * 18 + it, kb = item / 12, ng = item % 12;
      int Q = 6 * (k7 >> 1) + (kb >> 1), q12 = Q % 12, v = q12 / 3, e = q12 % 3;
      int ch = 48 * (Q / 12) + (e < 2 ? 8 * v + 4 * e : 32 + 4 * v) + 2 * (kb & 1) + (k7 & 1);
      int n8 = ng * 4 + (lane >> 3);
      uint4 w = __ldg(reinterpret_cast<const uint4*>(w1 + ch * 384 + n8 * 8));
      mx = __vmaxu2(mx, __vmaxu2(__vmaxu2(w.x & 0x7fff7fffu, w.y & 0x7fff7fffu), __vmaxu2(w.z & 0x7fff7fffu, w.w & 0x7fff7fffu)));
      uint32_t dst = m.sb + OFF_W1 + ((n8 / 12) * 6 + (kb >> 1)) * 3072 + (kb & 1) * 128 + (n8 % 12) * 256 + k7 * 16;
      asm volatile("st.shared.v4.b32 [%0], {%1,%2,%3,%4};" ::"r"(dst), "r"(pack_f16(bf_lo(w.x), bf_hi(w.x))),
                   "r"(pack_f16(bf_lo(w.y), bf_hi(w.y))), "r"(pack_f16(bf_lo(w.z), bf_hi(w.z))),
                   "r"(pack_f16(bf_lo(w.w), bf_hi(w.w)))
                   : "memory");
    }
    TR(m.wg, 1004);
    uint32_t v2[5][16];
    uint32_t mx2 = 0;
#pragma unroll
    for (int it = 0; it < 5; it++) {
      int item = (it * 8 + wid) * 4 + (lane >> 3);
      if (item > 143) item = 143;
      int kb = item / 3, q = item % 3;
      const uint4* src = reinterpret_cast<const uint4*>(w2 + (kb * 8 + k7) * 96 + q * 32);
#pragma unroll
      for (int t = 0; t < 4; t++) {
        uint4 v = __ldg(src + t);
        v2[it][4 * t] = v.x; v2[it][4 * t + 1] = v.y; v2[it][4 * t + 2] = v.z; v2[it][4 * t + 3] = v.w;
      }
    }
#pragma unroll
    for (int it = 0; it < 5; it++)
#pragma unroll
      for (int t = 0; t < 16; t++) mx2 = __vmaxu2(mx2, v2[it][t] & 0x7fff7fffu);
    TR(m.wg, 1005);
    mx = __reduce_max_sync(0xffffffffu, max(mx & 0xffffu, mx >> 16));
    mx2 = __reduce_max_sync(0xffffffffu, max(mx2 & 0xffffu, mx2 >> 16));
    if (lane == 0) {
      asm volatile("red.shared.max.u32 [%0], %1;" ::"r"(m.sb + OFF_MAX), "r"(mx) : "memory");
      asm volatile("red.shared.max.u32 [%0], %1;" ::"r"(m.sb + OFF_MAX + 4), "r"(mx2) : "memory");
    }
    NB_SYNC(NB_PREP, 256);
    asm volatile("ld.shared.v2.b32 {%0,%1}, [%2];" : "=r"(mx), "=r"(mx2) : "r"(m.sb + OFF_MAX) : "memory");
    TR(m.wg, 1006);
    int e1 = (int)(mx >> 7) - 126, e2 = (int)(mx2 >> 7) - 126;
    int s = min(-1 - e1 - e2, 14 - e2);
    s = max(-120, min(120, s));
    float sc = __uint_as_float((uint32_t)(127 + s) << 23) * (0.5f / GELU_A);
    m.unscale = __shfl_sync(0xffffffffu, ((uint32_t)(127 - s) << 7) * 0x10001u, 0);
#pragma unroll
    for (int it = 0; it < 5; it++) {
      int item = (it * 8 + wid) * 4 + (lane >> 3);
      if (item > 143) item = 143;
      int kb = item / 3, q = item % 3;
      uint32_t dst = m.sb + OFF_W2 + (kb >> 1) * 3072 + (kb & 1) * 128 + q * 1024 + k7 * 16;
#pragma unroll
      for (int j = 0; j < 4; j++) {
        uint32_t o[4];
#pragma unroll
        for (int t = 0; t < 4; t++) o[t] = pack_f16(bf_lo(v2[it][4 * t + j]) * sc, bf_hi(v2[it][4 * t + j]) * sc);
        asm volatile("st.shared.v4.b32 [%0], {%1,%2,%3,%4};" ::"r"(dst + j * 256), "r"(o[0]), "r"(o[1]), "r"(o[2]), "r"(o[3]) : "memory");
      }
    }
    asm volatile("fence.proxy.async.shared::cta;" ::: "memory");
    NB_SYNC(NB_PREP, 256);
  }
  const uint64_t dW1 = (uint64_t)(((m.sb + OFF_W1) & 0x3FFFF) >> 4) | ((uint64_t)8 << 16) | ((uint64_t)16 << 32);
  const uint64_t dW2 = dW1 + (OFF_W2 >> 4);

  TR(m.wg, 1000);
  uint32_t A1[24], g[24], d[24], cn[24], D2[24];
  float st[8], dl[2];
  ln_wait(m, 0);
  ln_load(m, cn);
  ln_sum(cn, st);
  ln_shfl(st);
  ln_release(m, true);
  ln_center(cn, st, dl);
  ln_guard(cn, st, dl);
  ln_shfl(st);
  ln_scale(cn, st, dl);
  ln_final(A1, cn);
  [[maybe_unused]] int rho = 2 * m.wg + m.rank + 2;
#pragma unroll 1
  for (int r = 0; r < 2 * m.wg + m.rank; r++) { tok_wait(m.wg); tok_pass(); }
  {
    uint32_t d0[24];
    WG_FENCE();
    tok_wait(m.wg);
    gemm6<true>(d0, A1, dW1);
    tok_pass(); PIN();
    WG_WAIT0(); rfence(d0);
    WG_FENCE();
    tok_wait(m.wg);
    gemm6<true>(d, A1, dW1 + CHK);
    tok_pass(); PIN();
    gelu<0, 24>(g, d0);
    PIN();
    WG_WAIT0(); rfence(d);
  }
#define G2(INIT, a, j)                      \
  WG_FENCE();                               \
  tok_wait(m.wg);                           \
  TR(m.wg, rho * 8);                        \
  gemm6<INIT>(D2, a, dW2 + (j) * CHK);      \
  PIN();                                    \
  TR(m.wg, rho * 8 + 1);
#define G1(dst, j)                          \
  TR(m.wg, rho * 8 + 2);                    \
  PIN(); WG_WAIT0(); rfence(D2);            \
  WG_FENCE();                               \
  gemm6<true>(dst, A1, dW1 + (j) * CHK);    \
  tok_pass(); PIN();                        \
  TR(m.wg, rho * 8 + 3);
#define ROUND_END(dst)                      \
  TR(m.wg, rho * 8 + 4);                    \
  PIN(); WG_WAIT0(); rfence(dst); rho++;
#define GA 12
#define GB 8
#define GC 9
#define GD 14
#pragma unroll 1
  for (int i = 0;; i++) {
    uint32_t g1[24], g2[24], g3[24], g4[24];
    uint32_t (&d2)[24] = g, (&d3)[24] = g1, (&d0)[24] = g2;
    G2(true, g, 0)
    if (i > 0) out_store(m, i - 1);
    if (i < 15) ln_wait(m, i + 1);
    ln_load(m, cn);
    gelu<0, GA>(g1, d);
    G1(d2, 2)
    ln_sum(cn, st);
    ln_shfl(st);
    ln_release(m, i < 15);
    gelu<GA, 24>(g1, d);
    ROUND_END(d2)

    G2(false, g1, 1)
    ln_center(cn, st, dl);
    gelu<0, GB>(g2, d2);
    PIN();
    ln_guard(cn, st, dl);
    ln_shfl(st);
    G1(d3, 3)
    issue_xres(m, i);
    ln_scale(cn, st, dl);
    gelu<GB, 24>(g2, d2);
    ROUND_END(d3)

    if (i == 15) {
      G2(false, g2, 2)
      tok_pass();
      x_wait(m, i);
      x_load(m, cn);
      gelu<0, 24>(g3, d3);
      ROUND_END(D2)
      G2(false, g3, 3)
      tok_pass();
      WG_WAIT0(); rfence(D2);
      epilogue<0, 6>(m, D2, cn);
      break;
    }
    G2(false, g2, 2)
    ln_final(A1, cn);
    gelu<0, GC>(g3, d3);
    G1(d0, 0)
    x_wait(m, i);
    x_load(m, cn);
    gelu<GC, 24>(g3, d3);
    ROUND_END(d0)

    G2(false, g3, 3)
    gelu<0, GD>(g4, d0);
    G1(g3, 1)
    epilogue<0, 6>(m, D2, cn);
    gelu<GD, 24>(g4, d0);
    ROUND_END(g3)
#pragma unroll
    for (int k = 0; k < 24; k++) { g[k] = g4[k]; d[k] = g3[k]; }
  }
  out_store(m, 15);
  if (m.wg == 0)
    for (int r = 0; r < 2; r++) { tok_wait(0); tok_pass(); }
  asm volatile("cp.async.bulk.wait_group 0;" ::: "memory");
  TR(m.wg, 1001);
  TRG(1021);
}

struct ConvCtx {
  uint32_t sb;
  uint32_t a_raw, a_c;
  uint32_t peer_off;
  int rank, v, c0, r0, zero;
  const CUtensorMap* tm;
};

__device__ __forceinline__ void conv_ld8(uint32_t a, uint32_t (&r)[6][6]) {
#pragma unroll
  for (int j = 0; j < 6; j++)
    asm volatile("ld.shared.v4.b32 {%0,%1,%2,%3}, [%4];"
                 : "=r"(r[j][0]), "=r"(r[j][1]), "=r"(r[j][2]), "=r"(r[j][3])
                 : "r"(a + (j >> 1) * 112 + (j & 1) * RAW_PLANE)
                 : "memory");
}
__device__ __forceinline__ void conv_ld4(uint32_t a, uint32_t (&r)[6][6]) {
#pragma unroll
  for (int j = 0; j < 6; j++)
    asm volatile("ld.shared.v2.b32 {%0,%1}, [%2];" : "=r"(r[j][4]), "=r"(r[j][5]) : "r"(a + (j >> 1) * 112 + (j & 1) * RAW_PLANE) : "memory");
}
__device__ __forceinline__ void conv_frags(const ConvCtx& c, const uint32_t (&r)[6][6], uint32_t (&A)[12][4]) {
#pragma unroll
  for (int ch = 0; ch < 12; ch++) {
    const uint32_t sel = (ch & 1) ? 0x7632 : 0x5410;
    A[ch][0] = __byte_perm(r[0][ch >> 1], r[1][ch >> 1], sel);
    A[ch][1] = __byte_perm(r[2][ch >> 1], r[3][ch >> 1], sel);
    A[ch][2] = A[ch][1] ^ c.zero;
    A[ch][3] = __byte_perm(r[4][ch >> 1], r[5][ch >> 1], sel);
  }
}
__device__ __forceinline__ uint32_t clock_pin() {
  uint32_t t;
  asm volatile("mov.u32 %0, %%clock;" : "=r"(t)::"memory");
  return t;
}

__device__ __forceinline__ void hmma(float (&d)[4], const uint32_t* a, const uint32_t* b, const float (&cc)[4]) {
  asm volatile("mma.sync.aligned.m16n8k16.row.col.f32.bf16.bf16.f32 {%0,%1,%2,%3}, {%4,%5,%6,%7}, {%8,%9}, {%10,%11,%12,%13};"
               : "=f"(d[0]), "=f"(d[1]), "=f"(d[2]), "=f"(d[3])
               : "r"(a[0]), "r"(a[1]), "r"(a[2]), "r"(a[3]), "r"(b[0]), "r"(b[1]), "f"(cc[0]), "f"(cc[1]), "f"(cc[2]), "f"(cc[3]));
}

template <bool GATED, bool MORE>
__device__ __forceinline__ void conv_step(const ConvCtx& c, int s, float (&K)[12][2], float (&V)[12][4], const uint32_t (&B)[12][4],
                                          uint32_t (&A)[12][4]) {
  const int nx = (s + 1) & 3;
  const int owner = nx & 1, slot = nx >> 1, par = ((s + 1) >> 2) & 1;
  float T[12][4];
  uint32_t r[6][6];
  const float Z[4] = {0.f, 0.f, 0.f, 0.f};
  const uint32_t off = (owner == c.rank) ? 0u : c.peer_off;
  uint32_t araw = c.a_raw + nx * RAW_BYTES, dst = c.a_c + off + slot * C_BYTES, bar = c.sb + off + BAR_CFULL + 8 * slot;
  if (MORE) mbar_wait(c.sb + BAR_RAW + 8 * nx, par);
  if (GATED) mbar_wait(c.sb + BAR_CEMPTY + 8 * (2 * owner + slot), par);
  asm volatile("" : "+r"(araw), "+r"(dst), "+r"(bar));
  TR(2, s * 8);
  PIN();
  if (GATED) NB_SYNC(NB_OPEN, 384);
  else NB_SYNC(NB_PLAN, 128);
  if (MORE) conv_ld8(araw, r);
  PIN();
  TR(2, s * 8 + 1);
#pragma unroll
  for (int ch = 0; ch < 12; ch++) {
    hmma(T[ch], A[ch], &B[ch][2], V[ch]);
    hmma(V[ch], A[ch], &B[ch][0], Z);
  }
  const uint32_t z1 = clock_pin();
  if (GATED) { NB_ARRIVE(NB_CLOSE, 256); NB_ARRIVE(NB_CLOSE + 1, 256); }
  PIN();
  TR(2, s * 8 + 2);
  uint32_t pk[12];
#pragma unroll
  for (int q = 0; q < 6; q++) {
    pk[2 * q] = pack_bf16(T[2 * q][1], T[2 * q + 1][1]);
    pk[2 * q + 1] = pack_bf16(T[2 * q][3], T[2 * q + 1][3]);
  }
  if (GATED || s >= 3) {
#pragma unroll
    for (int q = 0; q < 3; q++)
      asm volatile("st.async.weak.shared::cluster.mbarrier::complete_tx::bytes.v4.b32 [%0], {%1,%2,%3,%4}, [%5];" ::"r"(dst + q * 512),
                   "r"(pk[4 * q]), "r"(pk[4 * q + 1]), "r"(pk[4 * q + 2]), "r"(pk[4 * q + 3]), "r"(bar)
                   : "memory");
  }
#pragma unroll
  for (int ch = 0; ch < 12; ch++) {
    V[ch][1] += K[ch][0];
    V[ch][3] += K[ch][1];
    K[ch][0] = __uint_as_float(__float_as_uint(T[ch][0]) ^ (ch == 11 ? c.zero & z1 : c.zero));
    K[ch][1] = __uint_as_float(__float_as_uint(T[ch][2]) ^ c.zero);
    asm volatile("" : "+f"(V[ch][1]), "+f"(V[ch][3]), "+f"(K[ch][0]), "+f"(K[ch][1]));
  }
  PIN();
  TR(2, s * 8 + 3);
  if (MORE) {
    conv_ld4(araw + 64 - 8 * c.v, r);
    conv_frags(c, r, A);
#pragma unroll
    for (int ch = 0; ch < 12; ch++) rfence(A[ch]);
  }
  PIN();
  TR(2, s * 8 + 4);
  if (c.v == (s & 3) && s + 4 < NSTEP && elect_one())
    tma_raw(c.sb + OFF_RAW + c.v * RAW_BYTES, c.tm, 56 * c.rank - 8, c.c0 / 2 - 2, c.r0 - 3 + 2 * (s + 4), c.sb + BAR_RAW + 8 * c.v);
}

__device__ __forceinline__ void conv_role(const ConvCtx& c, const __nv_bfloat16* dw) {
  const int lane = threadIdx.x & 31, g = lane >> 2, t = lane & 3;
  uint32_t B[12][4];
  {
    const int e = g & 1, dc = (g >> 1) & 1, ro = g >> 2, rk = t >> 1;
    const uint8_t* dwp = reinterpret_cast<const uint8_t*>(dw) + 96 * c.rank;
#pragma unroll
    for (int b = 0; b < 2; b++) {
      const int i = 2 * (2 * e + b) + rk - ro;
      uint32_t w[4][6];
#pragma unroll
      for (int k = 0; k < 4; k++) {
        const int j = 4 * (t & 1) + k - dc;
        const bool ok = i >= 0 && i < 7 && j >= 0 && j < 7;
        uint4 w8 = make_uint4(0, 0, 0, 0);
        uint2 w4 = make_uint2(0, 0);
        if (ok) {
          w8 = __ldg(reinterpret_cast<const uint4*>(dwp + (i * 7 + j) * 192 + 16 * c.v));
          w4 = __ldg(reinterpret_cast<const uint2*>(dwp + (i * 7 + j) * 192 + 64 + 8 * c.v));
        }
        w[k][0] = w8.x; w[k][1] = w8.y; w[k][2] = w8.z; w[k][3] = w8.w; w[k][4] = w4.x; w[k][5] = w4.y;
      }
#pragma unroll
      for (int q = 0; q < 6; q++) {
        B[2 * q][2 * b] = __byte_perm(w[0][q], w[1][q], 0x5410);
        B[2 * q][2 * b + 1] = __byte_perm(w[2][q], w[3][q], 0x5410);
        B[2 * q + 1][2 * b] = __byte_perm(w[0][q], w[1][q], 0x7632);
        B[2 * q + 1][2 * b + 1] = __byte_perm(w[2][q], w[3][q], 0x7632);
      }
    }
  }
  TR(2, 1004);
  float K[12][2], V[12][4];
#pragma unroll
  for (int ch = 0; ch < 12; ch++) {
    K[ch][0] = K[ch][1] = 0.f;
#pragma unroll
    for (int k = 0; k < 4; k++) V[ch][k] = 0.f;
  }
  uint32_t A[12][4];
  {
    uint32_t r[6][6];
    mbar_wait(c.sb + BAR_RAW, 0);
    conv_ld8(c.a_raw, r);
    conv_ld4(c.a_raw + 64 - 8 * c.v, r);
    conv_frags(c, r, A);
  }
  NB_ARRIVE(NB_CLOSE, 256);
  NB_ARRIVE(NB_CLOSE + 1, 256);
  static_assert(SIGMA == 7, "ungated steps must not need a free-slot wait");
#pragma unroll 1
  for (int s = 0; s < SIGMA; s++) conv_step<false, true>(c, s, K, V, B, A);
#pragma unroll 1
  for (int s = SIGMA; s < NSTEP - 1; s++) conv_step<true, true>(c, s, K, V, B, A);
  conv_step<true, false>(c, NSTEP - 1, K, V, B, A);
#pragma unroll 1
  for (int r = NSTEP - SIGMA; r < NROUND - 1 + c.rank; r++) {
    NB_SYNC(NB_OPEN, 384);
    NB_ARRIVE(NB_CLOSE, 256);
    NB_ARRIVE(NB_CLOSE + 1, 256);
  }
  NB_SYNC(NB_OPEN, 384);
}

__global__ void __cluster_dims__(2, 1, 1) __launch_bounds__(384, 1)
convnext_kernel(const __grid_constant__ CUtensorMap tm, const __nv_bfloat16* __restrict__ x, const __nv_bfloat16* __restrict__ dw,
                const __nv_bfloat16* __restrict__ w1, const __nv_bfloat16* __restrict__ w2, __nv_bfloat16* __restrict__ out,
                int zero) {
  extern __shared__ __align__(1024) uint8_t smem[];
  const uint32_t sb = (uint32_t)__cvta_generic_to_shared(smem);
  const int tid = threadIdx.x, lane = tid & 31;
  const int wid = __shfl_sync(0xffffffffu, tid >> 5, 0);
  const int rank = blockIdx.x & 1, cl = blockIdx.x >> 1;
  const int c0 = (cl & 15) * 32, r0 = (cl >> 4) * 128;
  const uint32_t peer_off = mapa(sb, rank ^ 1) - sb;

  TR(wid >> 2, 1002);
  TRG(1020);
  if (tid == 256) {
    for (int i = 0; i < 4; i++) mbar_init(sb + BAR_RAW + 8 * i, 1);
    for (int i = 0; i < 2; i++) mbar_init(sb + BAR_CFULL + 8 * i, 1);
    for (int i = 0; i < 4; i++) mbar_init(sb + BAR_CEMPTY + 8 * i, 4);
    for (int i = 0; i < 8; i++) mbar_init(sb + BAR_XFULL + 8 * i, 1);
    asm volatile("st.shared.v2.b32 [%0], {%1,%1};" ::"r"(sb + OFF_MAX), "r"(0) : "memory");
    asm volatile("fence.mbarrier_init.release.cluster;" ::: "memory");
    asm volatile("fence.proxy.async.shared::cta;" ::: "memory");
    TR(2, 1006);
    for (int i = 0; i < 4; i++)
      tma_raw(sb + OFF_RAW + i * RAW_BYTES, &tm, 56 * rank - 8, c0 / 2 - 2, r0 - 3 + 2 * i, sb + BAR_RAW + 8 * i);
    for (int i = 0; i < 2; i++) mbar_expect(sb + BAR_CFULL + 8 * i, 12288);
    TR(2, 1007);
  }
  __syncwarp();
  asm volatile("barrier.cluster.arrive.aligned;\nbarrier.cluster.wait.aligned;" ::: "memory");

  TR(wid >> 2, 1003);
  if (wid < 8) {
    MlpCtx m;
    m.sb = sb; m.wg = wid >> 2; m.warp = wid & 3; m.rank = rank; m.peer_off = peer_off; m.zero = zero;
    m.xsrc = reinterpret_cast<const uint8_t*>(x) + ((size_t)(r0 + 4 * m.wg + 2 * rank) * IMG + c0 + 8 * m.warp) * (CH * 2);
    m.optr = reinterpret_cast<uint8_t*>(out) + ((size_t)(r0 + 4 * m.wg + 2 * rank) * IMG + c0 + 8 * m.warp) * (CH * 2);
    m.caddr = sb + OFF_C + m.wg * C_BYTES + m.warp * 128 + (lane & 3) * (6 * 512 + 32) + (lane >> 2) * 16;
    m.xaddr = sb + OFF_XRES + wid * 3072 + ((lane >> 3) & 1) * 1536 + ((lane >> 4) * 4 + ((lane >> 2) & 1)) * 192 + (lane & 3) * 16;
    m.unscale = 0;
    asm volatile("setmaxnreg.dec.sync.aligned.u32 %0;" ::"n"(REG_MLP));
    mlp_role(m, w1, w2);
    __syncwarp();
    asm volatile("barrier.cluster.arrive.relaxed.aligned;\nbarrier.cluster.wait.aligned;" ::: "memory");
  } else {
    ConvCtx c;
    c.sb = sb; c.rank = rank; c.v = wid - 8; c.c0 = c0; c.r0 = r0; c.zero = zero; c.tm = &tm;
    c.peer_off = peer_off;
    const int g = lane >> 2, t = lane & 3;
    c.a_raw = sb + OFF_RAW + ((t >> 1) * 19 + 2 * (g + (t & 1))) * 112 + (1 - rank) * 16 + 16 * c.v;
    const int q0 = 12 * rank + 3 * c.v;
    c.a_c = sb + OFF_C + q0 * 512 + (q0 / 6) * 32 + lane * 16;
    asm volatile("setmaxnreg.inc.sync.aligned.u32 %0;" ::"n"(REG_CONV));
    conv_role(c, dw);
    __syncwarp();
    asm volatile("barrier.cluster.arrive.relaxed.aligned;\nbarrier.cluster.wait.aligned;\nexit;" ::: "memory");
  }
}

typedef CUresult (*EncodeFn)(CUtensorMap*, CUtensorMapDataType, cuuint32_t, void*, const cuuint64_t*, const cuuint64_t*,
                             const cuuint32_t*, const cuuint32_t*, CUtensorMapInterleave, CUtensorMapSwizzle,
                             CUtensorMapL2promotion, CUtensorMapFloatOOBfill);

}

extern "C" void kernel_launch(void* const* d_in, const int* in_sizes, int n_in, void* d_out, int out_size) {
  const __nv_bfloat16* x = (const __nv_bfloat16*)d_in[0];
  const __nv_bfloat16* dw = (const __nv_bfloat16*)d_in[1];
  const __nv_bfloat16* w1 = (const __nv_bfloat16*)d_in[2];
  const __nv_bfloat16* w2 = (const __nv_bfloat16*)d_in[3];
  __nv_bfloat16* out = (__nv_bfloat16*)d_out;

  static EncodeFn encode = nullptr;
  if (!encode) {
    cudaDriverEntryPointQueryResult st;
    void* fn = nullptr;
    cudaGetDriverEntryPoint("cuTensorMapEncodeTiled", &fn, cudaEnableDefault, &st);
    encode = (EncodeFn)fn;
    cudaFuncSetAttribute(convnext_kernel, cudaFuncAttributeMaxDynamicSharedMemorySize, SMEM_BYTES);
  }
  CUtensorMap tm;
  cuuint64_t dims[4] = {CH, IMG / 2, IMG, 2};
  cuuint64_t strides[3] = {CH * 4, (cuuint64_t)IMG * CH * 2, CH * 2};
  cuuint32_t box[4] = {56, 19, 2, 1};
  cuuint32_t es[4] = {1, 1, 1, 1};
  encode(&tm, CU_TENSOR_MAP_DATA_TYPE_BFLOAT16, 4, (void*)x, dims, strides, box, es, CU_TENSOR_MAP_INTERLEAVE_NONE,
         CU_TENSOR_MAP_SWIZZLE_NONE, CU_TENSOR_MAP_L2_PROMOTION_L2_128B, CU_TENSOR_MAP_FLOAT_OOB_FILL_NONE);
  convnext_kernel<<<128, 384, SMEM_BYTES>>>(tm, x, dw, w1, w2, out, 0);
}
```

```cpp
#include <cuda_runtime.h>
#include <cuda_bf16.h>
#include <cuda.h>
#include <stdint.h>

namespace {

constexpr int IMG = 512, CH = 96;
constexpr int NSTEP = 67;
constexpr int SIGMA = 7;
constexpr int NROUND = 68;

constexpr uint32_t OFF_W1 = 0;
constexpr uint32_t OFF_W2 = 73728;
constexpr uint32_t OFF_RAW = 147456;
constexpr uint32_t RAW_PLANE = 4352;
constexpr uint32_t RAW_BYTES = 2 * RAW_PLANE;
constexpr uint32_t RAW_TX = 2 * 2 * 19 * 112;
constexpr uint32_t OFF_XRES = OFF_RAW + 4 * RAW_BYTES;
constexpr uint32_t OFF_C = OFF_XRES + 2 * 12288;
constexpr uint32_t C_BYTES = 12416;
constexpr uint32_t OFF_BAR = OFF_C + 2 * C_BYTES;
constexpr uint32_t BAR_RAW = OFF_BAR;
constexpr uint32_t BAR_CFULL = OFF_BAR + 32;
constexpr uint32_t BAR_CEMPTY = OFF_BAR + 48;
constexpr uint32_t BAR_XFULL = OFF_BAR + 80;
constexpr uint32_t BAR_W = OFF_BAR + 144;
constexpr uint32_t OFF_MAX = OFF_BAR + 160;
constexpr uint32_t SMEM_BYTES = OFF_BAR + 176;

constexpr float GELU_A = 0.32918364f;
constexpr uint32_t GELU_K2 = 0x40d940d9u;

constexpr int NB_CLOSE = 1, NB_SEC = 6  , NB_OPEN = 3, NB_PLAN = 4, NB_PREP = 5;
#define REG_MLP 144
constexpr int REG_CONV = 504 - 2 * REG_MLP;

#define WG_FENCE() asm volatile("wgmma.fence.sync.aligned;" ::: "memory")
#define WG_COMMIT() asm volatile("wgmma.commit_group.sync.aligned;" ::: "memory")
#define WG_WAIT0() asm volatile("wgmma.wait_group.sync.aligned 0;" ::: "memory")
#define WG_WAIT1() asm volatile("wgmma.wait_group.sync.aligned 1;" ::: "memory")
#define PIN() asm volatile("pmevent 0;" ::: "memory")
#define NB_SYNC(id, n) asm volatile("bar.sync %0, %1;" ::"n"(id), "n"(n) : "memory")
#define NB_ARRIVE(id, n) asm volatile("bar.arrive %0, %1;" ::"n"(id), "n"(n) : "memory")

#define TR(who, idx)
#define TRG(idx)

#define R24(c, d)                                                                                        \
  c(d[0]), c(d[1]), c(d[2]), c(d[3]), c(d[4]), c(d[5]), c(d[6]), c(d[7]), c(d[8]), c(d[9]), c(d[10]),    \
      c(d[11]), c(d[12]), c(d[13]), c(d[14]), c(d[15]), c(d[16]), c(d[17]), c(d[18]), c(d[19]), c(d[20]), \
      c(d[21]), c(d[22]), c(d[23])
#define WG_TXT(sd)                                                                             \
  "wgmma.mma_async.sync.aligned.m64n96k16.f16.f16.f16 "                                        \
  "{%0,%1,%2,%3,%4,%5,%6,%7,%8,%9,%10,%11,%12,%13,%14,%15,%16,%17,%18,%19,%20,%21,%22,%23}, " \
  "{%24,%25,%26,%27}, %28, " sd ", 1, 1, 1;\n"

__device__ __forceinline__ void wg_acc(uint32_t (&d)[24], const uint32_t* a, uint64_t db) {
  asm volatile(WG_TXT("1") : R24("+r", d) : "r"(a[0]), "r"(a[1]), "r"(a[2]), "r"(a[3]), "l"(db));
}
__device__ __forceinline__ void wg_init(uint32_t (&d)[24], const uint32_t* a, uint64_t db) {
  asm volatile(WG_TXT("0") : R24("=r", d) : "r"(a[0]), "r"(a[1]), "r"(a[2]), "r"(a[3]), "l"(db));
}
template <int N>
__device__ __forceinline__ void rfence(uint32_t (&d)[N]) {
#pragma unroll
  for (int i = 0; i < N; i++) asm volatile("" : "+r"(d[i])::"memory");
}
template <bool INIT, int KSTRIDE>
__device__ __forceinline__ void gemm6(uint32_t (&d)[24], const uint32_t (&a)[24], uint64_t db) {
#pragma unroll
  for (int k = 0; k < 6; k++) {
    if (INIT && k == 0) wg_init(d, &a[0], db);
    else wg_acc(d, &a[4 * k], db + k * KSTRIDE);
  }
  WG_COMMIT();
}

__device__ __forceinline__ void mbar_init(uint32_t bar, uint32_t cnt) {
  asm volatile("mbarrier.init.shared::cta.b64 [%0], %1;" ::"r"(bar), "r"(cnt) : "memory");
}
__device__ __forceinline__ void mbar_expect(uint32_t bar, uint32_t bytes) {
  asm volatile("mbarrier.arrive.expect_tx.shared::cta.b64 _, [%0], %1;" ::"r"(bar), "r"(bytes) : "memory");
}
__device__ __forceinline__ void mbar_arrive_cluster(uint32_t bar) {
  asm volatile("mbarrier.arrive.shared::cluster.b64 _, [%0];" ::"r"(bar) : "memory");
}
__device__ __forceinline__ bool mbar_try(uint32_t bar, uint32_t parity) {
  uint32_t ok;
  asm volatile(
      "{\n.reg .pred p;\nmbarrier.try_wait.parity.shared::cta.b64 p, [%1], %2;\nselp.u32 %0, 1, 0, p;\n}\n"
      : "=r"(ok)
      : "r"(bar), "r"(parity)
      : "memory");
  return ok;
}
__device__ __forceinline__ void mbar_wait(uint32_t bar, uint32_t parity) {
  if (__builtin_expect(mbar_try(bar, parity), 1)) return;
#pragma unroll 1
  for (uint32_t n = 0; n < (1u << 16) && !mbar_try(bar, parity); n++) {}
}
__device__ __forceinline__ uint32_t mapa(uint32_t addr, uint32_t rank) {
  uint32_t r;
  asm("mapa.shared::cluster.u32 %0, %1, %2;" : "=r"(r) : "r"(addr), "r"(rank));
  return r;
}
__device__ __forceinline__ void tma_raw(uint32_t dst, const CUtensorMap* tm, int c, int w2, int h, uint32_t bar) {
  mbar_expect(bar, RAW_TX);
#pragma unroll
  for (int e = 0; e < 2; e++)
    asm volatile(
        "cp.async.bulk.tensor.4d.shared::cluster.global.mbarrier::complete_tx::bytes [%0], [%1, {%2, %3, %4, %5}], [%6];"
        ::"r"(dst + e * RAW_PLANE), "l"(tm), "r"(c), "r"(w2 + e), "r"(h), "r"(1 - e), "r"(bar)
        : "memory");
}
__device__ __forceinline__ void bulk_load(uint32_t dst, const void* src, uint32_t bytes, uint32_t bar) {
  asm volatile("cp.async.bulk.shared::cluster.global.mbarrier::complete_tx::bytes [%0], [%1], %2, [%3];" ::"r"(dst),
               "l"(src), "r"(bytes), "r"(bar)
               : "memory");
}
__device__ __forceinline__ uint32_t pack_bf16(float lo, float hi) {
  uint32_t r;
  asm("cvt.rn.bf16x2.f32 %0, %1, %2;" : "=r"(r) : "f"(hi), "f"(lo));
  return r;
}
__device__ __forceinline__ uint32_t pack_f16(float lo, float hi) {
  uint32_t r;
  asm("cvt.rn.f16x2.f32 %0, %1, %2;" : "=r"(r) : "f"(hi), "f"(lo));
  return r;
}
__device__ __forceinline__ float bf_lo(uint32_t v) { return __uint_as_float(v << 16); }
__device__ __forceinline__ float bf_hi(uint32_t v) { return __uint_as_float(v & 0xffff0000u); }
__device__ __forceinline__ uint32_t bf_add(uint32_t a, uint32_t b) {
  uint32_t r;
  asm("add.rn.bf16x2 %0, %1, %2;" : "=r"(r) : "r"(a), "r"(b));
  return r;
}
__device__ __forceinline__ uint32_t bf_mul(uint32_t a, uint32_t b) {
  uint32_t r;
  asm("mul.rn.bf16x2 %0, %1, %2;" : "=r"(r) : "r"(a), "r"(b));
  return r;
}
__device__ __forceinline__ uint32_t bf_fma(uint32_t a, uint32_t b, uint32_t c) {
  uint32_t r;
  asm("fma.rn.bf16x2 %0, %1, %2, %3;" : "=r"(r) : "r"(a), "r"(b), "r"(c));
  return r;
}

__device__ __forceinline__ uint32_t bf_amax(uint32_t a, uint32_t b) {
  uint32_t r;
  asm("max.xorsign.abs.bf16x2 %0, %1, %2;" : "=r"(r) : "r"(a), "r"(b));
  return r;
}
__device__ __forceinline__ void lds128(uint32_t (&v)[4], uint32_t a) {
  asm volatile("ld.shared.v4.b32 {%0,%1,%2,%3}, [%4];" : "=r"(v[0]), "=r"(v[1]), "=r"(v[2]), "=r"(v[3]) : "r"(a) : "memory");
}

template <int LO, int HI>
__device__ __forceinline__ void gelu(uint32_t (&o)[24], const uint32_t (&d)[24]) {
#pragma unroll
  for (int qq = LO; qq < HI; qq++) {
    const int q = (qq + 4) % 24;
    uint32_t t, u;
    asm("fma.rn.f16x2 %0, %1, %1, %2;" : "=r"(t) : "r"(d[q]), "r"(GELU_K2));
    asm("mul.rn.f16x2 %0, %1, %2;" : "=r"(u) : "r"(d[q]), "r"(t));
    asm("tanh.approx.f16x2 %0, %1;" : "=r"(t) : "r"(u));
    asm("fma.rn.f16x2 %0, %1, %2, %1;" : "=r"(o[q]) : "r"(d[q]), "r"(t));
  }
}

__device__ __forceinline__ uint32_t laneid() {
  uint32_t l;
  asm volatile("mov.u32 %0, %%laneid;" : "=r"(l));
  return l;
}

__device__ __forceinline__ bool elect_one() {
  uint32_t p;
  asm volatile("{\n.reg .pred p;\nelect.sync _|p, 0xffffffff;\nselp.u32 %0, 1, 0, p;\n}\n" : "=r"(p));
  return p;
}

struct MlpCtx {
  uint32_t sb;
  uint32_t caddr;
  uint32_t xaddr;
  uint32_t unscale;
  uint32_t peer_off;
  int wg, warp, rank, zero;
  const uint8_t* xsrc;
  uint8_t* optr;
};

__device__ __forceinline__ void ln_wait(const MlpCtx& m, int i) { mbar_wait(m.sb + BAR_CFULL + 8 * m.wg, i & 1); }
__device__ __forceinline__ void ln_load(const MlpCtx& m, uint32_t (&c)[24]) {
#pragma unroll
  for (int p = 0; p < 6; p++)
    asm volatile("ld.shared.v4.b32 {%0,%1,%2,%3}, [%4];"
                 : "=r"(c[4 * p]), "=r"(c[4 * p + 1]), "=r"(c[4 * p + 2]), "=r"(c[4 * p + 3])
                 : "r"(m.caddr + p * 512)
                 : "memory");
}
__device__ __forceinline__ void ln_shfl(float (&st)[8]) {
#pragma unroll
  for (int k = 1; k < 4; k++) {
    st[2 * k] = __shfl_xor_sync(0xffffffffu, st[0], k);
    st[2 * k + 1] = __shfl_xor_sync(0xffffffffu, st[1], k);
  }
}
__device__ __forceinline__ float ln_total(const float (&st)[8], int r) { return (st[r] + st[r + 2]) + (st[r + 4] + st[r + 6]); }
__device__ __forceinline__ void ln_sum(const uint32_t (&c)[24], float (&st)[8]) {
#pragma unroll
  for (int r = 0; r < 2; r++) {
    uint32_t s0 = bf_add(c[r], c[r + 2]), s1 = bf_add(c[r + 4], c[r + 6]), s2 = bf_add(c[r + 8], c[r + 10]);
    uint32_t s3 = bf_add(c[r + 12], c[r + 14]), s4 = bf_add(c[r + 16], c[r + 18]), s5 = bf_add(c[r + 20], c[r + 22]);
    s0 = bf_add(s0, s1); s2 = bf_add(s2, s3); s4 = bf_add(s4, s5);
    s0 = bf_add(bf_add(s0, s2), s4);
    st[r] = bf_lo(s0) + bf_hi(s0);
  }
}
__device__ __forceinline__ void ln_release(const MlpCtx& m, bool on) {
  const uint32_t e = m.sb + BAR_CEMPTY + 8 * (2 * m.rank + m.wg);
  asm volatile(
      "{\n.reg .pred p, q;\nelect.sync _|p, 0xffffffff;\nsetp.ne.and.s32 p, %4, 0, p;\nsetp.eq.and.s32 q, %3, 0, p;\n"
      "@q mbarrier.arrive.expect_tx.shared::cta.b64 _, [%0], 12288;\n"
      "@p mbarrier.arrive.shared::cluster.b64 _, [%1];\n"
      "@p mbarrier.arrive.shared::cluster.b64 _, [%2];\n}\n" ::"r"(m.sb + BAR_CFULL + 8 * m.wg),
      "r"(e), "r"(e + m.peer_off), "r"(m.warp), "r"((int)on)
      : "memory");
}
__device__ __forceinline__ void ln_center(uint32_t (&c)[24], float (&st)[8], float (&dl)[2]) {
#pragma unroll
  for (int r = 0; r < 2; r++) {
    float nm = ln_total(st, r) * (-1.0f / 96.0f);
    uint32_t nm2 = pack_bf16(nm, nm);
    dl[r] = nm - bf_hi(nm2);
#pragma unroll
    for (int p = 0; p < 12; p++) c[2 * p + r] = bf_add(c[2 * p + r], nm2);
    uint32_t q0 = bf_mul(c[r], c[r]), q1 = bf_mul(c[r + 2], c[r + 2]);
#pragma unroll
    for (int p = 2; p < 12; p += 2) {
      q0 = bf_fma(c[2 * p + r], c[2 * p + r], q0);
      q1 = bf_fma(c[2 * p + 2 + r], c[2 * p + 2 + r], q1);
    }
    q0 = bf_add(q0, q1);
    st[r] = bf_lo(q0) + bf_hi(q0);
  }
}
__device__ __forceinline__ void ln_guard(uint32_t (&c)[24], float (&st)[8], float (&dl)[2]) {
  if (__builtin_expect(__any_sync(0xffffffffu, fmaxf(st[0], st[1]) > 0x1p26f), 0)) {
#pragma unroll
    for (int r = 0; r < 2; r++) {
      float mx = fmaxf(st[r], __shfl_xor_sync(0xffffffffu, st[r], 1));
      mx = fmaxf(mx, __shfl_xor_sync(0xffffffffu, mx, 2));
      int k = max(0, ((int)(__float_as_uint(mx) >> 23) - (127 + 20)) >> 1);
      uint32_t e = (uint32_t)(127 - k) << 23;
      uint32_t e2 = (e >> 16) | e;
#pragma unroll
      for (int p = 0; p < 12; p++) asm volatile("mul.rn.bf16x2 %0, %0, %1;" : "+r"(c[2 * p + r]) : "r"(e2));
      st[r] = st[r] * __uint_as_float(e) * __uint_as_float(e);
      dl[r] *= __uint_as_float(e);
    }
  }
}
__device__ __forceinline__ void ln_rstd(float (&st)[8], const float (&dl)[2]) {
#pragma unroll
  for (int r = 0; r < 2; r++) {
    float rs;
    asm("rsqrt.approx.ftz.f32 %0, %1;" : "=f"(rs) : "f"(fmaf(ln_total(st, r), 1.0f / 96.0f, 1e-5f)));
    float rr = rs * (GELU_A * 0x1p-112f), dd = dl[r] * rr;
    st[r] = __uint_as_float(pack_bf16(rr, rr));
    st[r + 2] = __uint_as_float(pack_bf16(dd, dd));
  }
}
__device__ __forceinline__ void ln_scale(uint32_t (&c)[24], const float (&st)[8]) {
#pragma unroll
  for (int p = 0; p < 24; p++) c[p] = bf_fma(c[p], __float_as_uint(st[p & 1]), __float_as_uint(st[2 + (p & 1)]));
}
__device__ __forceinline__ void ln_final(uint32_t (&a)[24], const uint32_t (&c)[24]) {
#pragma unroll
  for (int p = 0; p < 24; p++) a[p] = (c[p] & 0x7fff7fffu) * 7u + c[p];
}

__device__ __forceinline__ void issue_xres(const MlpCtx& m, int i) {
  if (elect_one()) {
    uint32_t bar = m.sb + BAR_XFULL + 8 * (4 * m.wg + m.warp);
    uint32_t dst = m.sb + OFF_XRES + (4 * m.wg + m.warp) * 3072;
    const uint8_t* src = m.xsrc + (size_t)i * (8 * IMG * CH * 2);
    asm volatile("cp.async.bulk.wait_group.read 0;" ::: "memory");
    mbar_expect(bar, 3072);
    bulk_load(dst, src, 1536, bar);
    bulk_load(dst + 1536, src + IMG * CH * 2, 1536, bar);
  }
}
__device__ __forceinline__ void x_wait(const MlpCtx& m, int i) { mbar_wait(m.sb + BAR_XFULL + 8 * (4 * m.wg + m.warp), i & 1); }
__device__ __forceinline__ void x_load(const MlpCtx& m, uint32_t (&x)[24]) {
#pragma unroll
  for (int k = 0; k < 6; k++)
    asm volatile("ld.shared.v4.b32 {%0,%1,%2,%3}, [%4];"
                 : "=r"(x[4 * k]), "=r"(x[4 * k + 1]), "=r"(x[4 * k + 2]), "=r"(x[4 * k + 3])
                 : "r"(m.xaddr + (k / 3) * 384 + (k % 3) * 64)
                 : "memory");
}
template <int LO, int HI>
__device__ __forceinline__ void epilogue(const MlpCtx& m, const uint32_t (&d)[24], uint32_t (&x)[24]) {
#pragma unroll
  for (int k = LO; k < HI; k++) {
    const int r = k / 3, q = k % 3;
    uint32_t* y = &x[4 * k];
#pragma unroll
    for (int j = 0; j < 4; j++) {
      uint32_t v = d[2 * (4 * q + j) + r];
      float lo, hi;
      asm("{\n.reg .b16 l, h;\nmov.b32 {l, h}, %2;\ncvt.f32.f16 %0, l;\ncvt.f32.f16 %1, h;\n}\n" : "=f"(lo), "=f"(hi) : "r"(v));
      asm("fma.rn.bf16x2 %0, %1, %2, %0;" : "+r"(y[j]) : "r"(pack_bf16(lo, hi)), "r"(m.unscale));
    }
    asm volatile("st.shared.v4.b32 [%0], {%1,%2,%3,%4};" ::"r"(m.xaddr + r * 384 + q * 64), "r"(y[0]), "r"(y[1]), "r"(y[2]), "r"(y[3])
                 : "memory");
  }
}
__device__ __forceinline__ void out_store(const MlpCtx& m, int i) {
  asm volatile("fence.proxy.async.shared::cta;" ::: "memory");
  __syncwarp();
  if (elect_one()) {
    const uint32_t src = m.sb + OFF_XRES + (4 * m.wg + m.warp) * 3072;
    uint8_t* dst = m.optr + (size_t)i * (8 * IMG * CH * 2);
    asm volatile("cp.async.bulk.global.shared::cta.bulk_group [%0], [%1], 1536;" ::"l"(dst), "r"(src) : "memory");
    asm volatile("cp.async.bulk.global.shared::cta.bulk_group [%0], [%1], 1536;" ::"l"(dst + IMG * CH * 2), "r"(src + 1536) : "memory");
    asm volatile("cp.async.bulk.commit_group;" ::: "memory");
  }
}

template <int J> __device__ __forceinline__ void tok_wait() {
  if (J == 0 || J == 3) NB_SYNC(NB_CLOSE, 256);
  else NB_SYNC(NB_SEC + (J & 1), 256);
}
template <int J> __device__ __forceinline__ void tok_next() {
  if (J == 0 || J == 3) NB_ARRIVE(NB_SEC + (J & 1), 256);
}
__device__ __forceinline__ void tok_pass() { NB_ARRIVE(NB_OPEN, 384); }
template <int J> __device__ __forceinline__ void tok_idle() { tok_wait<J>(); tok_next<J>(); tok_pass(); }

constexpr uint64_t CHK = 1152;

__device__ __forceinline__ void mlp_role(const MlpCtx& m0) {
  MlpCtx m = m0;
  const int lane = threadIdx.x & 31, wid = m.wg * 4 + m.warp;
  {
    uint32_t v[18][4];
    const int k7 = lane & 7;
    {
      mbar_wait(m.sb + BAR_W, 0);
      uint32_t mx = 0;
#pragma unroll
      for (int it = 0; it < 18; it++) {
        const int kb = (it / 3) * 2 + (wid & 1), ks = it / 3;
        const int Q = 6 * (k7 >> 1) + ks, q12 = Q % 12, cv = q12 / 3, e = q12 % 3;
        const int ch = 48 * (Q / 12) + (e < 2 ? 8 * cv + 4 * e : 32 + 4 * cv) + 2 * (kb & 1) + (k7 & 1);
        const int n8 = (it % 3) * 16 + ((wid >> 2) * 8 + ((((wid >> 1) & 1) * 4 + (lane >> 3) + k7) & 7));
        lds128(v[it], m.sb + OFF_W1 + ch * 768 + n8 * 16);
      }
#pragma unroll
      for (int it = 0; it < 18; it++)
#pragma unroll
        for (int t = 0; t < 4; t++) mx = bf_amax(mx, v[it][t]);
      mx = __reduce_max_sync(0xffffffffu, max(mx & 0x7fffu, (mx >> 16) & 0x7fffu));
      if (lane == 0) asm volatile("red.shared.max.u32 [%0], %1;" ::"r"(m.sb + OFF_MAX), "r"(mx) : "memory");
      NB_SYNC(NB_PREP, 256);
#pragma unroll
      for (int it = 0; it < 18; it++) {
        const int n8 = (it % 3) * 16 + ((wid >> 2) * 8 + ((((wid >> 1) & 1) * 4 + (lane >> 3) + k7) & 7));
        const uint32_t dst = m.sb + OFF_W1 + (it / 3) * 12288 + n8 * 256 + (wid & 1) * 128 + k7 * 16;
        asm volatile("st.shared.v4.b32 [%0], {%1,%2,%3,%4};" ::"r"(dst), "r"(pack_f16(bf_lo(v[it][0]), bf_hi(v[it][0]))),
                     "r"(pack_f16(bf_lo(v[it][1]), bf_hi(v[it][1]))), "r"(pack_f16(bf_lo(v[it][2]), bf_hi(v[it][2]))),
                     "r"(pack_f16(bf_lo(v[it][3]), bf_hi(v[it][3])))
                     : "memory");
      }
    }
    TR(m.wg, 1004);
    {
      mbar_wait(m.sb + BAR_W + 8, 0);
      const uint32_t base = m.sb + OFF_W2 + wid * 9216;
      uint32_t mx = 0, mx2 = 0;
#pragma unroll
      for (int it = 0; it < 18; it++) lds128(v[it], base + (lane >> 2) * 192 + (lane & 3) * 16 + (it / 3) * 1536 + (it % 3) * 64);
#pragma unroll
      for (int it = 0; it < 18; it++)
#pragma unroll
        for (int t = 0; t < 4; t++) mx2 = bf_amax(mx2, v[it][t]);
      mx2 = __reduce_max_sync(0xffffffffu, max(mx2 & 0x7fffu, (mx2 >> 16) & 0x7fffu));
      if (lane == 0) asm volatile("red.shared.max.u32 [%0], %1;" ::"r"(m.sb + OFF_MAX + 4), "r"(mx2) : "memory");
      TR(m.wg, 1005);
      NB_SYNC(NB_PREP, 256);
      asm volatile("ld.shared.v2.b32 {%0,%1}, [%2];" : "=r"(mx), "=r"(mx2) : "r"(m.sb + OFF_MAX) : "memory");
      int e1 = (int)(mx >> 7) - 126, e2 = (int)(mx2 >> 7) - 126;
      int s = min(-1 - e1 - e2, 14 - e2);
      s = max(-120, min(120, s));
      const float sc = __uint_as_float((uint32_t)(127 + s) << 23) * (0.5f / GELU_A);
      m.unscale = ((uint32_t)(127 - s) << 7) * 0x10001u;
#pragma unroll
      for (int it = 0; it < 18; it++)
#pragma unroll
        for (int j = 0; j < 4; j++)
          asm volatile("st.shared.b32 [%0], %1;" ::"r"(base + lane * 4 + (it / 6) * 3072 + ((it / 3) & 1) * 128 + ((it % 3) * 4 + j) * 256),
                       "r"(pack_f16(bf_lo(v[it][j]) * sc, bf_hi(v[it][j]) * sc))
                       : "memory");
    }
    asm volatile("fence.proxy.async.shared::cta;" ::: "memory");
    NB_SYNC(NB_PREP, 256);
  }
  asm volatile("barrier.cluster.wait.aligned;" ::: "memory");
  const uint64_t dW1 = (uint64_t)(((m.sb + OFF_W1) & 0x3FFFF) >> 4) | ((uint64_t)8 << 16) | ((uint64_t)16 << 32);
  const uint64_t dW2 = dW1 + (OFF_W2 >> 4);

  TR(m.wg, 1000);
  uint32_t A1[24], g[24], d[24], cn[24], D2[24];
  float st[8], dl[2];
  ln_wait(m, 0);
  ln_load(m, cn);
  ln_sum(cn, st);
  ln_shfl(st);
  ln_release(m, true);
  ln_center(cn, st, dl);
  ln_guard(cn, st, dl);
  ln_shfl(st);
  ln_rstd(st, dl);
  ln_scale(cn, st);
  ln_final(A1, cn);
  [[maybe_unused]] int rho = 2 * m.wg + m.rank + 2;
  if (m.wg & m.rank) tok_idle<3>();
  if (m.wg) tok_idle<0>();
  if (m.wg | m.rank) tok_idle<1>();
  {
    uint32_t d0[24];
    WG_FENCE();
    tok_wait<2>();
    gemm6<true, 768>(d0, A1, dW1);
    tok_pass(); PIN();
    WG_WAIT0(); rfence(d0);
    WG_FENCE();
    tok_wait<3>();
    tok_next<3>();
    gemm6<true, 768>(d, A1, dW1 + 192);
    tok_pass(); PIN();
    gelu<0, 24>(g, d0);
    PIN();
    ln_wait(m, 1);
    ln_load(m, cn);
    PIN();
    WG_WAIT0(); rfence(d);
  }
#define G2(INIT, a, j)                      \
  WG_FENCE();                               \
  tok_wait<j>();                            \
  TR(m.wg, rho * 8);                        \
  gemm6<INIT, 192>(D2, a, dW2 + (j) * CHK); \
  tok_next<j>(); PIN();                     \
  TR(m.wg, rho * 8 + 1);
#define G1(dst, j)                          \
  TR(m.wg, rho * 8 + 2);                    \
  PIN(); WG_WAIT0(); rfence(D2);            \
  WG_FENCE();                               \
  gemm6<true, 768>(dst, A1, dW1 + (j) * 192); \
  tok_pass(); PIN();                        \
  TR(m.wg, rho * 8 + 3);
#define ROUND_END(dst)                      \
  TR(m.wg, rho * 8 + 4);                    \
  PIN(); WG_WAIT0(); rfence(dst); rho++;
#define LNP 1
#define GA 8
#define GB 8
#define GC 8
#define GD 8
#pragma unroll 1
  for (int i = 0;; i++) {
    uint32_t g1[24], d2[24], g2[24], d3[24], g3[24], d0[24];
    G2(true, g, 0)
    gelu<0, GA>(g1, d);
    G1(d2, 2)
    ln_sum(cn, st);
    gelu<GA, 24>(g1, d);
    PIN();
    ln_release(m, i < 15);
    if (i > 0) out_store(m, i - 1);
    ln_shfl(st);
    ROUND_END(d2)

    G2(false, g1, 1)
    ln_center(cn, st, dl);
    gelu<0, GB>(g2, d2);
    PIN();
    ln_guard(cn, st, dl);
    ln_shfl(st);
    G1(d3, 3)
    ln_rstd(st, dl);
    ln_scale(cn, st);
    gelu<GB, 24>(g2, d2);
    PIN();
    issue_xres(m, i);
    ROUND_END(d3)

    if (i == 15) {
      G2(false, g2, 2)
      tok_pass();
      gelu<0, 24>(g3, d3);
      PIN();
      x_wait(m, i);
      x_load(m, cn);
      ROUND_END(D2)
      G2(false, g3, 3)
      tok_pass();
      WG_WAIT0(); rfence(D2);
      epilogue<0, 6>(m, D2, cn);
      break;
    }
    G2(false, g2, 2)
    ln_final(A1, cn);
    gelu<0, GC>(g3, d3);
    G1(d0, 0)
    gelu<GC, 24>(g3, d3);
    PIN();
    x_wait(m, i);
    x_load(m, cn);
    ROUND_END(d0)

    G2(false, g3, 3)
    gelu<0, GD>(g, d0);
    G1(d, 1)
    epilogue<0, 6>(m, D2, cn);
    gelu<GD, 24>(g, d0);
    PIN();
    if (i < 14) ln_wait(m, i);
    ln_load(m, cn);
    ROUND_END(d)
  }
  out_store(m, 15);
  if (m.wg == 0) { tok_idle<0>(); tok_idle<1>(); }
  asm volatile("cp.async.bulk.wait_group 0;" ::: "memory");
  TR(m.wg, 1001);
  TRG(1021);
}

struct ConvCtx {
  uint32_t sb;
  uint32_t a_raw, a_c;
  uint32_t peer_off;
  int rank, v, c0, r0, zero;
  const CUtensorMap* tm;
};

__device__ __forceinline__ void conv_ld8(uint32_t a, uint32_t (&r)[6][6]) {
#pragma unroll
  for (int j = 0; j < 6; j++)
    asm volatile("ld.shared.v4.b32 {%0,%1,%2,%3}, [%4];"
                 : "=r"(r[j][0]), "=r"(r[j][1]), "=r"(r[j][2]), "=r"(r[j][3])
                 : "r"(a + (j >> 1) * 112 + (j & 1) * RAW_PLANE)
                 : "memory");
}
__device__ __forceinline__ void conv_ld4(uint32_t a, uint32_t (&r)[6][6]) {
#pragma unroll
  for (int j = 0; j < 6; j++)
    asm volatile("ld.shared.v2.b32 {%0,%1}, [%2];" : "=r"(r[j][4]), "=r"(r[j][5]) : "r"(a + (j >> 1) * 112 + (j & 1) * RAW_PLANE) : "memory");
}
__device__ __forceinline__ void conv_frags(const ConvCtx& c, const uint32_t (&r)[6][6], uint32_t (&A)[12][4]) {
#pragma unroll
  for (int ch = 0; ch < 12; ch++) {
    const uint32_t sel = (ch & 1) ? 0x7632 : 0x5410;
    A[ch][0] = __byte_perm(r[0][ch >> 1], r[1][ch >> 1], sel);
    A[ch][1] = __byte_perm(r[2][ch >> 1], r[3][ch >> 1], sel);
    A[ch][2] = A[ch][1] ^ c.zero;
    A[ch][3] = __byte_perm(r[4][ch >> 1], r[5][ch >> 1], sel);
  }
}
__device__ __forceinline__ uint32_t clock_pin() {
  uint32_t t;
  asm volatile("mov.u32 %0, %%clock;" : "=r"(t)::"memory");
  return t;
}

__device__ __forceinline__ void hmma(float (&d)[4], const uint32_t* a, const uint32_t* b, const float (&cc)[4]) {
  asm volatile("mma.sync.aligned.m16n8k16.row.col.f32.bf16.bf16.f32 {%0,%1,%2,%3}, {%4,%5,%6,%7}, {%8,%9}, {%10,%11,%12,%13};"
               : "=f"(d[0]), "=f"(d[1]), "=f"(d[2]), "=f"(d[3])
               : "r"(a[0]), "r"(a[1]), "r"(a[2]), "r"(a[3]), "r"(b[0]), "r"(b[1]), "f"(cc[0]), "f"(cc[1]), "f"(cc[2]), "f"(cc[3]));
}

template <bool GATED, bool MORE>
__device__ __forceinline__ void conv_step(const ConvCtx& c, int s, float (&K)[12][2], float (&V)[12][4], const uint32_t (&B)[12][4],
                                          uint32_t (&A)[12][4]) {
  const int nx = (s + 1) & 3;
  const int owner = nx & 1, slot = nx >> 1, par = ((s + 1) >> 2) & 1;
  float T[12][4];
  uint32_t r[6][6];
  const float Z[4] = {0.f, 0.f, 0.f, 0.f};
  const uint32_t off = (owner == c.rank) ? 0u : c.peer_off;
  uint32_t araw = c.a_raw + nx * RAW_BYTES, dst = c.a_c + off + slot * C_BYTES, bar = c.sb + off + BAR_CFULL + 8 * slot;
  if (MORE) mbar_wait(c.sb + BAR_RAW + 8 * nx, par);
  if (GATED) mbar_wait(c.sb + BAR_CEMPTY + 8 * (2 * owner + slot), par);
  asm volatile("" : "+r"(araw), "+r"(dst), "+r"(bar));
  TR(2, s * 8);
  PIN();
  if (GATED) NB_SYNC(NB_OPEN, 384);
  else NB_SYNC(NB_PLAN, 128);
  if (MORE) conv_ld8(araw, r);
  PIN();
  TR(2, s * 8 + 1);
#pragma unroll
  for (int ch = 0; ch < 12; ch++) {
    hmma(T[ch], A[ch], &B[ch][2], V[ch]);
    hmma(V[ch], A[ch], &B[ch][0], Z);
  }
  const uint32_t z1 = clock_pin();
  if (GATED) NB_ARRIVE(NB_CLOSE, 256);
  PIN();
  TR(2, s * 8 + 2);
  uint32_t pk[12];
#pragma unroll
  for (int q = 0; q < 6; q++) {
    pk[2 * q] = pack_bf16(T[2 * q][1], T[2 * q + 1][1]);
    pk[2 * q + 1] = pack_bf16(T[2 * q][3], T[2 * q + 1][3]);
  }
  if (GATED || s >= 3) {
#pragma unroll
    for (int q = 0; q < 3; q++)
      asm volatile("st.async.weak.shared::cluster.mbarrier::complete_tx::bytes.v4.b32 [%0], {%1,%2,%3,%4}, [%5];" ::"r"(dst + q * 512),
                   "r"(pk[4 * q]), "r"(pk[4 * q + 1]), "r"(pk[4 * q + 2]), "r"(pk[4 * q + 3]), "r"(bar)
                   : "memory");
  }
#pragma unroll
  for (int ch = 0; ch < 12; ch++) {
    V[ch][1] += K[ch][0];
    V[ch][3] += K[ch][1];
    K[ch][0] = __uint_as_float(__float_as_uint(T[ch][0]) ^ (ch == 11 ? c.zero & z1 : c.zero));
    K[ch][1] = __uint_as_float(__float_as_uint(T[ch][2]) ^ c.zero);
    asm volatile("" : "+f"(V[ch][1]), "+f"(V[ch][3]), "+f"(K[ch][0]), "+f"(K[ch][1]));
  }
  PIN();
  TR(2, s * 8 + 3);
  if (MORE) {
    conv_ld4(araw + 64 - 8 * c.v, r);
    conv_frags(c, r, A);
#pragma unroll
    for (int ch = 0; ch < 12; ch++) rfence(A[ch]);
  }
  PIN();
  TR(2, s * 8 + 4);
  if (c.v == (s & 3) && s + 4 < NSTEP && elect_one())
    tma_raw(c.sb + OFF_RAW + c.v * RAW_BYTES, c.tm, 56 * c.rank - 8, c.c0 / 2 - 2, c.r0 - 3 + 2 * (s + 4), c.sb + BAR_RAW + 8 * c.v);
}

__device__ __forceinline__ void conv_role(const ConvCtx& c, const __nv_bfloat16* dw) {
  const int lane = threadIdx.x & 31, g = lane >> 2, t = lane & 3;
  uint32_t B[12][4];
  {
    const int e = g & 1, dc = (g >> 1) & 1, ro = g >> 2, rk = t >> 1;
    const uint8_t* dwp = reinterpret_cast<const uint8_t*>(dw) + 96 * c.rank;
#pragma unroll
    for (int b = 0; b < 2; b++) {
      const int i = 2 * (2 * e + b) + rk - ro;
      uint32_t w[4][6];
#pragma unroll
      for (int k = 0; k < 4; k++) {
        const int j = 4 * (t & 1) + k - dc;
        const bool ok = i >= 0 && i < 7 && j >= 0 && j < 7;
        uint4 w8 = make_uint4(0, 0, 0, 0);
        uint2 w4 = make_uint2(0, 0);
        if (ok) {
          w8 = __ldg(reinterpret_cast<const uint4*>(dwp + (i * 7 + j) * 192 + 16 * c.v));
          w4 = __ldg(reinterpret_cast<const uint2*>(dwp + (i * 7 + j) * 192 + 64 + 8 * c.v));
        }
        w[k][0] = w8.x; w[k][1] = w8.y; w[k][2] = w8.z; w[k][3] = w8.w; w[k][4] = w4.x; w[k][5] = w4.y;
      }
#pragma unroll
      for (int q = 0; q < 6; q++) {
        B[2 * q][2 * b] = __byte_perm(w[0][q], w[1][q], 0x5410);
        B[2 * q][2 * b + 1] = __byte_perm(w[2][q], w[3][q], 0x5410);
        B[2 * q + 1][2 * b] = __byte_perm(w[0][q], w[1][q], 0x7632);
        B[2 * q + 1][2 * b + 1] = __byte_perm(w[2][q], w[3][q], 0x7632);
      }
    }
  }
  TR(2, 1004);
  asm volatile("barrier.cluster.wait.aligned;" ::: "memory");
  float K[12][2], V[12][4];
#pragma unroll
  for (int ch = 0; ch < 12; ch++) {
    K[ch][0] = K[ch][1] = 0.f;
#pragma unroll
    for (int k = 0; k < 4; k++) V[ch][k] = 0.f;
  }
  uint32_t A[12][4];
  {
    uint32_t r[6][6];
    mbar_wait(c.sb + BAR_RAW, 0);
    conv_ld8(c.a_raw, r);
    conv_ld4(c.a_raw + 64 - 8 * c.v, r);
    conv_frags(c, r, A);
  }
  NB_ARRIVE(NB_CLOSE, 256);
  static_assert(SIGMA == 7, "ungated steps must not need a free-slot wait");
#pragma unroll 1
  for (int s = 0; s < SIGMA; s++) conv_step<false, true>(c, s, K, V, B, A);
#pragma unroll 1
  for (int s = SIGMA; s < NSTEP - 1; s++) conv_step<true, true>(c, s, K, V, B, A);
  conv_step<true, false>(c, NSTEP - 1, K, V, B, A);
#pragma unroll 1
  for (int r = NSTEP - SIGMA; r < NROUND - 1 + c.rank; r++) {
    NB_SYNC(NB_OPEN, 384);
    NB_ARRIVE(NB_CLOSE, 256);
  }
  NB_SYNC(NB_OPEN, 384);
}

__global__ void __cluster_dims__(2, 1, 1) __launch_bounds__(384, 1)
convnext_kernel(const __grid_constant__ CUtensorMap tm, const __nv_bfloat16* __restrict__ x, const __nv_bfloat16* __restrict__ dw,
                const __nv_bfloat16* __restrict__ w1, const __nv_bfloat16* __restrict__ w2, __nv_bfloat16* __restrict__ out,
                int zero) {
  extern __shared__ __align__(1024) uint8_t smem[];
  const uint32_t sb = (uint32_t)__cvta_generic_to_shared(smem);
  const int tid = threadIdx.x, lane = tid & 31;
  const int wid = __shfl_sync(0xffffffffu, tid >> 5, 0);
  const int rank = blockIdx.x & 1, cl = blockIdx.x >> 1;
  const int c0 = (cl & 15) * 32, r0 = (cl >> 4) * 128;
  const uint32_t peer_off = mapa(sb, rank ^ 1) - sb;

  TR(wid >> 2, 1002);
  TRG(1020);
  if (tid == 0) {
    for (int i = 0; i < 2; i++) mbar_init(sb + BAR_W + 8 * i, 1);
    asm volatile("fence.mbarrier_init.release.cluster;" ::: "memory");
    for (int i = 0; i < 2; i++) mbar_expect(sb + BAR_W + 8 * i, 73728);
    for (int i = 0; i < 4; i++) bulk_load(sb + OFF_W1 + i * 18432, reinterpret_cast<const uint8_t*>(w1) + i * 18432, 18432, sb + BAR_W);
    for (int i = 0; i < 4; i++) bulk_load(sb + OFF_W2 + i * 18432, reinterpret_cast<const uint8_t*>(w2) + i * 18432, 18432, sb + BAR_W + 8);
  }
  if (tid == 256) {
    for (int i = 0; i < 4; i++) mbar_init(sb + BAR_RAW + 8 * i, 1);
    asm volatile("fence.mbarrier_init.release.cluster;" ::: "memory");
    TR(2, 1006);
    for (int i = 0; i < 4; i++)
      tma_raw(sb + OFF_RAW + i * RAW_BYTES, &tm, 56 * rank - 8, c0 / 2 - 2, r0 - 3 + 2 * i, sb + BAR_RAW + 8 * i);
    TR(2, 1007);
  }
  if (tid == 128) {
    for (int i = 0; i < 2; i++) mbar_init(sb + BAR_CFULL + 8 * i, 1);
    for (int i = 0; i < 4; i++) mbar_init(sb + BAR_CEMPTY + 8 * i, 4);
    for (int i = 0; i < 8; i++) mbar_init(sb + BAR_XFULL + 8 * i, 1);
    asm volatile("st.shared.v2.b32 [%0], {%1,%1};" ::"r"(sb + OFF_MAX), "r"(0) : "memory");
    for (int i = 0; i < 2; i++) mbar_expect(sb + BAR_CFULL + 8 * i, 12288);
    asm volatile("fence.mbarrier_init.release.cluster;" ::: "memory");
  }
  __syncthreads();
  asm volatile("barrier.cluster.arrive.relaxed.aligned;" ::: "memory");

  TR(wid >> 2, 1003);
  if (wid < 8) {
    MlpCtx m;
    m.sb = sb; m.wg = wid >> 2; m.warp = wid & 3; m.rank = rank; m.peer_off = peer_off; m.zero = zero;
    m.xsrc = reinterpret_cast<const uint8_t*>(x) + ((size_t)(r0 + 4 * m.wg + 2 * rank) * IMG + c0 + 8 * m.warp) * (CH * 2);
    m.optr = reinterpret_cast<uint8_t*>(out) + ((size_t)(r0 + 4 * m.wg + 2 * rank) * IMG + c0 + 8 * m.warp) * (CH * 2);
    m.caddr = sb + OFF_C + m.wg * C_BYTES + m.warp * 128 + (lane & 3) * (6 * 512 + 32) + (lane >> 2) * 16;
    m.xaddr = sb + OFF_XRES + wid * 3072 + ((lane >> 3) & 1) * 1536 + ((lane >> 4) * 4 + ((lane >> 2) & 1)) * 192 + (lane & 3) * 16;
    m.unscale = 0;
    asm volatile("setmaxnreg.dec.sync.aligned.u32 %0;" ::"n"(REG_MLP));
    mlp_role(m);
    __syncwarp();
    asm volatile("barrier.cluster.arrive.relaxed.aligned;\nbarrier.cluster.wait.aligned;" ::: "memory");
  } else {
    ConvCtx c;
    c.sb = sb; c.rank = rank; c.v = wid - 8; c.c0 = c0; c.r0 = r0; c.zero = zero; c.tm = &tm;
    c.peer_off = peer_off;
    const int g = lane >> 2, t = lane & 3;
    c.a_raw = sb + OFF_RAW + ((t >> 1) * 19 + 2 * (g + (t & 1))) * 112 + (1 - rank) * 16 + 16 * c.v;
    const int q0 = 12 * rank + 3 * c.v;
    c.a_c = sb + OFF_C + q0 * 512 + (q0 / 6) * 32 + lane * 16;
    asm volatile("setmaxnreg.inc.sync.aligned.u32 %0;" ::"n"(REG_CONV));
    conv_role(c, dw);
    __syncwarp();
    asm volatile("barrier.cluster.arrive.relaxed.aligned;\nbarrier.cluster.wait.aligned;\nexit;" ::: "memory");
  }
}

typedef CUresult (*EncodeFn)(CUtensorMap*, CUtensorMapDataType, cuuint32_t, void*, const cuuint64_t*, const cuuint64_t*,
                             const cuuint32_t*, const cuuint32_t*, CUtensorMapInterleave, CUtensorMapSwizzle,
                             CUtensorMapL2promotion, CUtensorMapFloatOOBfill);

}

extern "C" void kernel_launch(void* const* d_in, const int* in_sizes, int n_in, void* d_out, int out_size) {
  const __nv_bfloat16* x = (const __nv_bfloat16*)d_in[0];
  const __nv_bfloat16* dw = (const __nv_bfloat16*)d_in[1];
  const __nv_bfloat16* w1 = (const __nv_bfloat16*)d_in[2];
  const __nv_bfloat16* w2 = (const __nv_bfloat16*)d_in[3];
  __nv_bfloat16* out = (__nv_bfloat16*)d_out;

  static EncodeFn encode = nullptr;
  if (!encode) {
    cudaDriverEntryPointQueryResult st;
    void* fn = nullptr;
    cudaGetDriverEntryPoint("cuTensorMapEncodeTiled", &fn, cudaEnableDefault, &st);
    encode = (EncodeFn)fn;
    cudaFuncSetAttribute(convnext_kernel, cudaFuncAttributeMaxDynamicSharedMemorySize, SMEM_BYTES);
  }
  CUtensorMap tm;
  cuuint64_t dims[4] = {CH, IMG / 2, IMG, 2};
  cuuint64_t strides[3] = {CH * 4, (cuuint64_t)IMG * CH * 2, CH * 2};
  cuuint32_t box[4] = {56, 19, 2, 1};
  cuuint32_t es[4] = {1, 1, 1, 1};
  encode(&tm, CU_TENSOR_MAP_DATA_TYPE_BFLOAT16, 4, (void*)x, dims, strides, box, es, CU_TENSOR_MAP_INTERLEAVE_NONE,
         CU_TENSOR_MAP_SWIZZLE_NONE, CU_TENSOR_MAP_L2_PROMOTION_L2_128B, CU_TENSOR_MAP_FLOAT_OOB_FILL_NONE);
  convnext_kernel<<<128, 384, SMEM_BYTES>>>(tm, x, dw, w1, w2, out, 0);
}
```

```cpp
#include <cuda_runtime.h>
#include <cuda_bf16.h>
#include <cuda.h>
#include <stdint.h>

namespace {

constexpr int IMG = 512, CH = 96;
constexpr int NSTEP = 67;
constexpr int SIGMA = 7;
constexpr int NROUND = 68;

constexpr uint32_t OFF_W1 = 0;
constexpr uint32_t OFF_W2 = 73728;
constexpr uint32_t OFF_RAW = 147456;
constexpr uint32_t RAW_PLANE = 4352;
constexpr uint32_t RAW_BYTES = 2 * RAW_PLANE;
constexpr uint32_t RAW_TX = 2 * 2 * 19 * 112;
constexpr uint32_t OFF_XRES = OFF_RAW + 4 * RAW_BYTES;
constexpr uint32_t OFF_C = OFF_XRES + 2 * 12288;
constexpr uint32_t C_BYTES = 12416;
constexpr uint32_t OFF_BAR = OFF_C + 2 * C_BYTES;
constexpr uint32_t BAR_RAW = OFF_BAR;
constexpr uint32_t BAR_CFULL = OFF_BAR + 32;
constexpr uint32_t BAR_CEMPTY = OFF_BAR + 48;
constexpr uint32_t BAR_XFULL = OFF_BAR + 80;
constexpr uint32_t BAR_W = OFF_BAR + 144;
constexpr uint32_t OFF_NRM = OFF_BAR + 160;
constexpr uint32_t SMEM_BYTES = OFF_BAR + 224;

constexpr float GELU_A = 0.32918364f;
constexpr uint32_t GELU_K2 = 0x40d940d9u;

constexpr int NB_CLOSE = 1, NB_SEC = 6  , NB_OPEN = 3, NB_PLAN = 4, NB_PREP = 5;
#define REG_MLP 144
constexpr int REG_CONV = 504 - 2 * REG_MLP;

#define WG_FENCE() asm volatile("wgmma.fence.sync.aligned;" ::: "memory")
#define WG_COMMIT() asm volatile("wgmma.commit_group.sync.aligned;" ::: "memory")
#define WG_WAIT0() asm volatile("wgmma.wait_group.sync.aligned 0;" ::: "memory")
#define WG_WAIT1() asm volatile("wgmma.wait_group.sync.aligned 1;" ::: "memory")
#define PIN() asm volatile("pmevent 0;" ::: "memory")
#define NB_SYNC(id, n) asm volatile("bar.sync %0, %1;" ::"n"(id), "n"(n) : "memory")
#define NB_ARRIVE(id, n) asm volatile("bar.arrive %0, %1;" ::"n"(id), "n"(n) : "memory")

#define TR(who, idx)
#define TRG(idx)

#define R24(c, d)                                                                                        \
  c(d[0]), c(d[1]), c(d[2]), c(d[3]), c(d[4]), c(d[5]), c(d[6]), c(d[7]), c(d[8]), c(d[9]), c(d[10]),    \
      c(d[11]), c(d[12]), c(d[13]), c(d[14]), c(d[15]), c(d[16]), c(d[17]), c(d[18]), c(d[19]), c(d[20]), \
      c(d[21]), c(d[22]), c(d[23])
#define WG_TXT(sd)                                                                             \
  "wgmma.mma_async.sync.aligned.m64n96k16.f16.f16.f16 "                                        \
  "{%0,%1,%2,%3,%4,%5,%6,%7,%8,%9,%10,%11,%12,%13,%14,%15,%16,%17,%18,%19,%20,%21,%22,%23}, " \
  "{%24,%25,%26,%27}, %28, " sd ", 1, 1, 1;\n"

__device__ __forceinline__ void wg_acc(uint32_t (&d)[24], const uint32_t* a, uint64_t db) {
  asm volatile(WG_TXT("1") : R24("+r", d) : "r"(a[0]), "r"(a[1]), "r"(a[2]), "r"(a[3]), "l"(db));
}
__device__ __forceinline__ void wg_init(uint32_t (&d)[24], const uint32_t* a, uint64_t db) {
  asm volatile(WG_TXT("0") : R24("=r", d) : "r"(a[0]), "r"(a[1]), "r"(a[2]), "r"(a[3]), "l"(db));
}
template <int N>
__device__ __forceinline__ void rfence(uint32_t (&d)[N]) {
#pragma unroll
  for (int i = 0; i < N; i++) asm volatile("" : "+r"(d[i])::"memory");
}
template <bool INIT, int KSTRIDE>
__device__ __forceinline__ void gemm6(uint32_t (&d)[24], const uint32_t (&a)[24], uint64_t db) {
#pragma unroll
  for (int k = 0; k < 6; k++) {
    if (INIT && k == 0) wg_init(d, &a[0], db);
    else wg_acc(d, &a[4 * k], db + k * KSTRIDE);
  }
  WG_COMMIT();
}

__device__ __forceinline__ void mbar_init(uint32_t bar, uint32_t cnt) {
  asm volatile("mbarrier.init.shared::cta.b64 [%0], %1;" ::"r"(bar), "r"(cnt) : "memory");
}
__device__ __forceinline__ void mbar_expect(uint32_t bar, uint32_t bytes) {
  asm volatile("mbarrier.arrive.expect_tx.shared::cta.b64 _, [%0], %1;" ::"r"(bar), "r"(bytes) : "memory");
}
__device__ __forceinline__ void mbar_arrive_cluster(uint32_t bar) {
  asm volatile("mbarrier.arrive.shared::cluster.b64 _, [%0];" ::"r"(bar) : "memory");
}
__device__ __forceinline__ bool mbar_try(uint32_t bar, uint32_t parity) {
  uint32_t ok;
  asm volatile(
      "{\n.reg .pred p;\nmbarrier.try_wait.parity.shared::cta.b64 p, [%1], %2;\nselp.u32 %0, 1, 0, p;\n}\n"
      : "=r"(ok)
      : "r"(bar), "r"(parity)
      : "memory");
  return ok;
}
__device__ __forceinline__ bool mbar_test(uint32_t bar, uint32_t parity) {
  uint32_t ok;
  asm volatile(
      "{\n.reg .pred p;\nmbarrier.test_wait.parity.shared::cta.b64 p, [%1], %2;\nselp.u32 %0, 1, 0, p;\n}\n"
      : "=r"(ok)
      : "r"(bar), "r"(parity)
      : "memory");
  return ok;
}
__device__ __forceinline__ void mbar_wait(uint32_t bar, uint32_t parity) {
  if (__builtin_expect(mbar_try(bar, parity), 1)) return;
#pragma unroll 1
  for (uint32_t n = 0; n < (1u << 16) && !mbar_try(bar, parity); n++) {}
}
__device__ __forceinline__ uint32_t mapa(uint32_t addr, uint32_t rank) {
  uint32_t r;
  asm("mapa.shared::cluster.u32 %0, %1, %2;" : "=r"(r) : "r"(addr), "r"(rank));
  return r;
}
__device__ __forceinline__ void tma_raw(uint32_t dst, const CUtensorMap* tm, int c, int w2, int h, uint32_t bar) {
  mbar_expect(bar, RAW_TX);
#pragma unroll
  for (int e = 0; e < 2; e++)
    asm volatile(
        "cp.async.bulk.tensor.4d.shared::cluster.global.mbarrier::complete_tx::bytes [%0], [%1, {%2, %3, %4, %5}], [%6];"
        ::"r"(dst + e * RAW_PLANE), "l"(tm), "r"(c), "r"(w2 + e), "r"(h), "r"(1 - e), "r"(bar)
        : "memory");
}
__device__ __forceinline__ void bulk_load(uint32_t dst, const void* src, uint32_t bytes, uint32_t bar) {
  asm volatile("cp.async.bulk.shared::cluster.global.mbarrier::complete_tx::bytes [%0], [%1], %2, [%3];" ::"r"(dst),
               "l"(src), "r"(bytes), "r"(bar)
               : "memory");
}
__device__ __forceinline__ uint32_t pack_bf16(float lo, float hi) {
  uint32_t r;
  asm("cvt.rn.bf16x2.f32 %0, %1, %2;" : "=r"(r) : "f"(hi), "f"(lo));
  return r;
}
__device__ __forceinline__ uint32_t pack_f16(float lo, float hi) {
  uint32_t r;
  asm("cvt.rn.f16x2.f32 %0, %1, %2;" : "=r"(r) : "f"(hi), "f"(lo));
  return r;
}
__device__ __forceinline__ float bf_lo(uint32_t v) { return __uint_as_float(v << 16); }
__device__ __forceinline__ float bf_hi(uint32_t v) { return __uint_as_float(v & 0xffff0000u); }
__device__ __forceinline__ uint32_t bf_add(uint32_t a, uint32_t b) {
  uint32_t r;
  asm("add.rn.bf16x2 %0, %1, %2;" : "=r"(r) : "r"(a), "r"(b));
  return r;
}
__device__ __forceinline__ uint32_t bf_mul(uint32_t a, uint32_t b) {
  uint32_t r;
  asm("mul.rn.bf16x2 %0, %1, %2;" : "=r"(r) : "r"(a), "r"(b));
  return r;
}
__device__ __forceinline__ uint32_t bf_fma(uint32_t a, uint32_t b, uint32_t c) {
  uint32_t r;
  asm("fma.rn.bf16x2 %0, %1, %2, %3;" : "=r"(r) : "r"(a), "r"(b), "r"(c));
  return r;
}

__device__ __forceinline__ uint32_t h_add(uint32_t a, uint32_t b) {
  uint32_t r;
  asm("add.rn.f16x2 %0, %1, %2;" : "=r"(r) : "r"(a), "r"(b));
  return r;
}
__device__ __forceinline__ uint32_t h_mul(uint32_t a, uint32_t b) {
  uint32_t r;
  asm("mul.rn.f16x2 %0, %1, %2;" : "=r"(r) : "r"(a), "r"(b));
  return r;
}
__device__ __forceinline__ uint32_t h_fma(uint32_t a, uint32_t b, uint32_t c) {
  uint32_t r;
  asm("fma.rn.f16x2 %0, %1, %2, %3;" : "=r"(r) : "r"(a), "r"(b), "r"(c));
  return r;
}
__device__ __forceinline__ float h_sum(uint32_t v) {
  float lo, hi;
  asm("{\n.reg .b16 l, h;\nmov.b32 {l, h}, %2;\ncvt.f32.f16 %0, l;\ncvt.f32.f16 %1, h;\n}\n" : "=f"(lo), "=f"(hi) : "r"(v));
  return lo + hi;
}
__device__ __forceinline__ void lds128(uint32_t (&v)[4], uint32_t a) {
  asm volatile("ld.shared.v4.b32 {%0,%1,%2,%3}, [%4];" : "=r"(v[0]), "=r"(v[1]), "=r"(v[2]), "=r"(v[3]) : "r"(a) : "memory");
}

template <int LO, int HI>
__device__ __forceinline__ void gelu(uint32_t (&o)[24], const uint32_t (&d)[24]) {
#pragma unroll
  for (int qq = LO; qq < HI; qq++) {
    const int q = (qq + 4) % 24;
    uint32_t t, u;
    asm("fma.rn.f16x2 %0, %1, %1, %2;" : "=r"(t) : "r"(d[q]), "r"(GELU_K2));
    asm("mul.rn.f16x2 %0, %1, %2;" : "=r"(u) : "r"(d[q]), "r"(t));
    asm("tanh.approx.f16x2 %0, %1;" : "=r"(t) : "r"(u));
    asm("fma.rn.f16x2 %0, %1, %2, %1;" : "=r"(o[q]) : "r"(d[q]), "r"(t));
  }
}

__device__ __forceinline__ uint32_t laneid() {
  uint32_t l;
  asm volatile("mov.u32 %0, %%laneid;" : "=r"(l));
  return l;
}

__device__ __forceinline__ bool elect_one() {
  uint32_t p;
  asm volatile("{\n.reg .pred p;\nelect.sync _|p, 0xffffffff;\nselp.u32 %0, 1, 0, p;\n}\n" : "=r"(p));
  return p;
}

struct MlpCtx {
  uint32_t sb;
  uint32_t caddr;
  uint32_t xaddr;
  uint32_t unscale;
  uint32_t peer_off;
  int wg, warp, rank, zero;
  const uint8_t* xsrc;
  uint8_t* optr;
};

__device__ __forceinline__ void ln_wait(const MlpCtx& m, int i) { mbar_wait(m.sb + BAR_CFULL + 8 * m.wg, i & 1); }
__device__ __forceinline__ void ln_load(const MlpCtx& m, uint32_t (&c)[24]) {
#pragma unroll
  for (int p = 0; p < 6; p++)
    asm volatile("ld.shared.v4.b32 {%0,%1,%2,%3}, [%4];"
                 : "=r"(c[4 * p]), "=r"(c[4 * p + 1]), "=r"(c[4 * p + 2]), "=r"(c[4 * p + 3])
                 : "r"(m.caddr + p * 512)
                 : "memory");
}
__device__ __forceinline__ void ln_shfl(float (&st)[8], int mask) {
#pragma unroll
  for (int k = 0; k < 4; k++) st[4 + k] = __shfl_xor_sync(0xffffffffu, st[k], mask);
}
__device__ __forceinline__ void ln_fold(float (&st)[8]) {
#pragma unroll
  for (int k = 0; k < 4; k++) st[k] += st[4 + k];
}
__device__ __forceinline__ void ln_sums(const uint32_t (&c)[24], float (&st)[8]) {
#pragma unroll
  for (int r = 0; r < 2; r++) {
    uint32_t s0 = h_add(c[r], c[r + 2]), s1 = h_add(c[r + 4], c[r + 6]), s2 = h_add(c[r + 8], c[r + 10]);
    uint32_t s3 = h_add(c[r + 12], c[r + 14]), s4 = h_add(c[r + 16], c[r + 18]), s5 = h_add(c[r + 20], c[r + 22]);
    s0 = h_add(s0, s1); s2 = h_add(s2, s3); s4 = h_add(s4, s5);
    st[r] = h_sum(h_add(h_add(s0, s2), s4));
    uint32_t q0 = h_mul(c[r], c[r]), q1 = h_mul(c[r + 2], c[r + 2]);
#pragma unroll
    for (int p = 2; p < 12; p += 2) {
      q0 = h_fma(c[2 * p + r], c[2 * p + r], q0);
      q1 = h_fma(c[2 * p + 2 + r], c[2 * p + 2 + r], q1);
    }
    st[2 + r] = h_sum(h_add(q0, q1));
  }
}
__device__ __forceinline__ void ln_release(const MlpCtx& m, bool on) {
  const uint32_t e = m.sb + BAR_CEMPTY + 8 * (2 * m.rank + m.wg);
  asm volatile(
      "{\n.reg .pred p, q;\nelect.sync _|p, 0xffffffff;\nsetp.ne.and.s32 p, %4, 0, p;\nsetp.eq.and.s32 q, %3, 0, p;\n"
      "@q mbarrier.arrive.expect_tx.shared::cta.b64 _, [%0], 12288;\n"
      "@p mbarrier.arrive.shared::cluster.b64 _, [%1];\n"
      "@p mbarrier.arrive.shared::cluster.b64 _, [%2];\n}\n" ::"r"(m.sb + BAR_CFULL + 8 * m.wg),
      "r"(e), "r"(e + m.peer_off), "r"(m.warp), "r"((int)on)
      : "memory");
}
__device__ __forceinline__ void ln_stats(float (&st)[8], uint32_t& bad, uint32_t bit) {
  bool ok = true;
#pragma unroll
  for (int r = 0; r < 2; r++) {
    const float nm = (st[r] + st[4 + r]) * (-1.0f / 96.0f);
    const float e2 = fmaf(st[2 + r] + st[6 + r], 1.0f / 96.0f, 1e-5f);
    float rs;
    asm("rsqrt.approx.ftz.f32 %0, %1;" : "=f"(rs) : "f"(fmaf(-nm, nm, e2)));
    ok = ok && (rs * rs * e2 <= 17.0f) && (e2 >= 1.001e-5f);
    const float rr = rs * GELU_A, dd = rr * nm;
    st[r] = __uint_as_float(pack_f16(rr, rr));
    st[2 + r] = __uint_as_float(pack_f16(dd, dd));
  }
  if (!ok) bad |= bit;
}
__device__ __forceinline__ void ln_apply(uint32_t (&a)[24], const uint32_t (&c)[24], const float (&st)[8]) {
#pragma unroll
  for (int p = 0; p < 24; p++) a[p] = h_fma(c[p], __float_as_uint(st[p & 1]), __float_as_uint(st[2 + (p & 1)]));
}

__device__ __noinline__ void slow_tile(const __nv_bfloat16* x, const __nv_bfloat16* dw, const __nv_bfloat16* w1,
                                       const __nv_bfloat16* w2, __nv_bfloat16* out, int row0, int col0, float* buf) {
  const int lane = threadIdx.x & 31;
  for (int px = 0; px < 16; px++) {
    const int row = row0 + (px >> 3), col = col0 + (px & 7);
    float c[3] = {0.f, 0.f, 0.f};
    for (int i = 0; i < 7; i++)
      for (int j = 0; j < 7; j++) {
        const int rr = row + i - 3, cc = col + j - 3;
        if (rr < 0 || rr >= IMG || cc < 0 || cc >= IMG) continue;
        for (int k = 0; k < 3; k++)
          c[k] = fmaf(__bfloat162float(x[((size_t)rr * IMG + cc) * CH + lane + 32 * k]), __bfloat162float(dw[(i * 7 + j) * CH + lane + 32 * k]), c[k]);
      }
    float mean = (c[0] + c[1] + c[2]) * (1.0f / 96.0f);
    for (int o = 16; o; o >>= 1) mean += __shfl_xor_sync(0xffffffffu, mean, o);
    float var = 0.f;
    for (int k = 0; k < 3; k++) { c[k] -= mean; var = fmaf(c[k] * (1.0f / 96.0f), c[k], var); }
    for (int o = 16; o; o >>= 1) var += __shfl_xor_sync(0xffffffffu, var, o);
    const float rs = 1.0f / sqrtf(var + 1e-5f);
    __syncwarp();
    for (int k = 0; k < 3; k++) buf[lane + 32 * k] = c[k] * rs;
    __syncwarp();
    for (int n = lane; n < 4 * CH; n += 32) {
      float y = 0.f;
      for (int k = 0; k < CH; k++) y = fmaf(buf[k], __bfloat162float(w1[k * 4 * CH + n]), y);
      buf[CH + n] = 0.5f * y * (1.0f + tanhf(0.7978845608f * (y + 0.044715f * y * y * y)));
    }
    __syncwarp();
    for (int n = lane; n < CH; n += 32) {
      float o = 0.f;
      for (int k = 0; k < 4 * CH; k++) o = fmaf(buf[CH + k], __bfloat162float(w2[k * CH + n]), o);
      const size_t idx = ((size_t)row * IMG + col) * CH + n;
      out[idx] = __float2bfloat16(__bfloat162float(x[idx]) + o);
    }
  }
}

__device__ __forceinline__ void issue_xres(const MlpCtx& m, int i) {
  if (elect_one()) {
    uint32_t bar = m.sb + BAR_XFULL + 8 * (4 * m.wg + m.warp);
    uint32_t dst = m.sb + OFF_XRES + (4 * m.wg + m.warp) * 3072;
    const uint8_t* src = m.xsrc + (size_t)i * (8 * IMG * CH * 2);
    asm volatile("cp.async.bulk.wait_group.read 0;" ::: "memory");
    mbar_expect(bar, 3072);
    bulk_load(dst, src, 1536, bar);
    bulk_load(dst + 1536, src + IMG * CH * 2, 1536, bar);
  }
}
__device__ __forceinline__ void x_wait(const MlpCtx& m, int i) { mbar_wait(m.sb + BAR_XFULL + 8 * (4 * m.wg + m.warp), i & 1); }
__device__ __forceinline__ void x_load(const MlpCtx& m, uint32_t (&x)[24]) {
#pragma unroll
  for (int k = 0; k < 6; k++)
    asm volatile("ld.shared.v4.b32 {%0,%1,%2,%3}, [%4];"
                 : "=r"(x[4 * k]), "=r"(x[4 * k + 1]), "=r"(x[4 * k + 2]), "=r"(x[4 * k + 3])
                 : "r"(m.xaddr + (k / 3) * 384 + (k % 3) * 64)
                 : "memory");
}
template <int LO, int HI>
__device__ __forceinline__ void epilogue(const MlpCtx& m, const uint32_t (&d)[24], uint32_t (&x)[24]) {
#pragma unroll
  for (int k = LO; k < HI; k++) {
    const int r = k / 3, q = k % 3;
    uint32_t* y = &x[4 * k];
#pragma unroll
    for (int j = 0; j < 4; j++) {
      uint32_t v = d[2 * (4 * q + j) + r];
      float lo, hi;
      asm("{\n.reg .b16 l, h;\nmov.b32 {l, h}, %2;\ncvt.f32.f16 %0, l;\ncvt.f32.f16 %1, h;\n}\n" : "=f"(lo), "=f"(hi) : "r"(v));
      asm("fma.rn.bf16x2 %0, %1, %2, %0;" : "+r"(y[j]) : "r"(pack_bf16(lo, hi)), "r"(m.unscale));
    }
    asm volatile("st.shared.v4.b32 [%0], {%1,%2,%3,%4};" ::"r"(m.xaddr + r * 384 + q * 64), "r"(y[0]), "r"(y[1]), "r"(y[2]), "r"(y[3])
                 : "memory");
  }
}
__device__ __forceinline__ void out_store(const MlpCtx& m, int i) {
  asm volatile("fence.proxy.async.shared::cta;" ::: "memory");
  __syncwarp();
  if (elect_one()) {
    const uint32_t src = m.sb + OFF_XRES + (4 * m.wg + m.warp) * 3072;
    uint8_t* dst = m.optr + (size_t)i * (8 * IMG * CH * 2);
    asm volatile("cp.async.bulk.global.shared::cta.bulk_group [%0], [%1], 1536;" ::"l"(dst), "r"(src) : "memory");
    asm volatile("cp.async.bulk.global.shared::cta.bulk_group [%0], [%1], 1536;" ::"l"(dst + IMG * CH * 2), "r"(src + 1536) : "memory");
    asm volatile("cp.async.bulk.commit_group;" ::: "memory");
  }
}

template <int J> __device__ __forceinline__ void tok_wait() {
  if (J == 0 || J == 3) NB_SYNC(NB_CLOSE, 256);
  else NB_SYNC(NB_SEC + (J & 1), 256);
}
template <int J> __device__ __forceinline__ void tok_next() {
  if (J == 0 || J == 3) NB_ARRIVE(NB_SEC + (J & 1), 256);
}
__device__ __forceinline__ void tok_pass() { NB_ARRIVE(NB_OPEN, 384); }
template <int J> __device__ __forceinline__ void tok_idle() { tok_wait<J>(); tok_next<J>(); tok_pass(); }

constexpr uint64_t CHK = 1152;

__device__ __forceinline__ void sumsq(const uint32_t (&v)[18][4], uint32_t dst) {
  uint32_t q[4] = {0, 0, 0, 0};
#pragma unroll
  for (int it = 0; it < 18; it++)
#pragma unroll
    for (int t = 0; t < 4; t++) q[t] = bf_fma(v[it][t], v[it][t], q[t]);
  q[0] = bf_add(bf_add(q[0], q[1]), bf_add(q[2], q[3]));
  float f = bf_lo(q[0]) + bf_hi(q[0]);
#pragma unroll
  for (int o = 16; o; o >>= 1) f += __shfl_xor_sync(0xffffffffu, f, o);
  if ((threadIdx.x & 31) == 0) asm volatile("st.shared.f32 [%0], %1;" ::"r"(dst), "f"(f) : "memory");
}

__device__ __forceinline__ uint32_t mlp_role(const MlpCtx& m0) {
  MlpCtx m = m0;
  uint32_t bad = 0;
  const int lane = threadIdx.x & 31, wid = m.wg * 4 + m.warp;
  {
    uint32_t v[18][4];
    const int k7 = lane & 7;
    {
      mbar_wait(m.sb + BAR_W, 0);
#pragma unroll
      for (int it = 0; it < 18; it++) {
        const int kb = (it / 3) * 2 + (wid & 1), ks = it / 3;
        const int Q = 6 * (k7 >> 1) + ks, q12 = Q % 12, cv = q12 / 3, e = q12 % 3;
        const int ch = 48 * (Q / 12) + (e < 2 ? 8 * cv + 4 * e : 32 + 4 * cv) + 2 * (kb & 1) + (k7 & 1);
        const int n8 = (it % 3) * 16 + ((wid >> 2) * 8 + ((((wid >> 1) & 1) * 4 + (lane >> 3) + k7) & 7));
        lds128(v[it], m.sb + OFF_W1 + ch * 768 + n8 * 16);
      }
      sumsq(v, m.sb + OFF_NRM + 4 * wid);
      NB_SYNC(NB_PREP, 256);
#pragma unroll
      for (int it = 0; it < 18; it++) {
        const int n8 = (it % 3) * 16 + ((wid >> 2) * 8 + ((((wid >> 1) & 1) * 4 + (lane >> 3) + k7) & 7));
        const uint32_t dst = m.sb + OFF_W1 + (it / 3) * 12288 + n8 * 256 + (wid & 1) * 128 + k7 * 16;
        asm volatile("st.shared.v4.b32 [%0], {%1,%2,%3,%4};" ::"r"(dst), "r"(pack_f16(bf_lo(v[it][0]), bf_hi(v[it][0]))),
                     "r"(pack_f16(bf_lo(v[it][1]), bf_hi(v[it][1]))), "r"(pack_f16(bf_lo(v[it][2]), bf_hi(v[it][2]))),
                     "r"(pack_f16(bf_lo(v[it][3]), bf_hi(v[it][3])))
                     : "memory");
      }
    }
    TR(m.wg, 1004);
    {
      mbar_wait(m.sb + BAR_W + 8, 0);
      const uint32_t base = m.sb + OFF_W2 + wid * 9216;
#pragma unroll
      for (int it = 0; it < 18; it++) lds128(v[it], base + (lane >> 2) * 192 + (lane & 3) * 16 + (it / 3) * 1536 + (it % 3) * 64);
      sumsq(v, m.sb + OFF_NRM + 32 + 4 * wid);
      TR(m.wg, 1005);
      NB_SYNC(NB_PREP, 256);
      int e[2];
#pragma unroll
      for (int k = 0; k < 2; k++) {
        uint32_t a[4], b[4];
        lds128(a, m.sb + OFF_NRM + 32 * k);
        lds128(b, m.sb + OFF_NRM + 32 * k + 16);
        float f = 0.f;
#pragma unroll
        for (int t = 0; t < 4; t++) f += __uint_as_float(a[t]) + __uint_as_float(b[t]);
        e[k] = (((int)(__float_as_uint(f * 1.5f) >> 23) - 127) >> 1) + 1;
      }
      const int s = min(11 - e[0] - e[1], 14 - e[1]);
      if (e[0] > 12 || e[0] < -5 || e[1] > 60 || e[1] < -60) bad = 0xffffu;
      const float sc = __uint_as_float((uint32_t)(127 + s) << 23) * (0.5f / GELU_A);
      m.unscale = __shfl_sync(0xffffffffu, ((uint32_t)(127 - s) << 7) * 0x10001u, 0);
#pragma unroll
      for (int it = 0; it < 18; it++)
#pragma unroll
        for (int j = 0; j < 4; j++)
          asm volatile("st.shared.b32 [%0], %1;" ::"r"(base + lane * 4 + (it / 6) * 3072 + ((it / 3) & 1) * 128 + ((it % 3) * 4 + j) * 256),
                       "r"(pack_f16(bf_lo(v[it][j]) * sc, bf_hi(v[it][j]) * sc))
                       : "memory");
    }
    asm volatile("fence.proxy.async.shared::cta;" ::: "memory");
    NB_SYNC(NB_PREP, 256);
  }
  asm volatile("barrier.cluster.wait.aligned;" ::: "memory");
  const uint64_t dW1 = (uint64_t)(((m.sb + OFF_W1) & 0x3FFFF) >> 4) | ((uint64_t)8 << 16) | ((uint64_t)16 << 32);
  const uint64_t dW2 = dW1 + (OFF_W2 >> 4);

  TR(m.wg, 1000);
  uint32_t A1[24], g[24], d[24], cn[24], D2[24];
  float st[8];
  ln_wait(m, 0);
  ln_load(m, cn);
  ln_sums(cn, st);
  ln_shfl(st, 1);
  ln_release(m, true);
  ln_fold(st);
  ln_shfl(st, 2);
  ln_stats(st, bad, 1);
  ln_apply(A1, cn, st);
  [[maybe_unused]] int rho = 2 * m.wg + m.rank + 2;
  if (m.wg & m.rank) tok_idle<3>();
  if (m.wg) tok_idle<0>();
  if (m.wg | m.rank) tok_idle<1>();
  {
    uint32_t d0[24];
    WG_FENCE();
    tok_wait<2>();
    gemm6<true, 768>(d0, A1, dW1);
    tok_pass(); PIN();
    WG_WAIT0(); rfence(d0);
    WG_FENCE();
    tok_wait<3>();
    tok_next<3>();
    gemm6<true, 768>(d, A1, dW1 + 192);
    tok_pass(); PIN();
    gelu<0, 24>(g, d0);
    PIN();
    ln_wait(m, 1);
    ln_load(m, cn);
    PIN();
    WG_WAIT0(); rfence(d);
  }
#define G2(INIT, a, j)                      \
  WG_FENCE();                               \
  tok_wait<j>();                            \
  TR(m.wg, rho * 8);                        \
  gemm6<INIT, 192>(D2, a, dW2 + (j) * CHK); \
  tok_next<j>(); PIN();                     \
  TR(m.wg, rho * 8 + 1);
#define G1(dst, j)                          \
  TR(m.wg, rho * 8 + 2);                    \
  PIN(); WG_WAIT0(); rfence(D2);            \
  WG_FENCE();                               \
  gemm6<true, 768>(dst, A1, dW1 + (j) * 192); \
  tok_pass(); PIN();                        \
  TR(m.wg, rho * 8 + 3);
#define ROUND_END(dst)                      \
  TR(m.wg, rho * 8 + 4);                    \
  PIN(); WG_WAIT0(); rfence(dst); rho++;
#define GA 10
#define GB 12
#define GC 10
#define GD 12
#pragma unroll 1
  for (int i = 0;; i++) {
    uint32_t g1[24], d2[24], g2[24], d3[24], g3[24], d0[24];
    G2(true, g, 0)
    gelu<0, GA>(g1, d);
    G1(d2, 2)
    ln_sums(cn, st);
    gelu<GA, 24>(g1, d);
    PIN();
    ln_release(m, i < 15);
    if (i > 0) out_store(m, i - 1);
    ln_shfl(st, 1);
    ROUND_END(d2)

    G2(false, g1, 1)
    ln_fold(st);
    gelu<0, GB>(g2, d2);
    PIN();
    ln_shfl(st, 2);
    G1(d3, 3)
    ln_stats(st, bad, 2u << i);
    gelu<GB, 24>(g2, d2);
    PIN();
    issue_xres(m, i);
    ROUND_END(d3)

    if (i == 15) {
      G2(false, g2, 2)
      tok_pass();
      gelu<0, 24>(g3, d3);
      PIN();
      x_wait(m, i);
      x_load(m, cn);
      ROUND_END(D2)
      G2(false, g3, 3)
      tok_pass();
      WG_WAIT0(); rfence(D2);
      epilogue<0, 6>(m, D2, cn);
      break;
    }
    G2(false, g2, 2)
    ln_apply(A1, cn, st);
    PIN();
    gelu<0, GC>(g3, d3);
    G1(d0, 0)
    gelu<GC, 24>(g3, d3);
    PIN();
    x_wait(m, i);
    x_load(m, cn);
    ROUND_END(d0)

    G2(false, g3, 3)
    gelu<0, GD>(g, d0);
    G1(d, 1)
    epilogue<0, 6>(m, D2, cn);
    gelu<GD, 24>(g, d0);
    PIN();
    if (i < 14) ln_wait(m, i);
    ln_load(m, cn);
    ROUND_END(d)
  }
  out_store(m, 15);
  if (m.wg == 0) { tok_idle<0>(); tok_idle<1>(); }
  asm volatile("cp.async.bulk.wait_group 0;" ::: "memory");
  TR(m.wg, 1001);
  TRG(1021);
  return __reduce_or_sync(0xffffffffu, bad & 0xffffu);
}

struct ConvCtx {
  uint32_t sb;
  uint32_t a_raw, a_c;
  uint32_t peer_off;
  int rank, v, c0, r0, zero;
  const CUtensorMap* tm;
};

__device__ __forceinline__ void conv_ld8(uint32_t a, uint32_t (&r)[6][6]) {
#pragma unroll
  for (int j = 0; j < 6; j++)
    asm volatile("ld.shared.v4.b32 {%0,%1,%2,%3}, [%4];"
                 : "=r"(r[j][0]), "=r"(r[j][1]), "=r"(r[j][2]), "=r"(r[j][3])
                 : "r"(a + (j >> 1) * 112 + (j & 1) * RAW_PLANE)
                 : "memory");
}
__device__ __forceinline__ void conv_ld4(uint32_t a, uint32_t (&r)[6][6]) {
#pragma unroll
  for (int j = 0; j < 6; j++)
    asm volatile("ld.shared.v2.b32 {%0,%1}, [%2];" : "=r"(r[j][4]), "=r"(r[j][5]) : "r"(a + (j >> 1) * 112 + (j & 1) * RAW_PLANE) : "memory");
}
__device__ __forceinline__ void conv_frags(uint32_t zero, const uint32_t (&r)[6][6], uint32_t (&A)[12][4]) {
#pragma unroll
  for (int ch = 0; ch < 12; ch++) {
    const uint32_t sel = (ch & 1) ? 0x7632 : 0x5410;
    A[ch][0] = __byte_perm(r[0][ch >> 1], r[1][ch >> 1], sel);
    A[ch][1] = __byte_perm(r[2][ch >> 1], r[3][ch >> 1], sel);
    A[ch][2] = A[ch][1] ^ zero;
    A[ch][3] = __byte_perm(r[4][ch >> 1], r[5][ch >> 1], sel);
  }
}
__device__ __forceinline__ uint32_t clock_pin() {
  uint32_t t;
  asm volatile("mov.u32 %0, %%clock;" : "=r"(t)::"memory");
  return t;
}

__device__ __forceinline__ void hmma_acc(uint32_t (&v)[4], const uint32_t (&a)[4], const uint32_t* b) {
  asm volatile("mma.sync.aligned.m16n8k16.row.col.f32.bf16.bf16.f32 {%0,%1,%2,%3}, {%4,%5,%6,%7}, {%8,%9}, {%0,%1,%2,%3};"
               : "+r"(v[0]), "+r"(v[1]), "+r"(v[2]), "+r"(v[3])
               : "r"(a[0]), "r"(a[1]), "r"(a[2]), "r"(a[3]), "r"(b[0]), "r"(b[1]));
}
__device__ __forceinline__ void hmma_new(uint32_t (&a)[4], const uint32_t* b) {
  asm volatile("mma.sync.aligned.m16n8k16.row.col.f32.bf16.bf16.f32 {%0,%1,%2,%3}, {%0,%1,%2,%3}, {%4,%5}, {%6,%6,%6,%6};"
               : "+r"(a[0]), "+r"(a[1]), "+r"(a[2]), "+r"(a[3])
               : "r"(b[0]), "r"(b[1]), "f"(0.f));
}

template <bool GATED, bool MORE>
__device__ __forceinline__ void conv_step(const ConvCtx& c, int s, uint32_t (&K)[12], uint32_t (&V)[12][4], const uint32_t (&B)[12][4],
                                          uint32_t (&A)[12][4]) {
  const int nx = (s + 1) & 3;
  uint32_t r[6][6];
  TR(2, s * 8);
  PIN();
  if (GATED) NB_SYNC(NB_OPEN, 384);
  else NB_SYNC(NB_PLAN, 128);
  if (MORE) conv_ld8(c.a_raw + nx * RAW_BYTES, r);
  if (c.v == (s & 3) && s + 4 < NSTEP && elect_one())
    tma_raw(c.sb + OFF_RAW + c.v * RAW_BYTES, c.tm, 56 * c.rank - 8, c.c0 / 2 - 2, c.r0 - 3 + 2 * (s + 4), c.sb + BAR_RAW + 8 * c.v);
  PIN();
  TR(2, s * 8 + 1);
#pragma unroll
  for (int ch = 0; ch < 12; ch++) {
    hmma_acc(V[ch], A[ch], &B[ch][2]);
    hmma_new(A[ch], &B[ch][0]);
  }
  const uint32_t z1 = clock_pin();
  if (GATED) NB_ARRIVE(NB_CLOSE, 256);
  PIN();
  TR(2, s * 8 + 2);
  uint32_t pk[12];
#pragma unroll
  for (int q = 0; q < 12; q++) {
    const int ch = q & ~1, h = 2 * (q & 1);
    pk[q] = h_add(pack_f16(__uint_as_float(V[ch][h + 1]), __uint_as_float(V[ch + 1][h])), K[q]);
    K[q] = pack_f16(__uint_as_float(V[ch][h]), __uint_as_float(V[ch + 1][h + 1]));
  }
  rfence(K);
  rfence(pk);
  PIN();
  if (MORE) conv_ld4(c.a_raw + nx * RAW_BYTES + 64 - 8 * c.v, r);
  const int n2 = (s + 2) & 3, par = ((s + 2) >> 2) & 1;
  const uint32_t braw = c.sb + BAR_RAW + 8 * n2, bemp = c.sb + BAR_CEMPTY + 8 * (2 * (n2 & 1) + (n2 >> 1));
  bool ok = true;
  if (MORE) ok = mbar_test(braw, par) & mbar_test(bemp, par);
  if (GATED || s >= 3) {
    const uint32_t off = ((nx & 1) == c.rank) ? 0u : c.peer_off;
    const uint32_t dst = c.a_c + off + (nx >> 1) * C_BYTES, bar = c.sb + off + BAR_CFULL + 8 * (nx >> 1);
#pragma unroll
    for (int q = 0; q < 3; q++)
      asm volatile("st.async.weak.shared::cluster.mbarrier::complete_tx::bytes.v4.b32 [%0], {%1,%2,%3,%4}, [%5];" ::"r"(dst + q * 512),
                   "r"(pk[4 * q]), "r"(pk[4 * q + 1]), "r"(pk[4 * q + 2]), "r"(pk[4 * q + 3]), "r"(bar)
                   : "memory");
  }
  TR(2, s * 8 + 3);
  if (MORE) {
    conv_frags(c.zero & z1, r, V);
#pragma unroll
    for (int ch = 0; ch < 12; ch++) rfence(V[ch]);
  }
  PIN();
  TR(2, s * 8 + 4);
  if (!ok) {
    if (s + 2 < NSTEP) mbar_wait(braw, par);
    if (s + 1 >= 7) mbar_wait(bemp, par);
  }
}

__device__ __forceinline__ void conv_role(const ConvCtx& c, const __nv_bfloat16* dw) {
  const int lane = threadIdx.x & 31, g = lane >> 2, t = lane & 3;
  uint32_t B[12][4];
  {
    const int dc = (g >> 1) & 1, ro = g >> 2, rk = t >> 1;
    const uint8_t* dwp = reinterpret_cast<const uint8_t*>(dw) + 96 * c.rank;
#pragma unroll
    for (int pb = 0; pb < 4; pb++) {
      const int par = pb >> 1, b = pb & 1;
      const int i = 2 * (2 * ((g ^ par) & 1) + b) + rk - ro;
      uint32_t w[4][6];
#pragma unroll
      for (int k = 0; k < 4; k++) {
        const int j = 4 * (t & 1) + k - dc;
        const bool ok = i >= 0 && i < 7 && j >= 0 && j < 7;
        uint4 w8 = make_uint4(0, 0, 0, 0);
        uint2 w4 = make_uint2(0, 0);
        if (ok) {
          w8 = __ldg(reinterpret_cast<const uint4*>(dwp + (i * 7 + j) * 192 + 16 * c.v));
          w4 = __ldg(reinterpret_cast<const uint2*>(dwp + (i * 7 + j) * 192 + 64 + 8 * c.v));
        }
        w[k][0] = w8.x; w[k][1] = w8.y; w[k][2] = w8.z; w[k][3] = w8.w; w[k][4] = w4.x; w[k][5] = w4.y;
      }
#pragma unroll
      for (int q = 0; q < 6; q++) {
        B[2 * q + par][2 * b] = __byte_perm(w[0][q], w[1][q], par ? 0x7632 : 0x5410);
        B[2 * q + par][2 * b + 1] = __byte_perm(w[2][q], w[3][q], par ? 0x7632 : 0x5410);
      }
    }
  }
  TR(2, 1004);
  asm volatile("barrier.cluster.wait.aligned;" ::: "memory");
  uint32_t K1[12], K2[12], V[12][4];
#pragma unroll
  for (int ch = 0; ch < 12; ch++) {
    K1[ch] = K2[ch] = 0;
#pragma unroll
    for (int k = 0; k < 4; k++) V[ch][k] = 0;
  }
  uint32_t A[12][4];
  {
    uint32_t r[6][6];
    mbar_wait(c.sb + BAR_RAW, 0);
    conv_ld8(c.a_raw, r);
    conv_ld4(c.a_raw + 64 - 8 * c.v, r);
    conv_frags(c.zero, r, A);
    mbar_wait(c.sb + BAR_RAW + 8, 0);
  }
  NB_ARRIVE(NB_CLOSE, 256);
  static_assert(SIGMA == 7, "ungated steps must not need a free-slot wait");
#pragma unroll 1
  for (int s = 0;; s += 2) {
    conv_step<false, true>(c, s, K1, V, B, A);
    if (s == SIGMA - 1) break;
    conv_step<false, true>(c, s + 1, K2, A, B, V);
  }
#pragma unroll 1
  for (int s = SIGMA;; s += 2) {
    conv_step<true, true>(c, s, K2, A, B, V);
    if (s == NSTEP - 2) break;
    conv_step<true, true>(c, s + 1, K1, V, B, A);
  }
  conv_step<true, false>(c, NSTEP - 1, K1, V, B, A);
#pragma unroll 1
  for (int r = NSTEP - SIGMA; r < NROUND - 1 + c.rank; r++) {
    NB_SYNC(NB_OPEN, 384);
    NB_ARRIVE(NB_CLOSE, 256);
  }
  NB_SYNC(NB_OPEN, 384);
}

__global__ void __cluster_dims__(2, 1, 1) __launch_bounds__(384, 1)
convnext_kernel(const __grid_constant__ CUtensorMap tm, const __nv_bfloat16* __restrict__ x, const __nv_bfloat16* __restrict__ dw,
                const __nv_bfloat16* __restrict__ w1, const __nv_bfloat16* __restrict__ w2, __nv_bfloat16* __restrict__ out,
                int zero) {
  extern __shared__ __align__(1024) uint8_t smem[];
  const uint32_t sb = (uint32_t)__cvta_generic_to_shared(smem);
  const int tid = threadIdx.x, lane = tid & 31;
  const int wid = __shfl_sync(0xffffffffu, tid >> 5, 0);
  const int rank = blockIdx.x & 1, cl = blockIdx.x >> 1;
  const int c0 = (cl & 15) * 32, r0 = (cl >> 4) * 128;
  const uint32_t peer_off = mapa(sb, rank ^ 1) - sb;

  TR(wid >> 2, 1002);
  TRG(1020);
  if (tid == 0) {
    for (int i = 0; i < 2; i++) mbar_init(sb + BAR_W + 8 * i, 1);
    asm volatile("fence.mbarrier_init.release.cluster;" ::: "memory");
    for (int i = 0; i < 2; i++) mbar_expect(sb + BAR_W + 8 * i, 73728);
    for (int i = 0; i < 4; i++) bulk_load(sb + OFF_W1 + i * 18432, reinterpret_cast<const uint8_t*>(w1) + i * 18432, 18432, sb + BAR_W);
    for (int i = 0; i < 4; i++) bulk_load(sb + OFF_W2 + i * 18432, reinterpret_cast<const uint8_t*>(w2) + i * 18432, 18432, sb + BAR_W + 8);
  }
  if (tid == 256) {
    for (int i = 0; i < 4; i++) mbar_init(sb + BAR_RAW + 8 * i, 1);
    asm volatile("fence.mbarrier_init.release.cluster;" ::: "memory");
    TR(2, 1006);
    for (int i = 0; i < 4; i++)
      tma_raw(sb + OFF_RAW + i * RAW_BYTES, &tm, 56 * rank - 8, c0 / 2 - 2, r0 - 3 + 2 * i, sb + BAR_RAW + 8 * i);
    TR(2, 1007);
  }
  if (tid == 128) {
    for (int i = 0; i < 2; i++) mbar_init(sb + BAR_CFULL + 8 * i, 1);
    for (int i = 0; i < 4; i++) mbar_init(sb + BAR_CEMPTY + 8 * i, 4);
    for (int i = 0; i < 8; i++) mbar_init(sb + BAR_XFULL + 8 * i, 1);
    for (int i = 0; i < 2; i++) mbar_expect(sb + BAR_CFULL + 8 * i, 12288);
    asm volatile("fence.mbarrier_init.release.cluster;" ::: "memory");
  }
  __syncthreads();
  asm volatile("barrier.cluster.arrive.relaxed.aligned;" ::: "memory");

  TR(wid >> 2, 1003);
  if (wid < 8) {
    MlpCtx m;
    m.sb = sb; m.wg = wid >> 2; m.warp = wid & 3; m.rank = rank; m.peer_off = peer_off; m.zero = zero;
    m.xsrc = reinterpret_cast<const uint8_t*>(x) + ((size_t)(r0 + 4 * m.wg + 2 * rank) * IMG + c0 + 8 * m.warp) * (CH * 2);
    m.optr = reinterpret_cast<uint8_t*>(out) + ((size_t)(r0 + 4 * m.wg + 2 * rank) * IMG + c0 + 8 * m.warp) * (CH * 2);
    m.caddr = sb + OFF_C + m.wg * C_BYTES + m.warp * 128 + (lane & 3) * (6 * 512 + 32) + (lane >> 2) * 16;
    m.xaddr = sb + OFF_XRES + wid * 3072 + ((lane >> 3) & 1) * 1536 + ((lane >> 4) * 4 + ((lane >> 2) & 1)) * 192 + (lane & 3) * 16;
    m.unscale = 0;
    asm volatile("setmaxnreg.dec.sync.aligned.u32 %0;" ::"n"(REG_MLP));
    const uint32_t bad = mlp_role(m);
    asm volatile("barrier.cluster.arrive.relaxed.aligned;\nbarrier.cluster.wait.aligned;" ::: "memory");
    if (bad) {
      asm volatile("fence.proxy.async;" ::: "memory");
      for (int i = 0; i < 16; i++)
        if (bad >> i & 1)
          slow_tile(x, dw, w1, w2, out, r0 + 8 * i + 4 * m.wg + 2 * rank, c0 + 8 * m.warp,
                    reinterpret_cast<float*>(smem + OFF_XRES + wid * 3072));
    }
  } else {
    ConvCtx c;
    c.sb = sb; c.rank = rank; c.v = wid - 8; c.c0 = c0; c.r0 = r0; c.zero = zero; c.tm = &tm;
    c.peer_off = peer_off;
    const int g = lane >> 2, t = lane & 3;
    c.a_raw = sb + OFF_RAW + ((t >> 1) * 19 + 2 * (g + (t & 1))) * 112 + (1 - rank) * 16 + 16 * c.v;
    const int q0 = 12 * rank + 3 * c.v;
    c.a_c = sb + OFF_C + q0 * 512 + (q0 / 6) * 32 + lane * 16;
    asm volatile("setmaxnreg.inc.sync.aligned.u32 %0;" ::"n"(REG_CONV));
    conv_role(c, dw);
    __syncwarp();
    asm volatile("barrier.cluster.arrive.relaxed.aligned;\nbarrier.cluster.wait.aligned;\nexit;" ::: "memory");
  }
}

typedef CUresult (*EncodeFn)(CUtensorMap*, CUtensorMapDataType, cuuint32_t, void*, const cuuint64_t*, const cuuint64_t*,
                             const cuuint32_t*, const cuuint32_t*, CUtensorMapInterleave, CUtensorMapSwizzle,
                             CUtensorMapL2promotion, CUtensorMapFloatOOBfill);

}

extern "C" void kernel_launch(void* const* d_in, const int* in_sizes, int n_in, void* d_out, int out_size) {
  const __nv_bfloat16* x = (const __nv_bfloat16*)d_in[0];
  const __nv_bfloat16* dw = (const __nv_bfloat16*)d_in[1];
  const __nv_bfloat16* w1 = (const __nv_bfloat16*)d_in[2];
  const __nv_bfloat16* w2 = (const __nv_bfloat16*)d_in[3];
  __nv_bfloat16* out = (__nv_bfloat16*)d_out;

  static EncodeFn encode = nullptr;
  if (!encode) {
    cudaDriverEntryPointQueryResult st;
    void* fn = nullptr;
    cudaGetDriverEntryPoint("cuTensorMapEncodeTiled", &fn, cudaEnableDefault, &st);
    encode = (EncodeFn)fn;
    cudaFuncSetAttribute(convnext_kernel, cudaFuncAttributeMaxDynamicSharedMemorySize, SMEM_BYTES);
  }
  CUtensorMap tm;
  cuuint64_t dims[4] = {CH, IMG / 2, IMG, 2};
  cuuint64_t strides[3] = {CH * 4, (cuuint64_t)IMG * CH * 2, CH * 2};
  cuuint32_t box[4] = {56, 19, 2, 1};
  cuuint32_t es[4] = {1, 1, 1, 1};
  encode(&tm, CU_TENSOR_MAP_DATA_TYPE_BFLOAT16, 4, (void*)x, dims, strides, box, es, CU_TENSOR_MAP_INTERLEAVE_NONE,
         CU_TENSOR_MAP_SWIZZLE_NONE, CU_TENSOR_MAP_L2_PROMOTION_L2_128B, CU_TENSOR_MAP_FLOAT_OOB_FILL_NONE);
  convnext_kernel<<<128, 384, SMEM_BYTES>>>(tm, x, dw, w1, w2, out, 0);
}
```

```cpp
#include <cuda_runtime.h>
#include <cuda_bf16.h>
#include <cuda.h>
#include <stdint.h>

namespace {

constexpr int IMG = 512, CH = 96;
constexpr int NSTEP = 67;
constexpr int SIGMA = 8;
constexpr int NROUND = 68;

constexpr uint32_t OFF_W1 = 0;
constexpr uint32_t OFF_W2 = 73728;
constexpr uint32_t OFF_RAW = 147456;
constexpr uint32_t RAW_PLANE = 4352;
constexpr uint32_t RAW_BYTES = 2 * RAW_PLANE;
constexpr uint32_t RAW_TX = 2 * 2 * 19 * 112;
constexpr uint32_t OFF_XRES = OFF_RAW + 4 * RAW_BYTES;
constexpr uint32_t OFF_C = OFF_XRES + 2 * 12288;
constexpr uint32_t C_BYTES = 12416;
constexpr uint32_t OFF_BAR = OFF_C + 2 * C_BYTES;
constexpr uint32_t BAR_RAW = OFF_BAR;
constexpr uint32_t BAR_CFULL = OFF_BAR + 32;
constexpr uint32_t BAR_CEMPTY = OFF_BAR + 48;
constexpr uint32_t BAR_XFULL = OFF_BAR + 80;
constexpr uint32_t BAR_W = OFF_BAR + 144;
constexpr uint32_t OFF_NRM = OFF_BAR + 160;
constexpr uint32_t OFF_LT = OFF_BAR + 160;
constexpr uint32_t SMEM_BYTES = OFF_BAR + 160 + 600;

constexpr float GELU_A = 0.32918364f;
constexpr uint32_t GELU_K2 = 0x40d940d9u;

constexpr int NB_CLOSE = 1, NB_SEC = 6  , NB_OPEN = 3, NB_PROD = 2, NB_PLAN = 4, NB_PREP = 5;
#define REG_MLP 144
constexpr int REG_CONV = 488 - 2 * REG_MLP;

#define WG_FENCE() asm volatile("wgmma.fence.sync.aligned;" ::: "memory")
#define WG_COMMIT() asm volatile("wgmma.commit_group.sync.aligned;" ::: "memory")
#define WG_WAIT0() asm volatile("wgmma.wait_group.sync.aligned 0;" ::: "memory")
#define WG_WAIT1() asm volatile("wgmma.wait_group.sync.aligned 1;" ::: "memory")
#define PIN() asm volatile("pmevent 0;" ::: "memory")
#define NB_SYNC(id, n) asm volatile("bar.sync %0, %1;" ::"n"(id), "n"(n) : "memory")
#define NB_ARRIVE(id, n) asm volatile("bar.arrive %0, %1;" ::"n"(id), "n"(n) : "memory")

#define TR(who, idx)
#define TRG(idx)

#define TL(base, off)
#define TLDUMP(cond, base, n)

#define R24(c, d)                                                                                        \
  c(d[0]), c(d[1]), c(d[2]), c(d[3]), c(d[4]), c(d[5]), c(d[6]), c(d[7]), c(d[8]), c(d[9]), c(d[10]),    \
      c(d[11]), c(d[12]), c(d[13]), c(d[14]), c(d[15]), c(d[16]), c(d[17]), c(d[18]), c(d[19]), c(d[20]), \
      c(d[21]), c(d[22]), c(d[23])
#define WG_TXT(sd)                                                                             \
  "wgmma.mma_async.sync.aligned.m64n96k16.f16.f16.f16 "                                        \
  "{%0,%1,%2,%3,%4,%5,%6,%7,%8,%9,%10,%11,%12,%13,%14,%15,%16,%17,%18,%19,%20,%21,%22,%23}, " \
  "{%24,%25,%26,%27}, %28, " sd ", 1, 1, 1;\n"

__device__ __forceinline__ void wg_acc(uint32_t (&d)[24], const uint32_t* a, uint64_t db) {
  asm volatile(WG_TXT("1") : R24("+r", d) : "r"(a[0]), "r"(a[1]), "r"(a[2]), "r"(a[3]), "l"(db));
}
__device__ __forceinline__ void wg_init(uint32_t (&d)[24], const uint32_t* a, uint64_t db) {
  asm volatile(WG_TXT("0") : R24("=r", d) : "r"(a[0]), "r"(a[1]), "r"(a[2]), "r"(a[3]), "l"(db));
}
template <int N>
__device__ __forceinline__ void rfence(uint32_t (&d)[N]) {
#pragma unroll
  for (int i = 0; i < N; i++) asm volatile("" : "+r"(d[i])::"memory");
}
template <bool INIT, int KSTRIDE>
__device__ __forceinline__ void gemm6(uint32_t (&d)[24], const uint32_t (&a)[24], uint64_t db) {
#pragma unroll
  for (int k = 0; k < 6; k++) {
    if (INIT && k == 0) wg_init(d, &a[0], db);
    else wg_acc(d, &a[4 * k], db + k * KSTRIDE);
  }
  WG_COMMIT();
}

__device__ __forceinline__ void mbar_init(uint32_t bar, uint32_t cnt) {
  asm volatile("mbarrier.init.shared::cta.b64 [%0], %1;" ::"r"(bar), "r"(cnt) : "memory");
}
__device__ __forceinline__ void mbar_expect(uint32_t bar, uint32_t bytes) {
  asm volatile("mbarrier.arrive.expect_tx.shared::cta.b64 _, [%0], %1;" ::"r"(bar), "r"(bytes) : "memory");
}
__device__ __forceinline__ void mbar_arrive_cluster(uint32_t bar) {
  asm volatile("mbarrier.arrive.shared::cluster.b64 _, [%0];" ::"r"(bar) : "memory");
}
__device__ __forceinline__ bool mbar_try(uint32_t bar, uint32_t parity) {
  uint32_t ok;
  asm volatile(
      "{\n.reg .pred p;\nmbarrier.try_wait.parity.shared::cta.b64 p, [%1], %2;\nselp.u32 %0, 1, 0, p;\n}\n"
      : "=r"(ok)
      : "r"(bar), "r"(parity)
      : "memory");
  return ok;
}
__device__ __forceinline__ bool mbar_test(uint32_t bar, uint32_t parity) {
  uint32_t ok;
  asm volatile(
      "{\n.reg .pred p;\nmbarrier.test_wait.parity.shared::cta.b64 p, [%1], %2;\nselp.u32 %0, 1, 0, p;\n}\n"
      : "=r"(ok)
      : "r"(bar), "r"(parity)
      : "memory");
  return ok;
}
__device__ __forceinline__ void mbar_wait(uint32_t bar, uint32_t parity) {
  if (__builtin_expect(mbar_try(bar, parity), 1)) return;
#pragma unroll 1
  for (uint32_t n = 0; n < (1u << 16) && !mbar_try(bar, parity); n++) {}
}
__device__ __forceinline__ uint32_t mapa(uint32_t addr, uint32_t rank) {
  uint32_t r;
  asm("mapa.shared::cluster.u32 %0, %1, %2;" : "=r"(r) : "r"(addr), "r"(rank));
  return r;
}
__device__ __forceinline__ void tma_raw(uint32_t dst, const CUtensorMap* tm, int c, int w2, int h, uint32_t bar) {
  mbar_expect(bar, RAW_TX);
#pragma unroll
  for (int e = 0; e < 2; e++)
    asm volatile(
        "cp.async.bulk.tensor.4d.shared::cluster.global.mbarrier::complete_tx::bytes [%0], [%1, {%2, %3, %4, %5}], [%6];"
        ::"r"(dst + e * RAW_PLANE), "l"(tm), "r"(c), "r"(w2 + e), "r"(h), "r"(1 - e), "r"(bar)
        : "memory");
}
__device__ __forceinline__ void bulk_load(uint32_t dst, const void* src, uint32_t bytes, uint32_t bar) {
  asm volatile("cp.async.bulk.shared::cluster.global.mbarrier::complete_tx::bytes [%0], [%1], %2, [%3];" ::"r"(dst),
               "l"(src), "r"(bytes), "r"(bar)
               : "memory");
}
__device__ __forceinline__ uint32_t pack_bf16(float lo, float hi) {
  uint32_t r;
  asm("cvt.rn.bf16x2.f32 %0, %1, %2;" : "=r"(r) : "f"(hi), "f"(lo));
  return r;
}
__device__ __forceinline__ uint32_t pack_f16(float lo, float hi) {
  uint32_t r;
  asm("cvt.rn.f16x2.f32 %0, %1, %2;" : "=r"(r) : "f"(hi), "f"(lo));
  return r;
}
__device__ __forceinline__ float bf_lo(uint32_t v) { return __uint_as_float(v << 16); }
__device__ __forceinline__ float bf_hi(uint32_t v) { return __uint_as_float(v & 0xffff0000u); }
__device__ __forceinline__ uint32_t bf_add(uint32_t a, uint32_t b) {
  uint32_t r;
  asm("add.rn.bf16x2 %0, %1, %2;" : "=r"(r) : "r"(a), "r"(b));
  return r;
}
__device__ __forceinline__ uint32_t bf_mul(uint32_t a, uint32_t b) {
  uint32_t r;
  asm("mul.rn.bf16x2 %0, %1, %2;" : "=r"(r) : "r"(a), "r"(b));
  return r;
}
__device__ __forceinline__ uint32_t bf_fma(uint32_t a, uint32_t b, uint32_t c) {
  uint32_t r;
  asm("fma.rn.bf16x2 %0, %1, %2, %3;" : "=r"(r) : "r"(a), "r"(b), "r"(c));
  return r;
}

__device__ __forceinline__ uint32_t h_add(uint32_t a, uint32_t b) {
  uint32_t r;
  asm("add.rn.f16x2 %0, %1, %2;" : "=r"(r) : "r"(a), "r"(b));
  return r;
}
__device__ __forceinline__ uint32_t h_mul(uint32_t a, uint32_t b) {
  uint32_t r;
  asm("mul.rn.f16x2 %0, %1, %2;" : "=r"(r) : "r"(a), "r"(b));
  return r;
}
__device__ __forceinline__ uint32_t h_fma(uint32_t a, uint32_t b, uint32_t c) {
  uint32_t r;
  asm("fma.rn.f16x2 %0, %1, %2, %3;" : "=r"(r) : "r"(a), "r"(b), "r"(c));
  return r;
}
__device__ __forceinline__ float h_sum(uint32_t v) {
  float lo, hi;
  asm("{\n.reg .b16 l, h;\nmov.b32 {l, h}, %2;\ncvt.f32.f16 %0, l;\ncvt.f32.f16 %1, h;\n}\n" : "=f"(lo), "=f"(hi) : "r"(v));
  return lo + hi;
}
__device__ __forceinline__ void lds128(uint32_t (&v)[4], uint32_t a) {
  asm volatile("ld.shared.v4.b32 {%0,%1,%2,%3}, [%4];" : "=r"(v[0]), "=r"(v[1]), "=r"(v[2]), "=r"(v[3]) : "r"(a) : "memory");
}

template <int LO, int HI>
__device__ __forceinline__ void gelu(uint32_t (&o)[24], const uint32_t (&d)[24]) {
#pragma unroll
  for (int qq = LO; qq < HI; qq++) {
    const int q = (qq + 4) % 24;
    uint32_t t, u;
    asm("fma.rn.f16x2 %0, %1, %1, %2;" : "=r"(t) : "r"(d[q]), "r"(GELU_K2));
    asm("mul.rn.f16x2 %0, %1, %2;" : "=r"(u) : "r"(d[q]), "r"(t));
    asm("tanh.approx.f16x2 %0, %1;" : "=r"(t) : "r"(u));
    asm("fma.rn.f16x2 %0, %1, %2, %1;" : "=r"(o[q]) : "r"(d[q]), "r"(t));
  }
}

__device__ __forceinline__ uint32_t laneid() {
  uint32_t l;
  asm volatile("mov.u32 %0, %%laneid;" : "=r"(l));
  return l;
}

__device__ __forceinline__ bool elect_one() {
  uint32_t p;
  asm volatile("{\n.reg .pred p;\nelect.sync _|p, 0xffffffff;\nselp.u32 %0, 1, 0, p;\n}\n" : "=r"(p));
  return p;
}

__device__ __forceinline__ uint32_t clock_pin() {
  uint32_t t;
  asm volatile("mov.u32 %0, %%clock;" : "=r"(t)::"memory");
  return t;
}

struct MlpCtx {
  uint32_t sb;
  uint32_t caddr;
  uint32_t xaddr;
  uint32_t unscale;
  uint32_t peer_off;
  int wg, warp, rank, zero;
  uint8_t* optr;
};

__device__ __forceinline__ void ln_wait(const MlpCtx& m, int i) { mbar_wait(m.sb + BAR_CFULL + 8 * m.wg, i & 1); }
__device__ __forceinline__ void ln_load(const MlpCtx& m, uint32_t (&c)[24]) {
#pragma unroll
  for (int p = 0; p < 6; p++)
    asm volatile("ld.shared.v4.b32 {%0,%1,%2,%3}, [%4];"
                 : "=r"(c[4 * p]), "=r"(c[4 * p + 1]), "=r"(c[4 * p + 2]), "=r"(c[4 * p + 3])
                 : "r"(m.caddr + p * 512)
                 : "memory");
}
__device__ __forceinline__ void ln_shfl(float (&st)[8], int mask) {
#pragma unroll
  for (int k = 0; k < 4; k++) st[4 + k] = __shfl_xor_sync(0xffffffffu, st[k], mask);
}
__device__ __forceinline__ void ln_fold(float (&st)[8]) {
#pragma unroll
  for (int k = 0; k < 4; k++) st[k] += st[4 + k];
}
__device__ __forceinline__ void ln_sums(const uint32_t (&c)[24], float (&st)[8]) {
#pragma unroll
  for (int r = 0; r < 2; r++) {
    uint32_t s0 = h_add(c[r], c[r + 2]), s1 = h_add(c[r + 4], c[r + 6]), s2 = h_add(c[r + 8], c[r + 10]);
    uint32_t s3 = h_add(c[r + 12], c[r + 14]), s4 = h_add(c[r + 16], c[r + 18]), s5 = h_add(c[r + 20], c[r + 22]);
    s0 = h_add(s0, s1); s2 = h_add(s2, s3); s4 = h_add(s4, s5);
    st[r] = h_sum(h_add(h_add(s0, s2), s4));
    uint32_t q0 = h_mul(c[r], c[r]), q1 = h_mul(c[r + 2], c[r + 2]);
#pragma unroll
    for (int p = 2; p < 12; p += 2) {
      q0 = h_fma(c[2 * p + r], c[2 * p + r], q0);
      q1 = h_fma(c[2 * p + 2 + r], c[2 * p + 2 + r], q1);
    }
    st[2 + r] = h_sum(h_add(q0, q1));
  }
}
__device__ __forceinline__ void ln_release(const MlpCtx& m) {
  const uint32_t e = m.sb + BAR_CEMPTY + 8 * (2 * m.rank + m.wg);
  asm volatile(
      "{\n.reg .pred p, q;\nelect.sync _|p, 0xffffffff;\nsetp.eq.and.s32 q, %3, 0, p;\n"
      "@q mbarrier.arrive.expect_tx.shared::cta.b64 _, [%0], 12288;\n"
      "@p mbarrier.arrive.shared::cluster.b64 _, [%1];\n"
      "@p mbarrier.arrive.shared::cluster.b64 _, [%2];\n}\n" ::"r"(m.sb + BAR_CFULL + 8 * m.wg),
      "r"(e), "r"(e + m.peer_off), "r"(m.warp)
      : "memory");
}
__device__ __forceinline__ void ln_stats(float (&st)[8], uint32_t& bad, uint32_t bit) {
  bool ok = true;
#pragma unroll
  for (int r = 0; r < 2; r++) {
    const float nm = (st[r] + st[4 + r]) * (-1.0f / 96.0f);
    const float e2 = fmaf(st[2 + r] + st[6 + r], 1.0f / 96.0f, 1e-5f);
    float rs;
    asm("rsqrt.approx.ftz.f32 %0, %1;" : "=f"(rs) : "f"(fmaf(-nm, nm, e2)));
    ok = ok && (rs * rs * e2 <= 17.0f) && (e2 >= 1.001e-5f);
    const float rr = rs * GELU_A, dd = rr * nm;
    st[r] = __uint_as_float(pack_f16(rr, rr));
    st[2 + r] = __uint_as_float(pack_f16(dd, dd));
  }
  if (!ok) bad |= bit;
}
__device__ __forceinline__ void ln_apply(uint32_t (&a)[24], const uint32_t (&c)[24], const float (&st)[8]) {
#pragma unroll
  for (int p = 0; p < 24; p++) a[p] = h_fma(c[p], __float_as_uint(st[p & 1]), __float_as_uint(st[2 + (p & 1)]));
}

__device__ __noinline__ void slow_tile(const __nv_bfloat16* x, const __nv_bfloat16* dw, const __nv_bfloat16* w1,
                                       const __nv_bfloat16* w2, __nv_bfloat16* out, int row0, int col0, float* buf) {
  const int lane = threadIdx.x & 31;
  for (int px = 0; px < 16; px++) {
    const int row = row0 + (px >> 3), col = col0 + (px & 7);
    float c[3] = {0.f, 0.f, 0.f};
    for (int i = 0; i < 7; i++)
      for (int j = 0; j < 7; j++) {
        const int rr = row + i - 3, cc = col + j - 3;
        if (rr < 0 || rr >= IMG || cc < 0 || cc >= IMG) continue;
        for (int k = 0; k < 3; k++)
          c[k] = fmaf(__bfloat162float(x[((size_t)rr * IMG + cc) * CH + lane + 32 * k]), __bfloat162float(dw[(i * 7 + j) * CH + lane + 32 * k]), c[k]);
      }
    float mean = (c[0] + c[1] + c[2]) * (1.0f / 96.0f);
    for (int o = 16; o; o >>= 1) mean += __shfl_xor_sync(0xffffffffu, mean, o);
    float var = 0.f;
    for (int k = 0; k < 3; k++) { c[k] -= mean; var = fmaf(c[k] * (1.0f / 96.0f), c[k], var); }
    for (int o = 16; o; o >>= 1) var += __shfl_xor_sync(0xffffffffu, var, o);
    const float rs = 1.0f / sqrtf(var + 1e-5f);
    __syncwarp();
    for (int k = 0; k < 3; k++) buf[lane + 32 * k] = c[k] * rs;
    __syncwarp();
    for (int n = lane; n < 4 * CH; n += 32) {
      float y = 0.f;
      for (int k = 0; k < CH; k++) y = fmaf(buf[k], __bfloat162float(w1[k * 4 * CH + n]), y);
      buf[CH + n] = 0.5f * y * (1.0f + tanhf(0.7978845608f * (y + 0.044715f * y * y * y)));
    }
    __syncwarp();
    for (int n = lane; n < CH; n += 32) {
      float o = 0.f;
      for (int k = 0; k < 4 * CH; k++) o = fmaf(buf[CH + k], __bfloat162float(w2[k * CH + n]), o);
      const size_t idx = ((size_t)row * IMG + col) * CH + n;
      out[idx] = __float2bfloat16(__bfloat162float(x[idx]) + o);
    }
  }
}

__device__ __forceinline__ void x_load(const MlpCtx& m, uint32_t (&x)[24]) {
#pragma unroll
  for (int k = 0; k < 6; k++)
    asm volatile("ld.shared.v4.b32 {%0,%1,%2,%3}, [%4];"
                 : "=r"(x[4 * k]), "=r"(x[4 * k + 1]), "=r"(x[4 * k + 2]), "=r"(x[4 * k + 3])
                 : "r"(m.xaddr + (k / 3) * 384 + (k % 3) * 64)
                 : "memory");
}
template <int LO, int HI>
__device__ __forceinline__ void epilogue(const MlpCtx& m, const uint32_t (&d)[24], uint32_t (&x)[24]) {
#pragma unroll
  for (int k = LO; k < HI; k++) {
    const int r = k / 3, q = k % 3;
    uint32_t* y = &x[4 * k];
#pragma unroll
    for (int j = 0; j < 4; j++) {
      uint32_t v = d[2 * (4 * q + j) + r];
      float lo, hi;
      asm("{\n.reg .b16 l, h;\nmov.b32 {l, h}, %2;\ncvt.f32.f16 %0, l;\ncvt.f32.f16 %1, h;\n}\n" : "=f"(lo), "=f"(hi) : "r"(v));
      asm("fma.rn.bf16x2 %0, %1, %2, %0;" : "+r"(y[j]) : "r"(pack_bf16(lo, hi)), "r"(m.unscale));
    }
    asm volatile("st.shared.v4.b32 [%0], {%1,%2,%3,%4};" ::"r"(m.xaddr + r * 384 + q * 64), "r"(y[0]), "r"(y[1]), "r"(y[2]), "r"(y[3])
                 : "memory");
  }
}
__device__ __forceinline__ void out_store(const MlpCtx& m, int i) {
  asm volatile("fence.proxy.async.shared::cta;" ::: "memory");
  __syncwarp();
  if (elect_one()) {
    const uint32_t src = m.sb + OFF_XRES + m.wg * 12288 + m.warp * 1536;
    uint8_t* dst = m.optr + (size_t)i * (8 * IMG * CH * 2);
    asm volatile("cp.async.bulk.global.shared::cta.bulk_group [%0], [%1], 1536;" ::"l"(dst), "r"(src) : "memory");
    asm volatile("cp.async.bulk.global.shared::cta.bulk_group [%0], [%1], 1536;" ::"l"(dst + IMG * CH * 2), "r"(src + 6144) : "memory");
    asm volatile("cp.async.bulk.commit_group;" ::: "memory");
  }
}

template <int J> __device__ __forceinline__ void tok_wait() {
  if (J == 0 || J == 3) NB_SYNC(NB_CLOSE, 256);
  else NB_SYNC(NB_SEC + (J & 1), 256);
}
template <int J> __device__ __forceinline__ void tok_next() {
  if (J == 0 || J == 3) { NB_ARRIVE(NB_SEC + (J & 1), 256); NB_ARRIVE(NB_PROD, 160); }
}
__device__ __forceinline__ void tok_pass() { NB_ARRIVE(NB_OPEN, 416); }
template <int J> __device__ __forceinline__ void tok_idle() { tok_wait<J>(); tok_next<J>(); tok_pass(); }

constexpr uint64_t CHK = 1152;

__device__ __forceinline__ void sumsq(const uint32_t (&v)[18][4], uint32_t dst) {
  uint32_t q[4] = {0, 0, 0, 0};
#pragma unroll
  for (int it = 0; it < 18; it++)
#pragma unroll
    for (int t = 0; t < 4; t++) q[t] = bf_fma(v[it][t], v[it][t], q[t]);
  q[0] = bf_add(bf_add(q[0], q[1]), bf_add(q[2], q[3]));
  float f = bf_lo(q[0]) + bf_hi(q[0]);
#pragma unroll
  for (int o = 16; o; o >>= 1) f += __shfl_xor_sync(0xffffffffu, f, o);
  if ((threadIdx.x & 31) == 0) asm volatile("st.shared.f32 [%0], %1;" ::"r"(dst), "f"(f) : "memory");
}

__device__ __forceinline__ uint32_t mlp_role(const MlpCtx& m0) {
  MlpCtx m = m0;
  uint32_t bad = 0;
  const int lane = threadIdx.x & 31, wid = m.wg * 4 + m.warp;
  {
    uint32_t v[18][4];
    const int k7 = lane & 7;
    {
      mbar_wait(m.sb + BAR_W, 0);
#pragma unroll
      for (int it = 0; it < 18; it++) {
        const int kb = (it / 3) * 2 + (wid & 1), ks = it / 3;
        const int Q = 6 * (k7 >> 1) + ks, q12 = Q % 12, cv = q12 / 3, e = q12 % 3;
        const int ch = 48 * (Q / 12) + (e < 2 ? 8 * cv + 4 * e : 32 + 4 * cv) + 2 * (kb & 1) + (k7 & 1);
        const int n8 = (it % 3) * 16 + ((wid >> 2) * 8 + ((((wid >> 1) & 1) * 4 + (lane >> 3) + k7) & 7));
        lds128(v[it], m.sb + OFF_W1 + ch * 768 + n8 * 16);
      }
      sumsq(v, m.sb + OFF_NRM + 4 * wid);
      NB_SYNC(NB_PREP, 256);
#pragma unroll
      for (int it = 0; it < 18; it++) {
        const int n8 = (it % 3) * 16 + ((wid >> 2) * 8 + ((((wid >> 1) & 1) * 4 + (lane >> 3) + k7) & 7));
        const uint32_t dst = m.sb + OFF_W1 + (it / 3) * 12288 + n8 * 256 + (wid & 1) * 128 + k7 * 16;
        asm volatile("st.shared.v4.b32 [%0], {%1,%2,%3,%4};" ::"r"(dst), "r"(pack_f16(bf_lo(v[it][0]), bf_hi(v[it][0]))),
                     "r"(pack_f16(bf_lo(v[it][1]), bf_hi(v[it][1]))), "r"(pack_f16(bf_lo(v[it][2]), bf_hi(v[it][2]))),
                     "r"(pack_f16(bf_lo(v[it][3]), bf_hi(v[it][3])))
                     : "memory");
      }
    }
    TR(m.wg, 1004);
    {
      mbar_wait(m.sb + BAR_W + 8, 0);
      const uint32_t base = m.sb + OFF_W2 + wid * 9216;
#pragma unroll
      for (int it = 0; it < 18; it++) lds128(v[it], base + (lane >> 2) * 192 + (lane & 3) * 16 + (it / 3) * 1536 + (it % 3) * 64);
      sumsq(v, m.sb + OFF_NRM + 32 + 4 * wid);
      TR(m.wg, 1005);
      NB_SYNC(NB_PREP, 256);
      int e[2];
#pragma unroll
      for (int k = 0; k < 2; k++) {
        uint32_t a[4], b[4];
        lds128(a, m.sb + OFF_NRM + 32 * k);
        lds128(b, m.sb + OFF_NRM + 32 * k + 16);
        float f = 0.f;
#pragma unroll
        for (int t = 0; t < 4; t++) f += __uint_as_float(a[t]) + __uint_as_float(b[t]);
        e[k] = (((int)(__float_as_uint(f * 1.5f) >> 23) - 127) >> 1) + 1;
      }
      const int s = min(11 - e[0] - e[1], 14 - e[1]);
      if (e[0] > 12 || e[0] < -5 || e[1] > 60 || e[1] < -60) bad = 0xffffu;
      const float sc = __uint_as_float((uint32_t)(127 + s) << 23) * (0.5f / GELU_A);
      m.unscale = __shfl_sync(0xffffffffu, ((uint32_t)(127 - s) << 7) * 0x10001u, 0);
#pragma unroll
      for (int it = 0; it < 18; it++)
#pragma unroll
        for (int j = 0; j < 4; j++)
          asm volatile("st.shared.b32 [%0], %1;" ::"r"(base + lane * 4 + (it / 6) * 3072 + ((it / 3) & 1) * 128 + ((it % 3) * 4 + j) * 256),
                       "r"(pack_f16(bf_lo(v[it][j]) * sc, bf_hi(v[it][j]) * sc))
                       : "memory");
    }
    asm volatile("fence.proxy.async.shared::cta;" ::: "memory");
    NB_SYNC(NB_PREP, 256);
  }
  asm volatile("barrier.cluster.wait.aligned;" ::: "memory");
  const uint64_t dW1 = (uint64_t)(((m.sb + OFF_W1) & 0x3FFFF) >> 4) | ((uint64_t)8 << 16) | ((uint64_t)16 << 32);
  const uint64_t dW2 = dW1 + (OFF_W2 >> 4);

  TR(m.wg, 1000);
  uint32_t A1[24], g[24], d[24], cn[24], D2[24];
  float st[8];
  ln_wait(m, 0);
  ln_load(m, cn);
  ln_sums(cn, st);
  ln_shfl(st, 1);
  ln_release(m);
  ln_fold(st);
  ln_shfl(st, 2);
  ln_stats(st, bad, 1);
  ln_apply(A1, cn, st);
  [[maybe_unused]] int rho = 2 * m.wg + m.rank + 2;
  if (m.wg & m.rank) tok_idle<3>();
  if (m.wg) tok_idle<0>();
  if (m.wg | m.rank) tok_idle<1>();
  {
    uint32_t d0[24];
    WG_FENCE();
    tok_wait<2>();
    gemm6<true, 768>(d0, A1, dW1);
    tok_pass(); PIN();
    WG_WAIT0(); rfence(d0);
    WG_FENCE();
    tok_wait<3>();
    tok_next<3>();
    gemm6<true, 768>(d, A1, dW1 + 192);
    tok_pass(); PIN();
    gelu<0, 24>(g, d0);
    PIN();
    ln_wait(m, 1);
    ln_load(m, cn);
    PIN();
    WG_WAIT0(); rfence(d);
  }
#define G2(INIT, a, j)                      \
  WG_FENCE();                               \
  tok_wait<j>();                            \
  TR(m.wg, rho * 8);                        \
  gemm6<INIT, 192>(D2, a, dW2 + (j) * CHK); \
  tok_next<j>(); PIN();                     \
  TL(ltb, (j) * 5 + 1);                     \
  TR(m.wg, rho * 8 + 1);
#define G1(dst, j, P)                       \
  TR(m.wg, rho * 8 + 2);                    \
  TL(ltb, ((j) ^ 2) * 5 + 2);               \
  P(); WG_WAIT0(); rfence(D2);              \
  WG_FENCE();                               \
  gemm6<true, 768>(dst, A1, dW1 + (j) * 192); \
  tok_pass(); P();                          \
  TL(ltb, ((j) ^ 2) * 5 + 3);               \
  TR(m.wg, rho * 8 + 3);
#define ROUND_END(dst, j)                   \
  TR(m.wg, rho * 8 + 4);                    \
  TL(ltb, (j) * 5 + 4);                     \
  PIN(); WG_WAIT0(); rfence(dst); rho++;
#define GA 10
#define GB 12
#define GC 12
#define GD 10
#pragma unroll 1
  for (int i = 0;; i++) {
    uint32_t g1[24], d2[24], g2[24], d3[24], g3[24], d0[24];
    G2(true, g, 0)
    gelu<0, GA>(g1, d);
    G1(d2, 2, PIN)
    ln_sums(cn, st);
    gelu<GA, 24>(g1, d);
    PIN();
    ln_shfl(st, 1);
    ROUND_END(d2, 0)

    G2(false, g1, 1)
    ln_fold(st);
    gelu<0, GB>(g2, d2);
    PIN();
    ln_shfl(st, 2);
    G1(d3, 3, PIN)
    ln_stats(st, bad, 2u << i);
    gelu<GB, 24>(g2, d2);
    ROUND_END(d3, 1)

    if (i == 15) {
      G2(false, g2, 2)
      tok_pass();
      gelu<0, 24>(g3, d3);
      PIN();
      x_load(m, cn);
      ROUND_END(D2, 2)
      G2(false, g3, 3)
      tok_pass();
      WG_WAIT0(); rfence(D2);
      epilogue<0, 6>(m, D2, cn);
      break;
    }
    G2(false, g2, 2)
    ln_apply(A1, cn, st);
    PIN();
    gelu<0, GC>(g3, d3);
    G1(d0, 0, PIN)
    gelu<GC, 24>(g3, d3);
    PIN();
    x_load(m, cn);
    ROUND_END(d0, 2)

    G2(false, g3, 3)
    gelu<0, GD>(g, d0);
    G1(d, 1, PIN)
    epilogue<0, 6>(m, D2, cn);
    gelu<GD, 24>(g, d0);
    PIN();
    asm volatile("fence.proxy.async.shared::cta;" ::: "memory");
    ln_load(m, cn);
    ROUND_END(d, 3)
    TLDUMP(m.warp == 0 && (i >> 1) == LTRACE, m.sb + OFF_LT + m.wg * 160 + (i & 1) * 80, 20)
  }
  out_store(m, 15);
  if (m.wg == 0) { tok_idle<0>(); tok_idle<1>(); }
  asm volatile("cp.async.bulk.wait_group 0;" ::: "memory");
  TR(m.wg, 1001);
  TRG(1021);
  return __reduce_or_sync(0xffffffffu, bad & 0xffffu);
}

struct ConvCtx {
  uint32_t sb;
  uint32_t a_raw, a_c;
  uint32_t peer_off;
  int rank, v, c0, r0, zero;
  const CUtensorMap* tm;
  const uint8_t* xsrc;
  uint8_t* optr;
};

__device__ __forceinline__ void raw_refill(const ConvCtx& c, int s) {
  if (s + 4 < NSTEP)
    tma_raw(c.sb + OFF_RAW + (s & 3) * RAW_BYTES, c.tm, 56 * c.rank - 8, c.c0 / 2 - 2, c.r0 - 3 + 2 * (s + 4), c.sb + BAR_RAW + 8 * (s & 3));
}
__device__ __forceinline__ void step_ready(const ConvCtx& c, int s) {
  const int nx = (s + 1) & 3, par = ((s + 1) >> 2) & 1;
  if (s + 1 < NSTEP) mbar_wait(c.sb + BAR_RAW + 8 * nx, par);
  if (s >= 7 && s < NSTEP) mbar_wait(c.sb + BAR_CEMPTY + 8 * (2 * (nx & 1) + (nx >> 1)), par);
}

__device__ __forceinline__ void prod_role(const ConvCtx& c) {
  asm volatile("barrier.cluster.wait.aligned;" ::: "memory");
  const bool lead = (threadIdx.x & 31) == 0;
#pragma unroll 1
  for (int r = -c.rank; r < NROUND; r++) {
    const int n = r >> 1, s = r + c.rank + SIGMA;
    const uint32_t w = (n + 1) & 1;
    const uint32_t buf = c.sb + OFF_XRES + w * 12288;
    NB_SYNC(NB_PROD, 160);
    if (lead) {
      if (s > SIGMA) raw_refill(c, s - 1);
      if (!(r & 1)) {
        if (n >= 1 && n < 29) {
          const uint32_t e = c.sb + BAR_CEMPTY + 8 * (2 * c.rank + w);
          mbar_expect(c.sb + BAR_CFULL + 8 * w, 12288);
          asm volatile("mbarrier.arrive.shared::cluster.b64 _, [%0], 4;" ::"r"(e) : "memory");
          asm volatile("mbarrier.arrive.shared::cluster.b64 _, [%0], 4;" ::"r"(e + c.peer_off) : "memory");
        }
        if (n >= 3 && n < 33) {
          uint8_t* dst = c.optr + (size_t)(n - 3) * (4 * IMG * CH * 2);
          asm volatile("cp.async.bulk.global.shared::cta.bulk_group [%0], [%1], 6144;" ::"l"(dst), "r"(buf) : "memory");
          asm volatile("cp.async.bulk.global.shared::cta.bulk_group [%0], [%1], 6144;" ::"l"(dst + IMG * CH * 2), "r"(buf + 6144) : "memory");
          asm volatile("cp.async.bulk.commit_group;" ::: "memory");
        }
      }
    }
    __syncwarp();
    step_ready(c, s);
    const int u = (r & 1) ? n - 1 : n + 2;
    if (u >= ((r & 1) ? 0 : 4) && u < 32) mbar_wait(c.sb + ((r & 1) ? BAR_XFULL : BAR_CFULL) + 8 * (u & 1), (u >> 1) & 1);
    NB_ARRIVE(NB_OPEN, 416);
    if (lead && !(r & 1) && n >= 1 && n < 33) {
      const uint8_t* src = c.xsrc + (size_t)(n - 1) * (4 * IMG * CH * 2);
      asm volatile("cp.async.bulk.wait_group.read 0;" ::: "memory");
      mbar_expect(c.sb + BAR_XFULL + 8 * w, 12288);
      bulk_load(buf, src, 6144, c.sb + BAR_XFULL + 8 * w);
      bulk_load(buf + 6144, src + IMG * CH * 2, 6144, c.sb + BAR_XFULL + 8 * w);
    }
    __syncwarp();
  }
  asm volatile("cp.async.bulk.wait_group 0;" ::: "memory");
}

__device__ __forceinline__ void conv_ld8(uint32_t a, uint32_t (&r)[6][6]) {
#pragma unroll
  for (int j = 0; j < 6; j++)
    asm volatile("ld.shared.v4.b32 {%0,%1,%2,%3}, [%4];"
                 : "=r"(r[j][0]), "=r"(r[j][1]), "=r"(r[j][2]), "=r"(r[j][3])
                 : "r"(a + (j >> 1) * 112 + (j & 1) * RAW_PLANE)
                 : "memory");
}
__device__ __forceinline__ void conv_ld4(uint32_t a, uint32_t (&r)[6][6]) {
#pragma unroll
  for (int j = 0; j < 6; j++)
    asm volatile("ld.shared.v2.b32 {%0,%1}, [%2];" : "=r"(r[j][4]), "=r"(r[j][5]) : "r"(a + (j >> 1) * 112 + (j & 1) * RAW_PLANE) : "memory");
}
__device__ __forceinline__ void conv_frags(uint32_t zero, const uint32_t (&r)[6][6], uint32_t (&A)[12][4]) {
#pragma unroll
  for (int ch = 0; ch < 12; ch++) {
    const uint32_t sel = (ch & 1) ? 0x7632 : 0x5410;
    A[ch][0] = __byte_perm(r[0][ch >> 1], r[1][ch >> 1], sel);
    A[ch][1] = __byte_perm(r[2][ch >> 1], r[3][ch >> 1], sel);
    A[ch][2] = A[ch][1] ^ zero;
    A[ch][3] = __byte_perm(r[4][ch >> 1], r[5][ch >> 1], sel);
  }
}
__device__ __forceinline__ void hmma_acc(uint32_t (&v)[4], const uint32_t (&a)[4], const uint32_t* b) {
  asm volatile("mma.sync.aligned.m16n8k16.row.col.f32.bf16.bf16.f32 {%0,%1,%2,%3}, {%4,%5,%6,%7}, {%8,%9}, {%0,%1,%2,%3};"
               : "+r"(v[0]), "+r"(v[1]), "+r"(v[2]), "+r"(v[3])
               : "r"(a[0]), "r"(a[1]), "r"(a[2]), "r"(a[3]), "r"(b[0]), "r"(b[1]));
}
__device__ __forceinline__ void hmma_new(uint32_t (&a)[4], const uint32_t* b) {
  asm volatile("mma.sync.aligned.m16n8k16.row.col.f32.bf16.bf16.f32 {%0,%1,%2,%3}, {%0,%1,%2,%3}, {%4,%5}, {%6,%6,%6,%6};"
               : "+r"(a[0]), "+r"(a[1]), "+r"(a[2]), "+r"(a[3])
               : "r"(b[0]), "r"(b[1]), "f"(0.f));
}

#define PRE 4
template <bool GATED, bool MORE>
__device__ __forceinline__ void conv_step(const ConvCtx& c, int s, uint32_t (&K)[12], uint32_t (&V)[12][4], const uint32_t (&B)[12][4],
                                          uint32_t (&A)[12][4]) {
  const int nx = (s + 1) & 3;
  uint32_t r[6][6];
  TL(ltb, 0);
  TR(2, s * 8);
  PIN();
  if (GATED) {
    NB_SYNC(NB_OPEN, 416);
  } else {
    step_ready(c, s);
    NB_SYNC(NB_PLAN, 128);
    if (c.v == (s & 3) && elect_one()) raw_refill(c, s);
  }
  if (MORE && (PRE & 8)) conv_ld8(c.a_raw + nx * RAW_BYTES, r);
  if (MORE && (PRE & 4)) conv_ld4(c.a_raw + nx * RAW_BYTES + 64 - 8 * c.v, r);
  PIN();
  TL(ltb, 1);
  TR(2, s * 8 + 1);
#pragma unroll
  for (int ch = 0; ch < 12; ch++) {
    hmma_acc(V[ch], A[ch], &B[ch][2]);
    hmma_new(A[ch], &B[ch][0]);
  }
  const uint32_t z1 = clock_pin();
  if (GATED) NB_ARRIVE(NB_CLOSE, 256);
  PIN();
  TL(ltb, 2);
  TR(2, s * 8 + 2);
#pragma unroll
  for (int q = 0; q < 12; q++) {
    const int ch = q & ~1, h = 2 * (q & 1);
    asm("add.rn.f16x2 %0, %0, %1;" : "+r"(K[q]) : "r"(pack_f16(__uint_as_float(V[ch][h + 1]), __uint_as_float(V[ch + 1][h]))));
  }
  if (GATED || s >= 3) {
    const uint32_t off = ((nx & 1) == c.rank) ? 0u : c.peer_off;
    const uint32_t dst = c.a_c + off + (nx >> 1) * C_BYTES, bar = c.sb + off + BAR_CFULL + 8 * (nx >> 1);
#pragma unroll
    for (int q = 0; q < 3; q++)
      asm volatile("st.async.weak.shared::cluster.mbarrier::complete_tx::bytes.v4.b32 [%0], {%1,%2,%3,%4}, [%5];" ::"r"(dst + q * 512),
                   "r"(K[4 * q]), "r"(K[4 * q + 1]), "r"(K[4 * q + 2]), "r"(K[4 * q + 3]), "r"(bar)
                   : "memory");
  }
  PIN();
#pragma unroll
  for (int q = 0; q < 12; q++) {
    const int ch = q & ~1, h = 2 * (q & 1);
    K[q] = pack_f16(__uint_as_float(V[ch][h]), __uint_as_float(V[ch + 1][h + 1]));
  }
  rfence(K);
  PIN();
  if (MORE && !(PRE & 8)) conv_ld8(c.a_raw + nx * RAW_BYTES, r);
  if (MORE && !(PRE & 4)) conv_ld4(c.a_raw + nx * RAW_BYTES + 64 - 8 * c.v, r);
  TR(2, s * 8 + 3);
  if (MORE) {
    conv_frags(c.zero & z1, r, V);
#pragma unroll
    for (int ch = 0; ch < 12; ch++) rfence(V[ch]);
  }
  PIN();
  TL(ltb, 4);
  TR(2, s * 8 + 4);
  TLDUMP(c.v == 0 && lr >= 0 && lr < 10, c.sb + OFF_LT + 320 + lr * 20, 5)
}

__device__ __forceinline__ void conv_role(const ConvCtx& c, const __nv_bfloat16* dw) {
  const int lane = threadIdx.x & 31, g = lane >> 2, t = lane & 3;
  uint32_t B[12][4];
  {
    const int dc = (g >> 1) & 1, ro = g >> 2, rk = t >> 1;
    const uint8_t* dwp = reinterpret_cast<const uint8_t*>(dw) + 96 * c.rank;
#pragma unroll
    for (int pb = 0; pb < 4; pb++) {
      const int par = pb >> 1, b = pb & 1;
      const int i = 2 * (2 * ((g ^ par) & 1) + b) + rk - ro;
      uint32_t w[4][6];
#pragma unroll
      for (int k = 0; k < 4; k++) {
        const int j = 4 * (t & 1) + k - dc;
        const bool ok = i >= 0 && i < 7 && j >= 0 && j < 7;
        uint4 w8 = make_uint4(0, 0, 0, 0);
        uint2 w4 = make_uint2(0, 0);
        if (ok) {
          w8 = __ldg(reinterpret_cast<const uint4*>(dwp + (i * 7 + j) * 192 + 16 * c.v));
          w4 = __ldg(reinterpret_cast<const uint2*>(dwp + (i * 7 + j) * 192 + 64 + 8 * c.v));
        }
        w[k][0] = w8.x; w[k][1] = w8.y; w[k][2] = w8.z; w[k][3] = w8.w; w[k][4] = w4.x; w[k][5] = w4.y;
      }
#pragma unroll
      for (int q = 0; q < 6; q++) {
        B[2 * q + par][2 * b] = __byte_perm(w[0][q], w[1][q], par ? 0x7632 : 0x5410);
        B[2 * q + par][2 * b + 1] = __byte_perm(w[2][q], w[3][q], par ? 0x7632 : 0x5410);
      }
    }
  }
  TR(2, 1004);
  asm volatile("barrier.cluster.wait.aligned;" ::: "memory");
  uint32_t K1[12], K2[12], V[12][4];
#pragma unroll
  for (int ch = 0; ch < 12; ch++) {
    K1[ch] = K2[ch] = 0;
#pragma unroll
    for (int k = 0; k < 4; k++) V[ch][k] = 0;
  }
  uint32_t A[12][4];
  {
    uint32_t r[6][6];
    mbar_wait(c.sb + BAR_RAW, 0);
    conv_ld8(c.a_raw, r);
    conv_ld4(c.a_raw + 64 - 8 * c.v, r);
    conv_frags(c.zero, r, A);
  }
  NB_ARRIVE(NB_CLOSE, 256);
#pragma unroll 1
  for (int s = 0; s < SIGMA; s += 2) {
    conv_step<false, true>(c, s, K1, V, B, A);
    conv_step<false, true>(c, s + 1, K2, A, B, V);
  }
#pragma unroll 1
  for (int s = SIGMA; s < NSTEP - 1; s += 2) {
    conv_step<true, true>(c, s, K1, V, B, A);
    conv_step<true, true>(c, s + 1, K2, A, B, V);
  }
  conv_step<true, false>(c, NSTEP - 1, K1, V, B, A);
#pragma unroll 1
  for (int r = NSTEP - SIGMA - c.rank; r < NROUND - 1; r++) {
    NB_SYNC(NB_OPEN, 416);
    NB_ARRIVE(NB_CLOSE, 256);
  }
  NB_SYNC(NB_OPEN, 416);
}

__global__ void __cluster_dims__(2, 1, 1) __launch_bounds__(512, 1)
convnext_kernel(const __grid_constant__ CUtensorMap tm, const __nv_bfloat16* __restrict__ x, const __nv_bfloat16* __restrict__ dw,
                const __nv_bfloat16* __restrict__ w1, const __nv_bfloat16* __restrict__ w2, __nv_bfloat16* __restrict__ out,
                int zero) {
  extern __shared__ __align__(1024) uint8_t smem[];
  const uint32_t sb = (uint32_t)__cvta_generic_to_shared(smem);
  const int tid = threadIdx.x, lane = tid & 31;
  const int wid = __shfl_sync(0xffffffffu, tid >> 5, 0);
  const int rank = blockIdx.x & 1, cl = blockIdx.x >> 1;
  const int c0 = (cl & 15) * 32, r0 = (cl >> 4) * 128;
  const uint32_t peer_off = mapa(sb, rank ^ 1) - sb;

  TR(wid >> 2, 1002);
  TRG(1020);
  if (tid == 0) {
    for (int i = 0; i < 2; i++) mbar_init(sb + BAR_W + 8 * i, 1);
    asm volatile("fence.mbarrier_init.release.cluster;" ::: "memory");
    for (int i = 0; i < 2; i++) mbar_expect(sb + BAR_W + 8 * i, 73728);
    for (int i = 0; i < 4; i++) bulk_load(sb + OFF_W1 + i * 18432, reinterpret_cast<const uint8_t*>(w1) + i * 18432, 18432, sb + BAR_W);
    for (int i = 0; i < 4; i++) bulk_load(sb + OFF_W2 + i * 18432, reinterpret_cast<const uint8_t*>(w2) + i * 18432, 18432, sb + BAR_W + 8);
  }
  if (wid >= 12 && lane == 0) {
    const int i = wid - 12;
    mbar_init(sb + BAR_RAW + 8 * i, 1);
    asm volatile("fence.mbarrier_init.release.cluster;" ::: "memory");
    tma_raw(sb + OFF_RAW + i * RAW_BYTES, &tm, 56 * rank - 8, c0 / 2 - 2, r0 - 3 + 2 * i, sb + BAR_RAW + 8 * i);
  }
  if (tid == 128) {
    for (int i = 0; i < 2; i++) mbar_init(sb + BAR_CFULL + 8 * i, 1);
    for (int i = 0; i < 4; i++) mbar_init(sb + BAR_CEMPTY + 8 * i, 4);
    for (int i = 0; i < 2; i++) mbar_init(sb + BAR_XFULL + 8 * i, 1);
    for (int i = 0; i < 2; i++) mbar_expect(sb + BAR_CFULL + 8 * i, 12288);
    asm volatile("fence.mbarrier_init.release.cluster;" ::: "memory");
  }
  __syncthreads();
  asm volatile("barrier.cluster.arrive.relaxed.aligned;" ::: "memory");

  TR(wid >> 2, 1003);
  if (wid < 8) {
    MlpCtx m;
    m.sb = sb; m.wg = wid >> 2; m.warp = wid & 3; m.rank = rank; m.peer_off = peer_off; m.zero = zero;
    m.optr = reinterpret_cast<uint8_t*>(out) + ((size_t)(r0 + 4 * m.wg + 2 * rank) * IMG + c0 + 8 * m.warp) * (CH * 2);
    m.caddr = sb + OFF_C + m.wg * C_BYTES + m.warp * 128 + (lane & 3) * (6 * 512 + 32) + (lane >> 2) * 16;
    m.xaddr = sb + OFF_XRES + m.wg * 12288 + m.warp * 1536 + ((lane >> 3) & 1) * 6144 + ((lane >> 4) * 4 + ((lane >> 2) & 1)) * 192 + (lane & 3) * 16;
    m.unscale = 0;
    asm volatile("setmaxnreg.inc.sync.aligned.u32 %0;" ::"n"(REG_MLP));
    const uint32_t bad = mlp_role(m);
    asm volatile("barrier.cluster.arrive.relaxed.aligned;\nbarrier.cluster.wait.aligned;" ::: "memory");
    if (bad) {
      asm volatile("fence.proxy.async;" ::: "memory");
      for (int i = 0; i < 16; i++)
        if (bad >> i & 1)
          slow_tile(x, dw, w1, w2, out, r0 + 8 * i + 4 * m.wg + 2 * rank, c0 + 8 * m.warp,
                    reinterpret_cast<float*>(smem + OFF_XRES + wid * 3072));
    }
  } else {
    ConvCtx c;
    c.sb = sb; c.rank = rank; c.v = wid - 8; c.c0 = c0; c.r0 = r0; c.zero = zero; c.tm = &tm;
    c.peer_off = peer_off;
    c.xsrc = reinterpret_cast<const uint8_t*>(x) + ((size_t)(r0 + 2 * rank) * IMG + c0) * (CH * 2);
    c.optr = reinterpret_cast<uint8_t*>(out) + ((size_t)(r0 + 2 * rank) * IMG + c0) * (CH * 2);
    const int g = lane >> 2, t = lane & 3;
    c.a_raw = sb + OFF_RAW + ((t >> 1) * 19 + 2 * (g + (t & 1))) * 112 + (1 - rank) * 16 + 16 * c.v;
    const int q0 = 12 * rank + 3 * c.v;
    c.a_c = sb + OFF_C + q0 * 512 + (q0 / 6) * 32 + lane * 16;
    if (wid < 12) {
      asm volatile("setmaxnreg.inc.sync.aligned.u32 %0;" ::"n"(REG_CONV));
      conv_role(c, dw);
      __syncwarp();
      asm volatile("barrier.cluster.arrive.relaxed.aligned;\nbarrier.cluster.wait.aligned;\nexit;" ::: "memory");
    } else {
      asm volatile("setmaxnreg.dec.sync.aligned.u32 24;");
      if (wid == 12) {
        prod_role(c);
        asm volatile("barrier.cluster.arrive.relaxed.aligned;\nbarrier.cluster.wait.aligned;" ::: "memory");
      }
    }
  }
}

typedef CUresult (*EncodeFn)(CUtensorMap*, CUtensorMapDataType, cuuint32_t, void*, const cuuint64_t*, const cuuint64_t*,
                             const cuuint32_t*, const cuuint32_t*, CUtensorMapInterleave, CUtensorMapSwizzle,
                             CUtensorMapL2promotion, CUtensorMapFloatOOBfill);

}

extern "C" void kernel_launch(void* const* d_in, const int* in_sizes, int n_in, void* d_out, int out_size) {
  const __nv_bfloat16* x = (const __nv_bfloat16*)d_in[0];
  const __nv_bfloat16* dw = (const __nv_bfloat16*)d_in[1];
  const __nv_bfloat16* w1 = (const __nv_bfloat16*)d_in[2];
  const __nv_bfloat16* w2 = (const __nv_bfloat16*)d_in[3];
  __nv_bfloat16* out = (__nv_bfloat16*)d_out;

  static EncodeFn encode = nullptr;
  if (!encode) {
    cudaDriverEntryPointQueryResult st;
    void* fn = nullptr;
    cudaGetDriverEntryPoint("cuTensorMapEncodeTiled", &fn, cudaEnableDefault, &st);
    encode = (EncodeFn)fn;
    cudaFuncSetAttribute(convnext_kernel, cudaFuncAttributeMaxDynamicSharedMemorySize, SMEM_BYTES);
  }
  CUtensorMap tm;
  cuuint64_t dims[4] = {CH, IMG / 2, IMG, 2};
  cuuint64_t strides[3] = {CH * 4, (cuuint64_t)IMG * CH * 2, CH * 2};
  cuuint32_t box[4] = {56, 19, 2, 1};
  cuuint32_t es[4] = {1, 1, 1, 1};
  encode(&tm, CU_TENSOR_MAP_DATA_TYPE_BFLOAT16, 4, (void*)x, dims, strides, box, es, CU_TENSOR_MAP_INTERLEAVE_NONE,
         CU_TENSOR_MAP_SWIZZLE_NONE, CU_TENSOR_MAP_L2_PROMOTION_L2_128B, CU_TENSOR_MAP_FLOAT_OOB_FILL_NONE);
  convnext_kernel<<<128, 512, SMEM_BYTES>>>(tm, x, dw, w1, w2, out, 0);
}
```

```cpp
#include <cuda_runtime.h>
#include <cuda_bf16.h>
#include <cuda.h>
#include <stdint.h>

namespace {

constexpr int IMG = 512, CH = 96;
constexpr int NSTEP = 67;
constexpr int SIGMA = 8;
constexpr int NROUND = 68;

constexpr uint32_t OFF_W1 = 0;
constexpr uint32_t OFF_W2 = 73728;
constexpr uint32_t OFF_RAW = 147456;
constexpr uint32_t RAW_PLANE = 4352;
constexpr uint32_t RAW_BYTES = 2 * RAW_PLANE;
constexpr uint32_t RAW_TX = 2 * 2 * 19 * 112;
constexpr uint32_t OFF_XRES = OFF_RAW + 4 * RAW_BYTES;
constexpr uint32_t OFF_C = OFF_XRES + 2 * 12288;
constexpr uint32_t C_BYTES = 12416;
constexpr uint32_t OFF_BAR = OFF_C + 2 * C_BYTES;
constexpr uint32_t BAR_RAW = OFF_BAR;
constexpr uint32_t BAR_CFULL = OFF_BAR + 32;
constexpr uint32_t BAR_CEMPTY = OFF_BAR + 48;
constexpr uint32_t BAR_XFULL = OFF_BAR + 80;
constexpr uint32_t BAR_W = OFF_BAR + 136;
constexpr uint32_t OFF_NRM = OFF_BAR + 160;
constexpr uint32_t OFF_LT = OFF_BAR + 160;
constexpr uint32_t SMEM_BYTES = OFF_BAR + 160 + 600;

constexpr float GELU_A = 0.32918364f;
constexpr uint32_t GELU_K2 = 0x40d940d9u;

constexpr int NB_CLOSE = 1, NB_SEC = 6  , NB_OPEN = 3, NB_PROD = 2, NB_PLAN = 8  , NB_PREP = 5;
#define REG_MLP 144
constexpr int REG_CONV = 488 - 2 * REG_MLP;

#define WG_FENCE() asm volatile("wgmma.fence.sync.aligned;" ::: "memory")
#define WG_COMMIT() asm volatile("wgmma.commit_group.sync.aligned;" ::: "memory")
#define WG_WAIT0() asm volatile("wgmma.wait_group.sync.aligned 0;" ::: "memory")
#define WG_WAIT1() asm volatile("wgmma.wait_group.sync.aligned 1;" ::: "memory")
#define PIN() asm volatile("pmevent 0;" ::: "memory")
#define NB_SYNC(id, n) asm volatile("bar.sync %0, %1;" ::"n"(id), "n"(n) : "memory")
#define NB_ARRIVE(id, n) asm volatile("bar.arrive %0, %1;" ::"n"(id), "n"(n) : "memory")

#define TR(who, idx)
#define TRG(idx)

#define TC(k)
#define TL(base, off)
#define TLDUMP(cond, base, n)

#define R24(c, d)                                                                                        \
  c(d[0]), c(d[1]), c(d[2]), c(d[3]), c(d[4]), c(d[5]), c(d[6]), c(d[7]), c(d[8]), c(d[9]), c(d[10]),    \
      c(d[11]), c(d[12]), c(d[13]), c(d[14]), c(d[15]), c(d[16]), c(d[17]), c(d[18]), c(d[19]), c(d[20]), \
      c(d[21]), c(d[22]), c(d[23])
#define WG_TXT(sd)                                                                             \
  "wgmma.mma_async.sync.aligned.m64n96k16.f16.f16.f16 "                                        \
  "{%0,%1,%2,%3,%4,%5,%6,%7,%8,%9,%10,%11,%12,%13,%14,%15,%16,%17,%18,%19,%20,%21,%22,%23}, " \
  "{%24,%25,%26,%27}, %28, " sd ", 1, 1, 1;\n"

__device__ __forceinline__ void wg_acc(uint32_t (&d)[24], const uint32_t* a, uint64_t db) {
  asm volatile(WG_TXT("1") : R24("+r", d) : "r"(a[0]), "r"(a[1]), "r"(a[2]), "r"(a[3]), "l"(db));
}
__device__ __forceinline__ void wg_init(uint32_t (&d)[24], const uint32_t* a, uint64_t db) {
  asm volatile(WG_TXT("0") : R24("=r", d) : "r"(a[0]), "r"(a[1]), "r"(a[2]), "r"(a[3]), "l"(db));
}
template <int N>
__device__ __forceinline__ void rfence(uint32_t (&d)[N]) {
#pragma unroll
  for (int i = 0; i < N; i++) asm volatile("" : "+r"(d[i])::"memory");
}
template <bool INIT, int KSTRIDE>
__device__ __forceinline__ void gemm6(uint32_t (&d)[24], const uint32_t (&a)[24], uint64_t db) {
#pragma unroll
  for (int k = 0; k < 6; k++) {
    if (INIT && k == 0) wg_init(d, &a[0], db);
    else wg_acc(d, &a[4 * k], db + k * KSTRIDE);
  }
  WG_COMMIT();
}

__device__ __forceinline__ void mbar_init(uint32_t bar, uint32_t cnt) {
  asm volatile("mbarrier.init.shared::cta.b64 [%0], %1;" ::"r"(bar), "r"(cnt) : "memory");
}
__device__ __forceinline__ void mbar_expect(uint32_t bar, uint32_t bytes) {
  asm volatile("mbarrier.arrive.expect_tx.shared::cta.b64 _, [%0], %1;" ::"r"(bar), "r"(bytes) : "memory");
}
__device__ __forceinline__ void mbar_arrive_cluster(uint32_t bar) {
  asm volatile("mbarrier.arrive.shared::cluster.b64 _, [%0];" ::"r"(bar) : "memory");
}
__device__ __forceinline__ bool mbar_try(uint32_t bar, uint32_t parity) {
  uint32_t ok;
  asm volatile(
      "{\n.reg .pred p;\nmbarrier.try_wait.parity.shared::cta.b64 p, [%1], %2;\nselp.u32 %0, 1, 0, p;\n}\n"
      : "=r"(ok)
      : "r"(bar), "r"(parity)
      : "memory");
  return ok;
}
__device__ __forceinline__ bool mbar_test(uint32_t bar, uint32_t parity) {
  uint32_t ok;
  asm volatile(
      "{\n.reg .pred p;\nmbarrier.test_wait.parity.shared::cta.b64 p, [%1], %2;\nselp.u32 %0, 1, 0, p;\n}\n"
      : "=r"(ok)
      : "r"(bar), "r"(parity)
      : "memory");
  return ok;
}
__device__ __forceinline__ void mbar_wait(uint32_t bar, uint32_t parity) {
  if (__builtin_expect(mbar_try(bar, parity), 1)) return;
#pragma unroll 1
  for (uint32_t n = 0; n < (1u << 16) && !mbar_try(bar, parity); n++) {}
}
__device__ __forceinline__ uint32_t mapa(uint32_t addr, uint32_t rank) {
  uint32_t r;
  asm("mapa.shared::cluster.u32 %0, %1, %2;" : "=r"(r) : "r"(addr), "r"(rank));
  return r;
}
__device__ __forceinline__ void tma_raw(uint32_t dst, const CUtensorMap* tm, int c, int w2, int h, uint32_t bar) {
  mbar_expect(bar, RAW_TX);
#pragma unroll
  for (int e = 0; e < 2; e++)
    asm volatile(
        "cp.async.bulk.tensor.4d.shared::cluster.global.mbarrier::complete_tx::bytes [%0], [%1, {%2, %3, %4, %5}], [%6];"
        ::"r"(dst + e * RAW_PLANE), "l"(tm), "r"(c), "r"(w2 + e), "r"(h), "r"(1 - e), "r"(bar)
        : "memory");
}
__device__ __forceinline__ void bulk_load(uint32_t dst, const void* src, uint32_t bytes, uint32_t bar) {
  asm volatile("cp.async.bulk.shared::cluster.global.mbarrier::complete_tx::bytes [%0], [%1], %2, [%3];" ::"r"(dst),
               "l"(src), "r"(bytes), "r"(bar)
               : "memory");
}
__device__ __forceinline__ uint32_t pack_bf16(float lo, float hi) {
  uint32_t r;
  asm("cvt.rn.bf16x2.f32 %0, %1, %2;" : "=r"(r) : "f"(hi), "f"(lo));
  return r;
}
__device__ __forceinline__ uint32_t pack_f16(float lo, float hi) {
  uint32_t r;
  asm("cvt.rn.f16x2.f32 %0, %1, %2;" : "=r"(r) : "f"(hi), "f"(lo));
  return r;
}
__device__ __forceinline__ float bf_lo(uint32_t v) { return __uint_as_float(v << 16); }
__device__ __forceinline__ float bf_hi(uint32_t v) { return __uint_as_float(v & 0xffff0000u); }
__device__ __forceinline__ uint32_t bf_add(uint32_t a, uint32_t b) {
  uint32_t r;
  asm("add.rn.bf16x2 %0, %1, %2;" : "=r"(r) : "r"(a), "r"(b));
  return r;
}
__device__ __forceinline__ uint32_t bf_mul(uint32_t a, uint32_t b) {
  uint32_t r;
  asm("mul.rn.bf16x2 %0, %1, %2;" : "=r"(r) : "r"(a), "r"(b));
  return r;
}
__device__ __forceinline__ uint32_t bf_fma(uint32_t a, uint32_t b, uint32_t c) {
  uint32_t r;
  asm("fma.rn.bf16x2 %0, %1, %2, %3;" : "=r"(r) : "r"(a), "r"(b), "r"(c));
  return r;
}

__device__ __forceinline__ uint32_t h_add(uint32_t a, uint32_t b) {
  uint32_t r;
  asm("add.rn.f16x2 %0, %1, %2;" : "=r"(r) : "r"(a), "r"(b));
  return r;
}
__device__ __forceinline__ uint32_t h_mul(uint32_t a, uint32_t b) {
  uint32_t r;
  asm("mul.rn.f16x2 %0, %1, %2;" : "=r"(r) : "r"(a), "r"(b));
  return r;
}
__device__ __forceinline__ uint32_t h_fma(uint32_t a, uint32_t b, uint32_t c) {
  uint32_t r;
  asm("fma.rn.f16x2 %0, %1, %2, %3;" : "=r"(r) : "r"(a), "r"(b), "r"(c));
  return r;
}
__device__ __forceinline__ float h_sum(uint32_t v) {
  float lo, hi;
  asm("{\n.reg .b16 l, h;\nmov.b32 {l, h}, %2;\ncvt.f32.f16 %0, l;\ncvt.f32.f16 %1, h;\n}\n" : "=f"(lo), "=f"(hi) : "r"(v));
  return lo + hi;
}
__device__ __forceinline__ void lds128(uint32_t (&v)[4], uint32_t a) {
  asm volatile("ld.shared.v4.b32 {%0,%1,%2,%3}, [%4];" : "=r"(v[0]), "=r"(v[1]), "=r"(v[2]), "=r"(v[3]) : "r"(a) : "memory");
}

template <int LO, int HI>
__device__ __forceinline__ void gelu(uint32_t (&o)[24], const uint32_t (&d)[24]) {
#pragma unroll
  for (int qq = LO; qq < HI; qq++) {
    const int q = (qq + 4) % 24;
    uint32_t t, u;
    asm("fma.rn.f16x2 %0, %1, %1, %2;" : "=r"(t) : "r"(d[q]), "r"(GELU_K2));
    asm("mul.rn.f16x2 %0, %1, %2;" : "=r"(u) : "r"(d[q]), "r"(t));
    asm("tanh.approx.f16x2 %0, %1;" : "=r"(t) : "r"(u));
    asm("fma.rn.f16x2 %0, %1, %2, %1;" : "=r"(o[q]) : "r"(d[q]), "r"(t));
  }
}

__device__ __forceinline__ uint32_t laneid() {
  uint32_t l;
  asm volatile("mov.u32 %0, %%laneid;" : "=r"(l));
  return l;
}

__device__ __forceinline__ bool elect_one() {
  uint32_t p;
  asm volatile("{\n.reg .pred p;\nelect.sync _|p, 0xffffffff;\nselp.u32 %0, 1, 0, p;\n}\n" : "=r"(p));
  return p;
}

__device__ __forceinline__ uint32_t clock_pin() {
  uint32_t t;
  asm volatile("mov.u32 %0, %%clock;" : "=r"(t)::"memory");
  return t;
}

struct MlpCtx {
  uint32_t sb;
  uint32_t caddr;
  uint32_t xaddr;
  uint32_t unscale;
  uint32_t peer_off;
  int wg, warp, rank, zero;
  uint8_t* optr;
};

__device__ __forceinline__ void ln_wait(const MlpCtx& m, int i) { mbar_wait(m.sb + BAR_CFULL + 8 * m.wg, i & 1); }
__device__ __forceinline__ void ln_load(const MlpCtx& m, uint32_t (&c)[24]) {
#pragma unroll
  for (int p = 0; p < 6; p++)
    asm volatile("ld.shared.v4.b32 {%0,%1,%2,%3}, [%4];"
                 : "=r"(c[4 * p]), "=r"(c[4 * p + 1]), "=r"(c[4 * p + 2]), "=r"(c[4 * p + 3])
                 : "r"(m.caddr + p * 512)
                 : "memory");
}
__device__ __forceinline__ void ln_shfl(float (&st)[8], int mask) {
#pragma unroll
  for (int k = 0; k < 4; k++) st[4 + k] = __shfl_xor_sync(0xffffffffu, st[k], mask);
}
__device__ __forceinline__ void ln_fold(float (&st)[8]) {
#pragma unroll
  for (int k = 0; k < 4; k++) st[k] += st[4 + k];
}
__device__ __forceinline__ void ln_sums(const uint32_t (&c)[24], float (&st)[8]) {
#pragma unroll
  for (int r = 0; r < 2; r++) {
    uint32_t s0 = h_add(c[r], c[r + 2]), s1 = h_add(c[r + 4], c[r + 6]), s2 = h_add(c[r + 8], c[r + 10]);
    uint32_t s3 = h_add(c[r + 12], c[r + 14]), s4 = h_add(c[r + 16], c[r + 18]), s5 = h_add(c[r + 20], c[r + 22]);
    s0 = h_add(s0, s1); s2 = h_add(s2, s3); s4 = h_add(s4, s5);
    st[r] = h_sum(h_add(h_add(s0, s2), s4));
    uint32_t q0 = h_mul(c[r], c[r]), q1 = h_mul(c[r + 2], c[r + 2]);
#pragma unroll
    for (int p = 2; p < 12; p += 2) {
      q0 = h_fma(c[2 * p + r], c[2 * p + r], q0);
      q1 = h_fma(c[2 * p + 2 + r], c[2 * p + 2 + r], q1);
    }
    st[2 + r] = h_sum(h_add(q0, q1));
  }
}
__device__ __forceinline__ void ln_release(const MlpCtx& m) {
  const uint32_t e = m.sb + BAR_CEMPTY + 8 * (2 * m.rank + m.wg);
  asm volatile(
      "{\n.reg .pred p, q;\nelect.sync _|p, 0xffffffff;\nsetp.eq.and.s32 q, %3, 0, p;\n"
      "@q mbarrier.arrive.expect_tx.shared::cta.b64 _, [%0], 12288;\n"
      "@p mbarrier.arrive.shared::cluster.b64 _, [%1];\n"
      "@p mbarrier.arrive.shared::cluster.b64 _, [%2];\n}\n" ::"r"(m.sb + BAR_CFULL + 8 * m.wg),
      "r"(e), "r"(e + m.peer_off), "r"(m.warp)
      : "memory");
}
__device__ __forceinline__ void ln_stats(float (&st)[8], uint32_t& bad, uint32_t bit) {
  bool ok = true;
#pragma unroll
  for (int r = 0; r < 2; r++) {
    const float nm = (st[r] + st[4 + r]) * (-1.0f / 96.0f);
    const float e2 = fmaf(st[2 + r] + st[6 + r], 1.0f / 96.0f, 1e-5f);
    float rs;
    asm("rsqrt.approx.ftz.f32 %0, %1;" : "=f"(rs) : "f"(fmaf(-nm, nm, e2)));
    ok = ok && (rs * rs * e2 <= 17.0f) && (e2 >= 1.001e-5f);
    const float rr = rs * GELU_A, dd = rr * nm;
    st[r] = __uint_as_float(pack_f16(rr, rr));
    st[2 + r] = __uint_as_float(pack_f16(dd, dd));
  }
  if (!ok) bad |= bit;
}
__device__ __forceinline__ void ln_apply(uint32_t (&a)[24], const uint32_t (&c)[24], const float (&st)[8]) {
#pragma unroll
  for (int p = 0; p < 24; p++) a[p] = h_fma(c[p], __float_as_uint(st[p & 1]), __float_as_uint(st[2 + (p & 1)]));
}

__device__ __noinline__ void slow_tile(const __nv_bfloat16* x, const __nv_bfloat16* dw, const __nv_bfloat16* w1,
                                       const __nv_bfloat16* w2, __nv_bfloat16* out, int row0, int col0, float* buf) {
  const int lane = threadIdx.x & 31;
  for (int px = 0; px < 16; px++) {
    const int row = row0 + (px >> 3), col = col0 + (px & 7);
    float c[3] = {0.f, 0.f, 0.f};
    for (int i = 0; i < 7; i++)
      for (int j = 0; j < 7; j++) {
        const int rr = row + i - 3, cc = col + j - 3;
        if (rr < 0 || rr >= IMG || cc < 0 || cc >= IMG) continue;
        for (int k = 0; k < 3; k++)
          c[k] = fmaf(__bfloat162float(x[((size_t)rr * IMG + cc) * CH + lane + 32 * k]), __bfloat162float(dw[(i * 7 + j) * CH + lane + 32 * k]), c[k]);
      }
    float mean = (c[0] + c[1] + c[2]) * (1.0f / 96.0f);
    for (int o = 16; o; o >>= 1) mean += __shfl_xor_sync(0xffffffffu, mean, o);
    float var = 0.f;
    for (int k = 0; k < 3; k++) { c[k] -= mean; var = fmaf(c[k] * (1.0f / 96.0f), c[k], var); }
    for (int o = 16; o; o >>= 1) var += __shfl_xor_sync(0xffffffffu, var, o);
    const float rs = 1.0f / sqrtf(var + 1e-5f);
    __syncwarp();
    for (int k = 0; k < 3; k++) buf[lane + 32 * k] = c[k] * rs;
    __syncwarp();
    for (int n = lane; n < 4 * CH; n += 32) {
      float y = 0.f;
      for (int k = 0; k < CH; k++) y = fmaf(buf[k], __bfloat162float(w1[k * 4 * CH + n]), y);
      buf[CH + n] = 0.5f * y * (1.0f + tanhf(0.7978845608f * (y + 0.044715f * y * y * y)));
    }
    __syncwarp();
    for (int n = lane; n < CH; n += 32) {
      float o = 0.f;
      for (int k = 0; k < 4 * CH; k++) o = fmaf(buf[CH + k], __bfloat162float(w2[k * CH + n]), o);
      const size_t idx = ((size_t)row * IMG + col) * CH + n;
      out[idx] = __float2bfloat16(__bfloat162float(x[idx]) + o);
    }
  }
}

__device__ __forceinline__ void x_load(const MlpCtx& m, uint32_t (&x)[24]) {
#pragma unroll
  for (int k = 0; k < 6; k++)
    asm volatile("ld.shared.v4.b32 {%0,%1,%2,%3}, [%4];"
                 : "=r"(x[4 * k]), "=r"(x[4 * k + 1]), "=r"(x[4 * k + 2]), "=r"(x[4 * k + 3])
                 : "r"(m.xaddr + (k / 3) * 384 + (k % 3) * 64)
                 : "memory");
}
template <int LO, int HI>
__device__ __forceinline__ void epilogue(const MlpCtx& m, const uint32_t (&d)[24], uint32_t (&x)[24]) {
#pragma unroll
  for (int k = LO; k < HI; k++) {
    const int r = k / 3, q = k % 3;
    uint32_t* y = &x[4 * k];
#pragma unroll
    for (int j = 0; j < 4; j++) {
      uint32_t v = d[2 * (4 * q + j) + r];
      float lo, hi;
      asm("{\n.reg .b16 l, h;\nmov.b32 {l, h}, %2;\ncvt.f32.f16 %0, l;\ncvt.f32.f16 %1, h;\n}\n" : "=f"(lo), "=f"(hi) : "r"(v));
      asm("fma.rn.bf16x2 %0, %1, %2, %0;" : "+r"(y[j]) : "r"(pack_bf16(lo, hi)), "r"(m.unscale));
    }
    asm volatile("st.shared.v4.b32 [%0], {%1,%2,%3,%4};" ::"r"(m.xaddr + r * 384 + q * 64), "r"(y[0]), "r"(y[1]), "r"(y[2]), "r"(y[3])
                 : "memory");
  }
}
__device__ __forceinline__ void out_store(const MlpCtx& m, int i) {
  asm volatile("fence.proxy.async.shared::cta;" ::: "memory");
  __syncwarp();
  if (elect_one()) {
    const uint32_t src = m.sb + OFF_XRES + m.wg * 12288 + m.warp * 1536;
    uint8_t* dst = m.optr + (size_t)i * (8 * IMG * CH * 2);
    asm volatile("cp.async.bulk.global.shared::cta.bulk_group [%0], [%1], 1536;" ::"l"(dst), "r"(src) : "memory");
    asm volatile("cp.async.bulk.global.shared::cta.bulk_group [%0], [%1], 1536;" ::"l"(dst + IMG * CH * 2), "r"(src + 6144) : "memory");
    asm volatile("cp.async.bulk.commit_group;" ::: "memory");
  }
}

#define FSET 0
constexpr int FJ = FSET ? 2 : 0;
template <int J> __device__ __forceinline__ void tok_wait() {
  if (J == FJ || J == 3) NB_SYNC(NB_CLOSE, 256);
  else NB_SYNC(NB_SEC + (J & 1), 256);
}
template <int J> __device__ __forceinline__ void tok_next() {
  if (J == FJ || J == 3) NB_ARRIVE(NB_SEC + (J & 1), 256);
  if (J == 0 || J == 3) NB_ARRIVE(NB_PROD, 160);
}
__device__ __forceinline__ void tok_pass() { NB_ARRIVE(NB_OPEN, 416); }
template <int J> __device__ __forceinline__ void tok_idle() { tok_wait<J>(); tok_next<J>(); tok_pass(); }

constexpr uint64_t CHK = 1152;

__device__ __forceinline__ void sumsq(const uint32_t (&v)[18][4], uint32_t dst) {
  uint32_t q[4] = {0, 0, 0, 0};
#pragma unroll
  for (int it = 0; it < 18; it++)
#pragma unroll
    for (int t = 0; t < 4; t++) q[t] = bf_fma(v[it][t], v[it][t], q[t]);
  q[0] = bf_add(bf_add(q[0], q[1]), bf_add(q[2], q[3]));
  float f = bf_lo(q[0]) + bf_hi(q[0]);
#pragma unroll
  for (int o = 16; o; o >>= 1) f += __shfl_xor_sync(0xffffffffu, f, o);
  if ((threadIdx.x & 31) == 0) asm volatile("st.shared.f32 [%0], %1;" ::"r"(dst), "f"(f) : "memory");
}

__device__ __forceinline__ uint32_t mlp_role(const MlpCtx& m0) {
  MlpCtx m = m0;
  uint32_t bad = 0;
  const int lane = threadIdx.x & 31, wid = m.wg * 4 + m.warp;
  {
    uint32_t v[18][4];
    const int k7 = lane & 7;
    {
      TR(m.wg, 1006);
      mbar_wait(m.sb + BAR_W, 0);
      TR(m.wg, 1007);
#pragma unroll
      for (int it = 0; it < 18; it++) {
        const int kb = (it / 3) * 2 + (wid & 1), ks = it / 3;
        const int Q = 6 * (k7 >> 1) + ks, q12 = Q % 12, cv = q12 / 3, e = q12 % 3;
        const int ch = 48 * (Q / 12) + (e < 2 ? 8 * cv + 4 * e : 32 + 4 * cv) + 2 * (kb & 1) + (k7 & 1);
        const int n8 = (it % 3) * 16 + ((wid >> 2) * 8 + ((((wid >> 1) & 1) * 4 + (lane >> 3) + k7) & 7));
        lds128(v[it], m.sb + OFF_W1 + ch * 768 + n8 * 16);
      }
      sumsq(v, m.sb + OFF_NRM + 4 * wid);
      NB_SYNC(NB_PREP, 256);
#pragma unroll
      for (int it = 0; it < 18; it++) {
        const int n8 = (it % 3) * 16 + ((wid >> 2) * 8 + ((((wid >> 1) & 1) * 4 + (lane >> 3) + k7) & 7));
        const uint32_t dst = m.sb + OFF_W1 + (it / 3) * 12288 + n8 * 256 + (wid & 1) * 128 + k7 * 16;
        asm volatile("st.shared.v4.b32 [%0], {%1,%2,%3,%4};" ::"r"(dst), "r"(pack_f16(bf_lo(v[it][0]), bf_hi(v[it][0]))),
                     "r"(pack_f16(bf_lo(v[it][1]), bf_hi(v[it][1]))), "r"(pack_f16(bf_lo(v[it][2]), bf_hi(v[it][2]))),
                     "r"(pack_f16(bf_lo(v[it][3]), bf_hi(v[it][3])))
                     : "memory");
      }
    }
    TR(m.wg, 1004);
    {
      mbar_wait(m.sb + BAR_W + 8, 0);
      const uint32_t base = m.sb + OFF_W2 + wid * 9216;
#pragma unroll
      for (int it = 0; it < 18; it++) lds128(v[it], base + (lane >> 2) * 192 + (lane & 3) * 16 + (it / 3) * 1536 + (it % 3) * 64);
      sumsq(v, m.sb + OFF_NRM + 32 + 4 * wid);
      TR(m.wg, 1005);
      NB_SYNC(NB_PREP, 256);
      int e[2];
#pragma unroll
      for (int k = 0; k < 2; k++) {
        uint32_t a[4], b[4];
        lds128(a, m.sb + OFF_NRM + 32 * k);
        lds128(b, m.sb + OFF_NRM + 32 * k + 16);
        float f = 0.f;
#pragma unroll
        for (int t = 0; t < 4; t++) f += __uint_as_float(a[t]) + __uint_as_float(b[t]);
        e[k] = (((int)(__float_as_uint(f * 1.5f) >> 23) - 127) >> 1) + 1;
      }
      const int s = min(11 - e[0] - e[1], 14 - e[1]);
      if (e[0] > 12 || e[0] < -5 || e[1] > 60 || e[1] < -60) bad = 0xffffu;
      const float sc = __uint_as_float((uint32_t)(127 + s) << 23) * (0.5f / GELU_A);
      m.unscale = __shfl_sync(0xffffffffu, ((uint32_t)(127 - s) << 7) * 0x10001u, 0);
#pragma unroll
      for (int it = 0; it < 18; it++)
#pragma unroll
        for (int j = 0; j < 4; j++)
          asm volatile("st.shared.b32 [%0], %1;" ::"r"(base + lane * 4 + (it / 6) * 3072 + ((it / 3) & 1) * 128 + ((it % 3) * 4 + j) * 256),
                       "r"(pack_f16(bf_lo(v[it][j]) * sc, bf_hi(v[it][j]) * sc))
                       : "memory");
    }
    asm volatile("fence.proxy.async.shared::cta;" ::: "memory");
    NB_SYNC(NB_PREP, 256);
  }
  asm volatile("barrier.cluster.wait.aligned;" ::: "memory");
  const uint64_t dW1 = (uint64_t)(((m.sb + OFF_W1) & 0x3FFFF) >> 4) | ((uint64_t)8 << 16) | ((uint64_t)16 << 32);
  const uint64_t dW2 = dW1 + (OFF_W2 >> 4);

  TR(m.wg, 1000);
  uint32_t A1[24], g[24], d[24], cn[24], D2[24];
  float st[8];
  ln_wait(m, 0);
  ln_load(m, cn);
  ln_sums(cn, st);
  ln_shfl(st, 1);
  ln_release(m);
  ln_fold(st);
  ln_shfl(st, 2);
  ln_stats(st, bad, 1);
  ln_apply(A1, cn, st);
  [[maybe_unused]] int rho = 2 * m.wg + m.rank + 2;
  if (m.wg & m.rank) tok_idle<3>();
  if (m.wg) tok_idle<0>();
  if (m.wg | m.rank) tok_idle<1>();
  {
    uint32_t d0[24];
    WG_FENCE();
    tok_wait<2>();
    tok_next<2>();
    gemm6<true, 768>(d0, A1, dW1);
    tok_pass(); PIN();
    WG_WAIT0(); rfence(d0);
    WG_FENCE();
    tok_wait<3>();
    tok_next<3>();
    gemm6<true, 768>(d, A1, dW1 + 192);
    tok_pass(); PIN();
    gelu<0, 24>(g, d0);
    PIN();
    ln_wait(m, 1);
    ln_load(m, cn);
    PIN();
    WG_WAIT0(); rfence(d);
  }
#define G2(INIT, a, j)                      \
  WG_FENCE();                               \
  tok_wait<j>();                            \
  TR(m.wg, rho * 8);                        \
  gemm6<INIT, 192>(D2, a, dW2 + (j) * CHK); \
  tok_next<j>(); PIN();                     \
  TL(ltb, (j) * 5 + 1);                     \
  TR(m.wg, rho * 8 + 1);
#define G1(dst, j, P)                       \
  TR(m.wg, rho * 8 + 2);                    \
  TL(ltb, ((j) ^ 2) * 5 + 2);               \
  P(); WG_WAIT0(); rfence(D2);              \
  WG_FENCE();                               \
  gemm6<true, 768>(dst, A1, dW1 + (j) * 192); \
  tok_pass(); P();                          \
  TL(ltb, ((j) ^ 2) * 5 + 3);               \
  TR(m.wg, rho * 8 + 3);
#define ROUND_END(dst, j)                   \
  TR(m.wg, rho * 8 + 4);                    \
  TL(ltb, (j) * 5 + 4);                     \
  PIN(); WG_WAIT0(); rfence(dst); rho++;
#define GA 10
#define GB 12
#define GC 12
#define GD 10
#pragma unroll 1
  for (int i = 0;; i++) {
    uint32_t g1[24], d2[24], g2[24], d3[24], g3[24], d0[24];
    G2(true, g, 0)
    gelu<0, GA>(g1, d);
    G1(d2, 2, PIN)
    ln_sums(cn, st);
    gelu<GA, 24>(g1, d);
    PIN();
    ln_shfl(st, 1);
    ROUND_END(d2, 0)

    G2(false, g1, 1)
    ln_fold(st);
    gelu<0, GB>(g2, d2);
    PIN();
    ln_shfl(st, 2);
    G1(d3, 3, PIN)
    ln_stats(st, bad, 2u << i);
    gelu<GB, 24>(g2, d2);
    ROUND_END(d3, 1)

    if (i == 15) {
      G2(false, g2, 2)
      tok_pass();
      gelu<0, 24>(g3, d3);
      PIN();
      x_load(m, cn);
      ROUND_END(D2, 2)
      G2(false, g3, 3)
      tok_pass();
      WG_WAIT0(); rfence(D2);
      epilogue<0, 6>(m, D2, cn);
      break;
    }
    G2(false, g2, 2)
    ln_apply(A1, cn, st);
    PIN();
    gelu<0, GC>(g3, d3);
    G1(d0, 0, PIN)
    gelu<GC, 24>(g3, d3);
    PIN();
    x_load(m, cn);
    ROUND_END(d0, 2)

    G2(false, g3, 3)
    gelu<0, GD>(g, d0);
    G1(d, 1, PIN)
    epilogue<0, 6>(m, D2, cn);
    gelu<GD, 24>(g, d0);
    PIN();
    asm volatile("fence.proxy.async.shared::cta;" ::: "memory");
    ln_load(m, cn);
    ROUND_END(d, 3)
    TLDUMP(m.warp == 0 && (i >> 1) == LTRACE, m.sb + OFF_LT + m.wg * 160 + (i & 1) * 80, 20)
  }
  out_store(m, 15);
  if (m.wg == 0) { tok_idle<0>(); tok_idle<1>(); }
  asm volatile("cp.async.bulk.wait_group 0;" ::: "memory");
  TR(m.wg, 1001);
  TRG(1021);
  return __reduce_or_sync(0xffffffffu, bad & 0xffffu);
}

struct ConvCtx {
  uint32_t sb;
  uint32_t a_raw, a_c;
  uint32_t peer_off;
  int rank, v, c0, r0, zero;
  const CUtensorMap* tm;
  const uint8_t* xsrc;
  uint8_t* optr;
};

__device__ __forceinline__ void raw_refill(const ConvCtx& c, int s) {
  if (s + 4 < NSTEP)
    tma_raw(c.sb + OFF_RAW + (s & 3) * RAW_BYTES, c.tm, 56 * c.rank - 8, c.c0 / 2 - 2, c.r0 - 3 + 2 * (s + 4), c.sb + BAR_RAW + 8 * (s & 3));
}
__device__ __forceinline__ void step_ready(const ConvCtx& c, int s) {
  const int nx = (s + 1) & 3, par = ((s + 1) >> 2) & 1;
  if (s + 1 < NSTEP) mbar_wait(c.sb + BAR_RAW + 8 * nx, par);
  if (s >= 7 && s < NSTEP) mbar_wait(c.sb + BAR_CEMPTY + 8 * (2 * (nx & 1) + (nx >> 1)), par);
}

__device__ __forceinline__ void prod_role(const ConvCtx& c) {
  asm volatile("barrier.cluster.wait.aligned;" ::: "memory");
  const bool lead = (threadIdx.x & 31) == 0;
#pragma unroll 1
  for (int s = 0; s < SIGMA; s++) {
    asm volatile("bar.sync %0, 160;" ::"r"(NB_PLAN + (s & 3)) : "memory");
    if (lead) raw_refill(c, s);
    __syncwarp();
  }
#pragma unroll 1
  for (int r = -c.rank; r < NROUND; r++) {
    const int n = r >> 1, s = r + c.rank + SIGMA;
    const uint32_t w = (n + 1) & 1;
    const uint32_t buf = c.sb + OFF_XRES + w * 12288;
    if (r == 4) TC(1);
    if (r == 56) TC(2);
    NB_SYNC(NB_PROD, 160);
    if (lead) {
      if (s > SIGMA) raw_refill(c, s - 1);
      if (!(r & 1)) {
        if (n >= 1 && n < 29) {
          const uint32_t e = c.sb + BAR_CEMPTY + 8 * (2 * c.rank + w);
          mbar_expect(c.sb + BAR_CFULL + 8 * w, 12288);
          asm volatile("mbarrier.arrive.shared::cluster.b64 _, [%0], 4;" ::"r"(e) : "memory");
          asm volatile("mbarrier.arrive.shared::cluster.b64 _, [%0], 4;" ::"r"(e + c.peer_off) : "memory");
        }
        if (n >= 3 && n < 33) {
          uint8_t* dst = c.optr + (size_t)(n - 3) * (4 * IMG * CH * 2);
          asm volatile("cp.async.bulk.global.shared::cta.bulk_group [%0], [%1], 6144;" ::"l"(dst), "r"(buf) : "memory");
          asm volatile("cp.async.bulk.global.shared::cta.bulk_group [%0], [%1], 6144;" ::"l"(dst + IMG * CH * 2), "r"(buf + 6144) : "memory");
          asm volatile("cp.async.bulk.commit_group;" ::: "memory");
        }
      }
    }
    __syncwarp();
    step_ready(c, s);
    const int u = (r & 1) ? n - 1 : n + 2;
    if (u >= ((r & 1) ? 0 : 4) && u < 32) mbar_wait(c.sb + ((r & 1) ? BAR_XFULL : BAR_CFULL) + 8 * (u & 1), (u >> 1) & 1);
    NB_ARRIVE(NB_OPEN, 416);
    if (lead && !(r & 1) && n >= 1 && n < 33) {
      const uint8_t* src = c.xsrc + (size_t)(n - 1) * (4 * IMG * CH * 2);
      asm volatile("cp.async.bulk.wait_group.read 0;" ::: "memory");
      mbar_expect(c.sb + BAR_XFULL + 8 * w, 12288);
      bulk_load(buf, src, 6144, c.sb + BAR_XFULL + 8 * w);
      bulk_load(buf + 6144, src + IMG * CH * 2, 6144, c.sb + BAR_XFULL + 8 * w);
    }
    __syncwarp();
  }
  asm volatile("cp.async.bulk.wait_group 0;" ::: "memory");
}

__device__ __forceinline__ void conv_ld8(uint32_t a, uint32_t (&r)[6][6]) {
#pragma unroll
  for (int j = 0; j < 6; j++)
    asm volatile("ld.shared.v4.b32 {%0,%1,%2,%3}, [%4];"
                 : "=r"(r[j][0]), "=r"(r[j][1]), "=r"(r[j][2]), "=r"(r[j][3])
                 : "r"(a + (j >> 1) * 112 + (j & 1) * RAW_PLANE)
                 : "memory");
}
__device__ __forceinline__ void conv_ld4(uint32_t a, uint32_t (&r)[6][6]) {
#pragma unroll
  for (int j = 0; j < 6; j++)
    asm volatile("ld.shared.v2.b32 {%0,%1}, [%2];" : "=r"(r[j][4]), "=r"(r[j][5]) : "r"(a + (j >> 1) * 112 + (j & 1) * RAW_PLANE) : "memory");
}
template <int LO, int HI>
__device__ __forceinline__ void conv_frags(uint32_t zero, const uint32_t (&r)[6][6], uint32_t (&A)[12][4]) {
#pragma unroll
  for (int ch = LO; ch < HI; ch++) {
    const uint32_t sel = (ch & 1) ? 0x7632 : 0x5410;
    A[ch][0] = __byte_perm(r[0][ch >> 1], r[1][ch >> 1], sel);
    A[ch][1] = __byte_perm(r[2][ch >> 1], r[3][ch >> 1], sel);
    A[ch][2] = A[ch][1] ^ zero;
    A[ch][3] = __byte_perm(r[4][ch >> 1], r[5][ch >> 1], sel);
    rfence(A[ch]);
  }
}
__device__ __forceinline__ void hmma_acc(uint32_t (&v)[4], const uint32_t (&a)[4], const uint32_t* b) {
  asm volatile("mma.sync.aligned.m16n8k16.row.col.f32.bf16.bf16.f32 {%0,%1,%2,%3}, {%4,%5,%6,%7}, {%8,%9}, {%0,%1,%2,%3};"
               : "+r"(v[0]), "+r"(v[1]), "+r"(v[2]), "+r"(v[3])
               : "r"(a[0]), "r"(a[1]), "r"(a[2]), "r"(a[3]), "r"(b[0]), "r"(b[1]));
}
__device__ __forceinline__ void hmma_new(uint32_t (&a)[4], const uint32_t* b) {
  asm volatile("mma.sync.aligned.m16n8k16.row.col.f32.bf16.bf16.f32 {%0,%1,%2,%3}, {%0,%1,%2,%3}, {%4,%5}, {%6,%6,%6,%6};"
               : "+r"(a[0]), "+r"(a[1]), "+r"(a[2]), "+r"(a[3])
               : "r"(b[0]), "r"(b[1]), "f"(0.f));
}

#define PRE 4
template <int S4, bool GATED, bool MORE>
__device__ __forceinline__ void conv_step(const ConvCtx& c, int s, uint32_t (&K)[12], uint32_t (&V)[12][4], const uint32_t (&B)[12][4],
                                          uint32_t (&A)[12][4]) {
  const int nx = GATED ? (((s + 1) & 2) | ((S4 + 1) & 1)) : ((S4 + 1) & 3);
  uint32_t r[6][6];
  TL(ltb, 0);
  TR(2, s * 8);
  PIN();
  if (GATED) {
    NB_SYNC(NB_OPEN, 416);
  } else {
    NB_ARRIVE(NB_PLAN + S4, 160);
    mbar_wait(c.sb + BAR_RAW + 8 * nx, ((s + 1) >> 2) & 1);
    if (S4 == 3 && s == 7) mbar_wait(c.sb + BAR_CEMPTY, 0);
  }
  if (MORE && (PRE & 8)) conv_ld8(c.a_raw + nx * RAW_BYTES, r);
  if (MORE && (PRE & 4)) conv_ld4(c.a_raw + nx * RAW_BYTES + 64 - 8 * c.v, r);
  PIN();
  TL(ltb, 1);
  TR(2, s * 8 + 1);
#define EARLY 6
  uint32_t z1;
#pragma unroll
  for (int ch = 0; ch < 12; ch++) hmma_acc(V[ch], A[ch], &B[ch][2]);
#pragma unroll
  for (int ch = 0; ch < 12 - EARLY; ch++) hmma_new(A[ch], &B[ch][0]);
  z1 = clock_pin();
  if (GATED) NB_ARRIVE(NB_CLOSE, 256);
  if (EARLY) {
#pragma unroll
    for (int ch = 12 - EARLY; ch < 12; ch++) hmma_new(A[ch], &B[ch][0]);
  }
  PIN();
  TL(ltb, 2);
  TR(2, s * 8 + 2);
#pragma unroll
  for (int q = 0; q < 12; q++) {
    const int ch = q & ~1, h = 2 * (q & 1);
    asm("add.rn.f16x2 %0, %0, %1;" : "+r"(K[q]) : "r"(pack_f16(__uint_as_float(V[ch][h + 1]), __uint_as_float(V[ch + 1][h]))));
  }
  if (GATED || s >= 3) {
    const uint32_t off = ((nx & 1) == c.rank) ? 0u : c.peer_off;
    const uint32_t dst = laneid() * 16 + (c.a_c + off + (nx >> 1) * C_BYTES), bar = c.sb + off + BAR_CFULL + 8 * (nx >> 1);
#pragma unroll
    for (int q = 0; q < 3; q++)
      asm volatile("st.async.weak.shared::cluster.mbarrier::complete_tx::bytes.v4.b32 [%0], {%1,%2,%3,%4}, [%5];" ::"r"(dst + q * 512),
                   "r"(K[4 * q]), "r"(K[4 * q + 1]), "r"(K[4 * q + 2]), "r"(K[4 * q + 3]), "r"(bar)
                   : "memory");
  }
  PIN();
#pragma unroll
  for (int q = 0; q < 12; q++) {
    const int ch = q & ~1, h = 2 * (q & 1);
    K[q] = pack_f16(__uint_as_float(V[ch][h]), __uint_as_float(V[ch + 1][h + 1]));
  }
  rfence(K);
  const uint32_t zero = c.zero & z1;
  if (MORE && PRE == 4) conv_frags<8, 12>(zero, r, V);
  if (MORE && PRE == 8) conv_frags<0, 8>(zero, r, V);
  PIN();
  TR(2, s * 8 + 3);
  if (MORE && PRE == 4) {
    conv_ld8(c.a_raw + nx * RAW_BYTES, r);
    conv_frags<0, 8>(zero, r, V);
  }
  if (MORE && PRE == 8) {
    conv_ld4(c.a_raw + nx * RAW_BYTES + 64 - 8 * c.v, r);
    conv_frags<8, 12>(zero, r, V);
  }
  PIN();
  TL(ltb, 4);
  TR(2, s * 8 + 4);
  TLDUMP(c.v == 0 && lr >= 0 && lr < 10, c.sb + OFF_LT + 320 + lr * 20, 5)
}

__device__ __forceinline__ void conv_role(const ConvCtx& c) {
  const int lane = threadIdx.x & 31, g = lane >> 2, t = lane & 3;
  uint32_t B[12][4];
  {
    const int dc = (g >> 1) & 1, ro = g >> 2, rk = t >> 1;
    const int i0 = 4 * (g & 1) + rk - ro, j0 = 4 * (t & 1) - dc;
    const uint32_t base = c.sb + OFF_XRES + 96 * c.rank + (i0 * 7 + j0) * 192;
    TR(2, 1005);
    mbar_wait(c.sb + BAR_W + 16, 0);
    TR(2, 1006);
#pragma unroll
    for (int b = 0; b < 2; b++) {
      uint32_t w[4][6];
#pragma unroll
      for (int k = 0; k < 4; k++) {
        const int ok = (unsigned)(i0 + 2 * b) < 7u && (unsigned)(j0 + k) < 7u;
#pragma unroll
        for (int q = 0; q < 6; q++) w[k][q] = 0;
        asm volatile(
            "{\n.reg .pred p;\nsetp.ne.s32 p, %8, 0;\n@p ld.shared.v4.b32 {%0,%1,%2,%3}, [%6];\n@p ld.shared.v2.b32 {%4,%5}, [%7];\n}\n"
            : "+r"(w[k][0]), "+r"(w[k][1]), "+r"(w[k][2]), "+r"(w[k][3]), "+r"(w[k][4]), "+r"(w[k][5])
            : "r"(base + (b * 14 + k) * 192 + 16 * c.v), "r"(base + (b * 14 + k) * 192 + 64 + 8 * c.v), "r"(ok)
            : "memory");
      }
#pragma unroll
      for (int q = 0; q < 6; q++) {
        B[2 * q][2 * b] = __byte_perm(w[0][q], w[1][q], 0x5410);
        B[2 * q][2 * b + 1] = __byte_perm(w[2][q], w[3][q], 0x5410);
        B[2 * q + 1][2 * b] = __shfl_xor_sync(0xffffffffu, __byte_perm(w[0][q], w[1][q], 0x7632), 4);
        B[2 * q + 1][2 * b + 1] = __shfl_xor_sync(0xffffffffu, __byte_perm(w[2][q], w[3][q], 0x7632), 4);
      }
    }
  }
  TR(2, 1004);
  asm volatile("barrier.cluster.wait.aligned;" ::: "memory");
  uint32_t K1[12], K2[12], V[12][4];
#pragma unroll
  for (int ch = 0; ch < 12; ch++) {
    K1[ch] = K2[ch] = 0;
#pragma unroll
    for (int k = 0; k < 4; k++) V[ch][k] = 0;
  }
  uint32_t A[12][4];
  {
    uint32_t r[6][6];
    TR(2, 1007);
    mbar_wait(c.sb + BAR_RAW, 0);
    TR(2, 1008);
    conv_ld8(c.a_raw, r);
    conv_ld4(c.a_raw + 64 - 8 * c.v, r);
    conv_frags<0, 12>(c.zero, r, A);
  }
  NB_ARRIVE(NB_CLOSE, 256);
  static_assert(SIGMA == 8, "");
#pragma unroll 1
  for (int s = 0; s < SIGMA; s += 4) {
    conv_step<0, false, true>(c, s, K1, V, B, A);
    conv_step<1, false, true>(c, s + 1, K2, A, B, V);
    conv_step<2, false, true>(c, s + 2, K1, V, B, A);
    conv_step<3, false, true>(c, s + 3, K2, A, B, V);
  }
#pragma unroll 1
  for (int s = SIGMA; s < NSTEP - 1; s += 2) {
    conv_step<0, true, true>(c, s, K1, V, B, A);
    conv_step<1, true, true>(c, s + 1, K2, A, B, V);
  }
  conv_step<2, true, false>(c, NSTEP - 1, K1, V, B, A);
#pragma unroll 1
  for (int r = NSTEP - SIGMA - c.rank; r < NROUND - 1; r++) {
    NB_SYNC(NB_OPEN, 416);
    NB_ARRIVE(NB_CLOSE, 256);
  }
  NB_SYNC(NB_OPEN, 416);
}

__global__ void __cluster_dims__(2, 1, 1) __launch_bounds__(512, 1)
convnext_kernel(const __grid_constant__ CUtensorMap tm, const __nv_bfloat16* __restrict__ x, const __nv_bfloat16* __restrict__ dw,
                const __nv_bfloat16* __restrict__ w1, const __nv_bfloat16* __restrict__ w2, __nv_bfloat16* __restrict__ out,
                int zero) {
  extern __shared__ __align__(1024) uint8_t smem[];
  const uint32_t sb = (uint32_t)__cvta_generic_to_shared(smem);
  const int tid = threadIdx.x, lane = tid & 31;
  const int wid = __shfl_sync(0xffffffffu, tid >> 5, 0);
  const int rank = blockIdx.x & 1, cl = blockIdx.x >> 1;
  const int c0 = (cl & 15) * 32, r0 = (cl >> 4) * 128;
  const uint32_t peer_off = mapa(sb, rank ^ 1) - sb;

  TR(wid >> 2, 1002);
  TRG(1020);
  if (tid == 384) {
    asm volatile("prefetch.tensormap [%0];" ::"l"(&tm) : "memory");
    for (int i = 0; i < 3; i++) mbar_init(sb + BAR_W + 8 * i, 1);
    for (int i = 0; i < 4; i++) mbar_init(sb + BAR_RAW + 8 * i, 1);
    asm volatile("fence.mbarrier_init.release.cluster;" ::: "memory");
  }
  if (tid == 128) {
    for (int i = 0; i < 2; i++) mbar_init(sb + BAR_CFULL + 8 * i, 1);
    for (int i = 0; i < 4; i++) mbar_init(sb + BAR_CEMPTY + 8 * i, 4);
    for (int i = 0; i < 2; i++) mbar_init(sb + BAR_XFULL + 8 * i, 1);
    for (int i = 0; i < 2; i++) mbar_expect(sb + BAR_CFULL + 8 * i, 12288);
    asm volatile("fence.mbarrier_init.release.cluster;" ::: "memory");
  }
  __syncthreads();
  asm volatile("barrier.cluster.arrive.relaxed.aligned;" ::: "memory");

  TR(wid >> 2, 1003);
  if (wid < 8) {
    MlpCtx m;
    m.sb = sb; m.wg = wid >> 2; m.warp = wid & 3; m.rank = rank; m.peer_off = peer_off; m.zero = zero;
    m.optr = reinterpret_cast<uint8_t*>(out) + ((size_t)(r0 + 4 * m.wg + 2 * rank) * IMG + c0 + 8 * m.warp) * (CH * 2);
    m.caddr = sb + OFF_C + m.wg * C_BYTES + m.warp * 128 + (lane & 3) * (6 * 512 + 32) + (lane >> 2) * 16;
    m.xaddr = sb + OFF_XRES + m.wg * 12288 + m.warp * 1536 + ((lane >> 3) & 1) * 6144 + ((lane >> 4) * 4 + ((lane >> 2) & 1)) * 192 + (lane & 3) * 16;
    m.unscale = 0;
    asm volatile("setmaxnreg.inc.sync.aligned.u32 %0;" ::"n"(REG_MLP));
    const uint32_t bad = mlp_role(m);
    asm volatile("barrier.cluster.arrive.relaxed.aligned;\nbarrier.cluster.wait.aligned;" ::: "memory");
    if (bad) {
      asm volatile("fence.proxy.async;" ::: "memory");
      for (int i = 0; i < 16; i++)
        if (bad >> i & 1)
          slow_tile(x, dw, w1, w2, out, r0 + 8 * i + 4 * m.wg + 2 * rank, c0 + 8 * m.warp,
                    reinterpret_cast<float*>(smem + OFF_XRES + wid * 3072));
    }
  } else {
    ConvCtx c;
    c.sb = sb; c.rank = rank; c.v = wid - 8; c.c0 = c0; c.r0 = r0; c.zero = zero; c.tm = &tm;
    c.peer_off = peer_off;
    c.xsrc = reinterpret_cast<const uint8_t*>(x) + ((size_t)(r0 + 2 * rank) * IMG + c0) * (CH * 2);
    c.optr = reinterpret_cast<uint8_t*>(out) + ((size_t)(r0 + 2 * rank) * IMG + c0) * (CH * 2);
    const int g = lane >> 2, t = lane & 3;
    c.a_raw = sb + OFF_RAW + ((t >> 1) * 19 + 2 * (g + (t & 1))) * 112 + (1 - rank) * 16 + 16 * c.v;
    const int q0 = 12 * rank + 3 * c.v;
    c.a_c = sb + OFF_C + q0 * 512 + (q0 / 6) * 32;
    if (wid < 12) {
      asm volatile("setmaxnreg.inc.sync.aligned.u32 %0;" ::"n"(REG_CONV));
      conv_role(c);
      __syncwarp();
      asm volatile("barrier.cluster.arrive.relaxed.aligned;\nbarrier.cluster.wait.aligned;\nexit;" ::: "memory");
    } else {
      asm volatile("setmaxnreg.dec.sync.aligned.u32 24;");
      if (wid == 13) TC(0);
      if (wid == 12) {
        if (lane == 0) {
          mbar_expect(sb + BAR_W + 16, 49 * CH * 2);
          bulk_load(sb + OFF_XRES, dw, 49 * CH * 2, sb + BAR_W + 16);
          TR(3, 1004);
#pragma unroll 1
          for (int h = 0; h < 2; h++) {
            raw_refill(c, 2 * h - 4);
            raw_refill(c, 2 * h - 3);
            const uint8_t* w = reinterpret_cast<const uint8_t*>(h ? w2 : w1);
            mbar_expect(sb + BAR_W + 8 * h, 73728);
            for (int i = 0; i < 2; i++) bulk_load(sb + h * OFF_W2 + i * 36864, w + i * 36864, 36864, sb + BAR_W + 8 * h);
            TR(3, 1005 + h);
          }
        }
        __syncwarp();
        prod_role(c);
        asm volatile("barrier.cluster.arrive.relaxed.aligned;\nbarrier.cluster.wait.aligned;" ::: "memory");
        TC(3);
      }
    }
  }
}

typedef CUresult (*EncodeFn)(CUtensorMap*, CUtensorMapDataType, cuuint32_t, void*, const cuuint64_t*, const cuuint64_t*,
                             const cuuint32_t*, const cuuint32_t*, CUtensorMapInterleave, CUtensorMapSwizzle,
                             CUtensorMapL2promotion, CUtensorMapFloatOOBfill);

}

extern "C" void kernel_launch(void* const* d_in, const int* in_sizes, int n_in, void* d_out, int out_size) {
  const __nv_bfloat16* x = (const __nv_bfloat16*)d_in[0];
  const __nv_bfloat16* dw = (const __nv_bfloat16*)d_in[1];
  const __nv_bfloat16* w1 = (const __nv_bfloat16*)d_in[2];
  const __nv_bfloat16* w2 = (const __nv_bfloat16*)d_in[3];
  __nv_bfloat16* out = (__nv_bfloat16*)d_out;

  static EncodeFn encode = nullptr;
  if (!encode) {
    cudaDriverEntryPointQueryResult st;
    void* fn = nullptr;
    cudaGetDriverEntryPoint("cuTensorMapEncodeTiled", &fn, cudaEnableDefault, &st);
    encode = (EncodeFn)fn;
    cudaFuncSetAttribute(convnext_kernel, cudaFuncAttributeMaxDynamicSharedMemorySize, SMEM_BYTES);
  }
  CUtensorMap tm;
  cuuint64_t dims[4] = {CH, IMG / 2, IMG, 2};
  cuuint64_t strides[3] = {CH * 4, (cuuint64_t)IMG * CH * 2, CH * 2};
  cuuint32_t box[4] = {56, 19, 2, 1};
  cuuint32_t es[4] = {1, 1, 1, 1};
  encode(&tm, CU_TENSOR_MAP_DATA_TYPE_BFLOAT16, 4, (void*)x, dims, strides, box, es, CU_TENSOR_MAP_INTERLEAVE_NONE,
         CU_TENSOR_MAP_SWIZZLE_NONE, CU_TENSOR_MAP_L2_PROMOTION_L2_128B, CU_TENSOR_MAP_FLOAT_OOB_FILL_NONE);
  convnext_kernel<<<128, 512, SMEM_BYTES>>>(tm, x, dw, w1, w2, out, 0);
}
```

```cpp
#include <cuda_runtime.h>
#include <cuda_bf16.h>
#include <cuda.h>
#include <stdint.h>

#define PROMO CU_TENSOR_MAP_L2_PROMOTION_L2_128B
#define CTX 12288
#define CCNT 1
namespace {

constexpr int IMG = 512, CH = 96;
constexpr int NSTEP = 67;
constexpr int SIGMA = 8;
constexpr int NROUND = 68;

constexpr uint32_t OFF_W1 = 0;
constexpr uint32_t OFF_W2 = 73728;
constexpr uint32_t OFF_RAW = 147456;
#define PITCH 112
constexpr uint32_t RAW_PLANE = (38 * PITCH + 127) / 128 * 128;
constexpr uint32_t RAW_BYTES = 2 * RAW_PLANE;
constexpr uint32_t RAW_TX = 2 * 2 * 19 * PITCH;
constexpr uint32_t OFF_XRES = OFF_RAW + 4 * RAW_BYTES;
constexpr uint32_t OFF_C = OFF_XRES + 2 * 12288;
constexpr uint32_t C_BYTES = 12288;
constexpr uint32_t OFF_BAR = OFF_C + 2 * C_BYTES;
constexpr uint32_t BAR_RAW = OFF_BAR;
constexpr uint32_t BAR_CFULL = OFF_BAR + 32;
constexpr uint32_t BAR_CEMPTY = OFF_BAR + 48;
constexpr uint32_t BAR_XFULL = OFF_BAR + 80;
constexpr uint32_t BAR_W = OFF_BAR + 96;
constexpr uint32_t OFF_NRM = OFF_BAR + 160;
constexpr uint32_t OFF_LT = OFF_BAR + 160;
constexpr uint32_t SMEM_BYTES = OFF_BAR + 160 + 600;

constexpr float GELU_A = 0.32918364f;
constexpr uint32_t GELU_K2 = 0x40d940d9u;

constexpr int NB_CLOSE = 1, NB_SEC = 6  , NB_OPEN = 3, NB_PROD = 2, NB_PLAN = 4, NB_PREP = 5, NB_WG = 8  ;
#define REG_MLP 144
constexpr int REG_CONV = 488 - 2 * REG_MLP;

#define WG_FENCE() asm volatile("wgmma.fence.sync.aligned;" ::: "memory")
#define WG_COMMIT() asm volatile("wgmma.commit_group.sync.aligned;" ::: "memory")
#define WG_WAIT0() asm volatile("wgmma.wait_group.sync.aligned 0;" ::: "memory")
#define WG_WAIT1() asm volatile("wgmma.wait_group.sync.aligned 1;" ::: "memory")
#define PIN() asm volatile("pmevent 0;" ::: "memory")
#define NB_SYNC(id, n) asm volatile("bar.sync %0, %1;" ::"n"(id), "n"(n) : "memory")
#define NB_ARRIVE(id, n) asm volatile("bar.arrive %0, %1;" ::"n"(id), "n"(n) : "memory")

#define TS(idx)
#define TC(k)
#define TF(k)
#define TL(base, off)
#define TLDUMP(cond, base, n)

#define R24(c, d)                                                                                        \
  c(d[0]), c(d[1]), c(d[2]), c(d[3]), c(d[4]), c(d[5]), c(d[6]), c(d[7]), c(d[8]), c(d[9]), c(d[10]),    \
      c(d[11]), c(d[12]), c(d[13]), c(d[14]), c(d[15]), c(d[16]), c(d[17]), c(d[18]), c(d[19]), c(d[20]), \
      c(d[21]), c(d[22]), c(d[23])
#define WG_TXT(sd)                                                                             \
  "wgmma.mma_async.sync.aligned.m64n96k16.f16.f16.f16 "                                        \
  "{%0,%1,%2,%3,%4,%5,%6,%7,%8,%9,%10,%11,%12,%13,%14,%15,%16,%17,%18,%19,%20,%21,%22,%23}, " \
  "{%24,%25,%26,%27}, %28, " sd ", 1, 1, 1;\n"

__device__ __forceinline__ void wg_acc(uint32_t (&d)[24], const uint32_t* a, uint64_t db) {
  asm volatile(WG_TXT("1") : R24("+r", d) : "r"(a[0]), "r"(a[1]), "r"(a[2]), "r"(a[3]), "l"(db));
}
__device__ __forceinline__ void wg_init(uint32_t (&d)[24], const uint32_t* a, uint64_t db) {
  asm volatile(WG_TXT("0") : R24("=r", d) : "r"(a[0]), "r"(a[1]), "r"(a[2]), "r"(a[3]), "l"(db));
}
template <int N>
__device__ __forceinline__ void rfence(uint32_t (&d)[N]) {
#pragma unroll
  for (int i = 0; i < N; i++) asm volatile("" : "+r"(d[i])::"memory");
}
template <bool INIT, int KSTRIDE>
__device__ __forceinline__ void gemm6(uint32_t (&d)[24], const uint32_t (&a)[24], uint64_t db) {
#pragma unroll
  for (int k = 0; k < 6; k++) {
    if (INIT && k == 0) wg_init(d, &a[0], db);
    else wg_acc(d, &a[4 * k], db + k * KSTRIDE);
  }
  WG_COMMIT();
}

__device__ __forceinline__ void mbar_init(uint32_t bar, uint32_t cnt) {
  asm volatile("mbarrier.init.shared::cta.b64 [%0], %1;" ::"r"(bar), "r"(cnt) : "memory");
}
__device__ __forceinline__ void mbar_expect(uint32_t bar, uint32_t bytes) {
  asm volatile("mbarrier.arrive.expect_tx.shared::cta.b64 _, [%0], %1;" ::"r"(bar), "r"(bytes) : "memory");
}
__device__ __forceinline__ void mbar_arrive_cluster(uint32_t bar) {
  asm volatile("mbarrier.arrive.shared::cluster.b64 _, [%0];" ::"r"(bar) : "memory");
}
__device__ __forceinline__ bool mbar_try(uint32_t bar, uint32_t parity) {
  uint32_t ok;
  asm volatile(
      "{\n.reg .pred p;\nmbarrier.try_wait.parity.shared::cta.b64 p, [%1], %2;\nselp.u32 %0, 1, 0, p;\n}\n"
      : "=r"(ok)
      : "r"(bar), "r"(parity)
      : "memory");
  return ok;
}
__device__ __forceinline__ bool mbar_test(uint32_t bar, uint32_t parity) {
  uint32_t ok;
  asm volatile(
      "{\n.reg .pred p;\nmbarrier.test_wait.parity.shared::cta.b64 p, [%1], %2;\nselp.u32 %0, 1, 0, p;\n}\n"
      : "=r"(ok)
      : "r"(bar), "r"(parity)
      : "memory");
  return ok;
}
__device__ __forceinline__ void mbar_wait(uint32_t bar, uint32_t parity) {
  if (__builtin_expect(mbar_try(bar, parity), 1)) return;
#pragma unroll 1
  for (uint32_t n = 0; n < (1u << 16) && !mbar_try(bar, parity); n++) {}
}
__device__ __forceinline__ uint32_t mapa(uint32_t addr, uint32_t rank) {
  uint32_t r;
  asm("mapa.shared::cluster.u32 %0, %1, %2;" : "=r"(r) : "r"(addr), "r"(rank));
  return r;
}
__device__ __forceinline__ void tma_raw(uint32_t dst, const CUtensorMap* tm, int c, int w2, int h, uint32_t bar) {
  mbar_expect(bar, RAW_TX);
#pragma unroll
  for (int e = 0; e < 2; e++)
    asm volatile(
        "cp.async.bulk.tensor.4d.shared::cluster.global.mbarrier::complete_tx::bytes [%0], [%1, {%2, %3, %4, %5}], [%6];"
        ::"r"(dst + e * RAW_PLANE), "l"(tm), "r"(c), "r"(w2 + e), "r"(h), "r"(1 - e), "r"(bar)
        : "memory");
}
__device__ __forceinline__ void bulk_load(uint32_t dst, const void* src, uint32_t bytes, uint32_t bar) {
  asm volatile("cp.async.bulk.shared::cluster.global.mbarrier::complete_tx::bytes [%0], [%1], %2, [%3];" ::"r"(dst),
               "l"(src), "r"(bytes), "r"(bar)
               : "memory");
}
__device__ __forceinline__ void bulk_load_last(uint32_t dst, const void* src, uint32_t bytes, uint32_t bar) {
  asm volatile(
      "{\n.reg .b64 pol;\ncreatepolicy.fractional.L2::evict_first.b64 pol, 1.0;\n"
      "cp.async.bulk.shared::cluster.global.mbarrier::complete_tx::bytes.L2::cache_hint [%0], [%1], %2, [%3], pol;\n}\n" ::"r"(dst),
      "l"(src), "r"(bytes), "r"(bar)
      : "memory");
}
__device__ __forceinline__ uint32_t pack_bf16(float lo, float hi) {
  uint32_t r;
  asm("cvt.rn.bf16x2.f32 %0, %1, %2;" : "=r"(r) : "f"(hi), "f"(lo));
  return r;
}
__device__ __forceinline__ uint32_t pack_f16(float lo, float hi) {
  uint32_t r;
  asm("cvt.rn.f16x2.f32 %0, %1, %2;" : "=r"(r) : "f"(hi), "f"(lo));
  return r;
}
__device__ __forceinline__ float bf_lo(uint32_t v) { return __uint_as_float(v << 16); }
__device__ __forceinline__ float bf_hi(uint32_t v) { return __uint_as_float(v & 0xffff0000u); }
__device__ __forceinline__ uint32_t bf_add(uint32_t a, uint32_t b) {
  uint32_t r;
  asm("add.rn.bf16x2 %0, %1, %2;" : "=r"(r) : "r"(a), "r"(b));
  return r;
}
__device__ __forceinline__ uint32_t bf_mul(uint32_t a, uint32_t b) {
  uint32_t r;
  asm("mul.rn.bf16x2 %0, %1, %2;" : "=r"(r) : "r"(a), "r"(b));
  return r;
}
__device__ __forceinline__ uint32_t bf_fma(uint32_t a, uint32_t b, uint32_t c) {
  uint32_t r;
  asm("fma.rn.bf16x2 %0, %1, %2, %3;" : "=r"(r) : "r"(a), "r"(b), "r"(c));
  return r;
}

__device__ __forceinline__ uint32_t h_add(uint32_t a, uint32_t b) {
  uint32_t r;
  asm("add.rn.f16x2 %0, %1, %2;" : "=r"(r) : "r"(a), "r"(b));
  return r;
}
__device__ __forceinline__ uint32_t h_mul(uint32_t a, uint32_t b) {
  uint32_t r;
  asm("mul.rn.f16x2 %0, %1, %2;" : "=r"(r) : "r"(a), "r"(b));
  return r;
}
__device__ __forceinline__ uint32_t h_fma(uint32_t a, uint32_t b, uint32_t c) {
  uint32_t r;
  asm("fma.rn.f16x2 %0, %1, %2, %3;" : "=r"(r) : "r"(a), "r"(b), "r"(c));
  return r;
}
__device__ __forceinline__ float h_sum(uint32_t v) {
  float lo, hi;
  asm("{\n.reg .b16 l, h;\nmov.b32 {l, h}, %2;\ncvt.f32.f16 %0, l;\ncvt.f32.f16 %1, h;\n}\n" : "=f"(lo), "=f"(hi) : "r"(v));
  return lo + hi;
}
__device__ __forceinline__ void lds128(uint32_t (&v)[4], uint32_t a) {
  asm volatile("ld.shared.v4.b32 {%0,%1,%2,%3}, [%4];" : "=r"(v[0]), "=r"(v[1]), "=r"(v[2]), "=r"(v[3]) : "r"(a) : "memory");
}

template <int LO, int HI>
__device__ __forceinline__ void gelu(uint32_t (&o)[24], const uint32_t (&d)[24]) {
#pragma unroll
  for (int qq = LO; qq < HI; qq++) {
    const int q = (qq + 4) % 24;
    uint32_t t, u;
    asm("fma.rn.f16x2 %0, %1, %1, %2;" : "=r"(t) : "r"(d[q]), "r"(GELU_K2));
    asm("mul.rn.f16x2 %0, %1, %2;" : "=r"(u) : "r"(d[q]), "r"(t));
    asm("tanh.approx.f16x2 %0, %1;" : "=r"(t) : "r"(u));
    asm("fma.rn.f16x2 %0, %1, %2, %1;" : "=r"(o[q]) : "r"(d[q]), "r"(t));
  }
}

__device__ __forceinline__ uint32_t laneid() {
  uint32_t l;
  asm volatile("mov.u32 %0, %%laneid;" : "=r"(l));
  return l;
}

__device__ __forceinline__ bool elect_one() {
  uint32_t p;
  asm volatile("{\n.reg .pred p;\nelect.sync _|p, 0xffffffff;\nselp.u32 %0, 1, 0, p;\n}\n" : "=r"(p));
  return p;
}

__device__ __forceinline__ uint32_t clock_pin() {
  uint32_t t;
  asm volatile("mov.u32 %0, %%clock;" : "=r"(t)::"memory");
  return t;
}

struct MlpCtx {
  uint32_t sb;
  uint32_t caddr;
  uint32_t xaddr;
  uint32_t unscale;
  uint32_t peer_off;
  int wg, warp, rank, zero;
  uint8_t* optr;
};

__device__ __forceinline__ void ln_wait(const MlpCtx& m, int i) { mbar_wait(m.sb + BAR_CFULL + 8 * m.wg, i & 1); }
__device__ __forceinline__ void ln_load(const MlpCtx& m, uint32_t (&c)[24]) {
#pragma unroll
  for (int p = 0; p < 6; p++)
    asm volatile("ld.shared.v4.b32 {%0,%1,%2,%3}, [%4];"
                 : "=r"(c[4 * p]), "=r"(c[4 * p + 1]), "=r"(c[4 * p + 2]), "=r"(c[4 * p + 3])
                 : "r"(m.caddr + p * 2048)
                 : "memory");
}
__device__ __forceinline__ void ln_shfl(float (&st)[8], int mask) {
#pragma unroll
  for (int k = 0; k < 4; k++) st[4 + k] = __shfl_xor_sync(0xffffffffu, st[k], mask);
}
__device__ __forceinline__ void ln_fold(float (&st)[8]) {
#pragma unroll
  for (int k = 0; k < 4; k++) st[k] += st[4 + k];
}
__device__ __forceinline__ void ln_sums(const uint32_t (&c)[24], float (&st)[8]) {
#pragma unroll
  for (int r = 0; r < 2; r++) {
    uint32_t s0 = h_add(c[r], c[r + 2]), s1 = h_add(c[r + 4], c[r + 6]), s2 = h_add(c[r + 8], c[r + 10]);
    uint32_t s3 = h_add(c[r + 12], c[r + 14]), s4 = h_add(c[r + 16], c[r + 18]), s5 = h_add(c[r + 20], c[r + 22]);
    s0 = h_add(s0, s1); s2 = h_add(s2, s3); s4 = h_add(s4, s5);
    st[r] = h_sum(h_add(h_add(s0, s2), s4));
    uint32_t q0 = h_mul(c[r], c[r]), q1 = h_mul(c[r + 2], c[r + 2]);
#pragma unroll
    for (int p = 2; p < 12; p += 2) {
      q0 = h_fma(c[2 * p + r], c[2 * p + r], q0);
      q1 = h_fma(c[2 * p + 2 + r], c[2 * p + 2 + r], q1);
    }
    st[2 + r] = h_sum(h_add(q0, q1));
  }
}
__device__ __forceinline__ void ln_release(const MlpCtx& m) {
  const uint32_t e = m.sb + BAR_CEMPTY + 8 * (2 * m.rank + m.wg);
  asm volatile(
      "{\n.reg .pred p, q;\nelect.sync _|p, 0xffffffff;\nsetp.eq.and.s32 q, %3, 0, p;\n"
      "@q mbarrier.arrive.expect_tx.shared::cta.b64 _, [%0], %4;\n"
      "@p mbarrier.arrive.shared::cluster.b64 _, [%1];\n"
      "@p mbarrier.arrive.shared::cluster.b64 _, [%2];\n}\n" ::"r"(m.sb + BAR_CFULL + 8 * m.wg),
      "r"(e), "r"(e + m.peer_off), "r"(m.warp), "n"(CTX)
      : "memory");
}
__device__ __forceinline__ void ln_stats(float (&st)[8], uint32_t& bad, uint32_t bit) {
  bool ok = true;
#pragma unroll
  for (int r = 0; r < 2; r++) {
    const float nm = (st[r] + st[4 + r]) * (-1.0f / 96.0f);
    const float e2 = fmaf(st[2 + r] + st[6 + r], 1.0f / 96.0f, 1e-5f);
    float rs;
    asm("rsqrt.approx.ftz.f32 %0, %1;" : "=f"(rs) : "f"(fmaf(-nm, nm, e2)));
    ok = ok && (rs * rs * e2 <= 17.0f) && (e2 >= 1.001e-5f);
    const float rr = rs * GELU_A, dd = rr * nm;
    st[r] = __uint_as_float(pack_f16(rr, rr));
    st[2 + r] = __uint_as_float(pack_f16(dd, dd));
  }
  if (!ok) bad |= bit;
}
__device__ __forceinline__ void ln_apply(uint32_t (&a)[24], const uint32_t (&c)[24], const float (&st)[8]) {
#pragma unroll
  for (int p = 0; p < 24; p++) {
    a[p] = h_fma(c[p], __float_as_uint(st[p & 1]), __float_as_uint(st[2 + (p & 1)]));
  }
}

__device__ __noinline__ void slow_tile(const __nv_bfloat16* x, const __nv_bfloat16* dw, const __nv_bfloat16* w1,
                                       const __nv_bfloat16* w2, __nv_bfloat16* out, int row0, int col0, float* buf) {
  const int lane = threadIdx.x & 31;
  for (int px = 0; px < 16; px++) {
    const int row = row0 + (px >> 3), col = col0 + (px & 7);
    float c[3] = {0.f, 0.f, 0.f};
    for (int i = 0; i < 7; i++)
      for (int j = 0; j < 7; j++) {
        const int rr = row + i - 3, cc = col + j - 3;
        if (rr < 0 || rr >= IMG || cc < 0 || cc >= IMG) continue;
        for (int k = 0; k < 3; k++)
          c[k] = fmaf(__bfloat162float(x[((size_t)rr * IMG + cc) * CH + lane + 32 * k]), __bfloat162float(dw[(i * 7 + j) * CH + lane + 32 * k]), c[k]);
      }
    float mean = (c[0] + c[1] + c[2]) * (1.0f / 96.0f);
    for (int o = 16; o; o >>= 1) mean += __shfl_xor_sync(0xffffffffu, mean, o);
    float var = 0.f;
    for (int k = 0; k < 3; k++) { c[k] -= mean; var = fmaf(c[k] * (1.0f / 96.0f), c[k], var); }
    for (int o = 16; o; o >>= 1) var += __shfl_xor_sync(0xffffffffu, var, o);
    const float rs = 1.0f / sqrtf(var + 1e-5f);
    __syncwarp();
    for (int k = 0; k < 3; k++) buf[lane + 32 * k] = c[k] * rs;
    __syncwarp();
    for (int n = lane; n < 4 * CH; n += 32) {
      float y = 0.f;
      for (int k = 0; k < CH; k++) y = fmaf(buf[k], __bfloat162float(w1[k * 4 * CH + n]), y);
      buf[CH + n] = 0.5f * y * (1.0f + tanhf(0.7978845608f * (y + 0.044715f * y * y * y)));
    }
    __syncwarp();
    for (int n = lane; n < CH; n += 32) {
      float o = 0.f;
      for (int k = 0; k < 4 * CH; k++) o = fmaf(buf[CH + k], __bfloat162float(w2[k * CH + n]), o);
      const size_t idx = ((size_t)row * IMG + col) * CH + n;
      out[idx] = __float2bfloat16(__bfloat162float(x[idx]) + o);
    }
  }
}

__device__ __forceinline__ void x_load(const MlpCtx& m, uint32_t (&x)[24]) {
#pragma unroll
  for (int k = 0; k < 6; k++)
    asm volatile("ld.shared.v4.b32 {%0,%1,%2,%3}, [%4];"
                 : "=r"(x[4 * k]), "=r"(x[4 * k + 1]), "=r"(x[4 * k + 2]), "=r"(x[4 * k + 3])
                 : "r"(m.xaddr + (k / 3) * 384 + (k % 3) * 64)
                 : "memory");
}
template <int LO, int HI>
__device__ __forceinline__ void epilogue(const MlpCtx& m, const uint32_t (&d)[24], uint32_t (&x)[24]) {
#pragma unroll
  for (int k = LO; k < HI; k++) {
    const int r = k / 3, q = k % 3;
    uint32_t* y = &x[4 * k];
#pragma unroll
    for (int j = 0; j < 4; j++) {
      uint32_t v = d[2 * (4 * q + j) + r];
      float lo, hi;
      asm("{\n.reg .b16 l, h;\nmov.b32 {l, h}, %2;\ncvt.f32.f16 %0, l;\ncvt.f32.f16 %1, h;\n}\n" : "=f"(lo), "=f"(hi) : "r"(v));
      asm("fma.rn.bf16x2 %0, %1, %2, %0;" : "+r"(y[j]) : "r"(pack_bf16(lo, hi)), "r"(m.unscale));
    }
    asm volatile("st.shared.v4.b32 [%0], {%1,%2,%3,%4};" ::"r"(m.xaddr + r * 384 + q * 64), "r"(y[0]), "r"(y[1]), "r"(y[2]), "r"(y[3])
                 : "memory");
  }
}
__device__ __forceinline__ void out_store(const MlpCtx& m, int i) {
  asm volatile("fence.proxy.async.shared::cta;" ::: "memory");
  __syncwarp();
  if (elect_one()) {
    const uint32_t src = m.sb + OFF_XRES + m.wg * 12288 + m.warp * 1536;
    uint8_t* dst = m.optr + (size_t)i * (8 * IMG * CH * 2);
    asm volatile("cp.async.bulk.global.shared::cta.bulk_group [%0], [%1], 1536;" ::"l"(dst), "r"(src) : "memory");
    asm volatile("cp.async.bulk.global.shared::cta.bulk_group [%0], [%1], 1536;" ::"l"(dst + IMG * CH * 2), "r"(src + 6144) : "memory");
    asm volatile("cp.async.bulk.commit_group;" ::: "memory");
  }
}

#define FSET 0
constexpr int FJ = FSET ? 2 : 0;
template <int J> __device__ __forceinline__ void tok_wait() {
  if (J == FJ || J == 3) NB_SYNC(NB_CLOSE, 256);
  else NB_SYNC(NB_SEC + (J & 1), 256);
}
template <int J> __device__ __forceinline__ void tok_next() {
  if (J == FJ || J == 3) NB_ARRIVE(NB_SEC + (J & 1), 256);
  if (J == 0) NB_ARRIVE(NB_PROD, 160);
}
__device__ __forceinline__ void tok_pass() { NB_ARRIVE(NB_OPEN, 416); }
template <int J> __device__ __forceinline__ void tok_idle() { tok_wait<J>(); tok_next<J>(); tok_pass(); }

constexpr uint64_t CHK = 1152;

__device__ __forceinline__ float warp_sumsq(const uint32_t (&q)[4]) {
  const uint32_t t = bf_add(bf_add(q[0], q[1]), bf_add(q[2], q[3]));
  float f = bf_lo(t) + bf_hi(t);
#pragma unroll
  for (int o = 16; o; o >>= 1) f += __shfl_xor_sync(0xffffffffu, f, o);
  return f;
}
__device__ __forceinline__ int norm_exp(float f) { return (((int)(__float_as_uint(f * 1.5f) >> 23) - 127) >> 1) + 1; }
__device__ __forceinline__ int scale_exp(int e1, int e2) { return min(11 - e1 - e2, 14 - e2); }

__device__ __forceinline__ uint32_t mlp_role(const MlpCtx& m0, const uint4* w1, const uint4* w2) {
  MlpCtx m = m0;
  uint32_t bad = 0;
  const int lane = threadIdx.x & 31, wid = m.wg * 4 + m.warp;
  {
    int s;
    {
      const uint4 a = __ldg(w1 + lane * 145), b = __ldg(w2 + lane * 145);
      const uint32_t qa[4] = {bf_mul(a.x, a.x), bf_mul(a.y, a.y), bf_mul(a.z, a.z), bf_mul(a.w, a.w)};
      const uint32_t qb[4] = {bf_mul(b.x, b.x), bf_mul(b.y, b.y), bf_mul(b.z, b.z), bf_mul(b.w, b.w)};
      s = max(-64, min(64, scale_exp(norm_exp(144.f * warp_sumsq(qa)), norm_exp(144.f * warp_sumsq(qb))) - 1));
    }
    TS(2);
    const int k7 = lane & 7;
    uint32_t q[4] = {0, 0, 0, 0}, v[6][4];
    {
      const int n8 = ((m.warp >> 1) * 4 + (lane >> 3) + k7) & 7, hf = m.warp & 1, t4 = k7 >> 1;
      const uint32_t base = m.sb + OFF_W1 + m.wg * 36864;
      const uint32_t src = base + (2 * hf + (k7 & 1)) * 768 + n8 * 16, dst = base + n8 * 256 + hf * 128 + k7 * 16;
      uint32_t u[18][4];
      mbar_wait(m.sb + BAR_W + 8 * m.wg, 0);
      TS(3);
#pragma unroll
      for (int k = 0; k < 18; k++) lds128(u[k], src + (k < 12 ? 8 * t4 + 4 * (k / 6) : 32 + 4 * t4) * 768 + (k % 6) * 128);
#pragma unroll
      for (int k = 0; k < 18; k++)
#pragma unroll
        for (int t = 0; t < 4; t++) {
          q[t] = bf_fma(u[k][t], u[k][t], q[t]);
          u[k][t] = pack_f16(bf_lo(u[k][t]), bf_hi(u[k][t]));
        }
      if (m.wg == 0) NB_SYNC(NB_WG, 128);
      else NB_SYNC(NB_WG + 1, 128);
#pragma unroll
      for (int k = 0; k < 18; k++)
        asm volatile("st.shared.v4.b32 [%0], {%1,%2,%3,%4};" ::"r"(dst + k * 2048), "r"(u[k][0]), "r"(u[k][1]), "r"(u[k][2]), "r"(u[k][3])
                     : "memory");
    }
    const float f1 = warp_sumsq(q);
    TS(4);
    {
      constexpr float F = 0.5f / GELU_A, FHI = 1.515625f;
      const float p2 = __uint_as_float((uint32_t)(127 + s - 56) << 23);
      const uint32_t hi = pack_bf16(FHI * 0x1p-56f, FHI * 0x1p-56f), lo = pack_bf16((F - FHI) * 0x1p-56f, (F - FHI) * 0x1p-56f);
      const uint32_t pw = pack_bf16(p2, p2);
      uint32_t base = m.sb + OFF_W2 + wid * 3072;
      const uint32_t so = (lane >> 2) * 192 + (lane & 3) * 16, dO = k7 * 16 + (lane >> 3) * 256;
      q[0] = q[1] = q[2] = q[3] = 0;
#pragma unroll 1
      for (int it = 0; it < 3; it++, base += 24576) {
        mbar_wait(m.sb + BAR_W + 24 + 8 * it, 0);
#pragma unroll
        for (int k = 0; k < 6; k++) lds128(v[k], base + so + (k / 3) * 1536 + (k % 3) * 64);
#pragma unroll
        for (int k = 0; k < 6; k++)
#pragma unroll
          for (int j = 0; j < 4; j++) {
            q[j] = bf_fma(v[k][j], v[k][j], q[j]);
            const uint32_t w = bf_mul(v[k][j], pw), t = bf_fma(w, hi, bf_mul(w, lo));
            v[k][j] = (t & 0x7fff7fffu) * 7u + t;
          }
        __syncwarp();
#pragma unroll
        for (int k = 0; k < 6; k++)
          asm volatile("stmatrix.sync.aligned.m8n8.x4.shared.b16 [%0], {%1,%2,%3,%4};" ::"r"(base + dO + (k / 3) * 128 + (k % 3) * 1024),
                       "r"(v[k][0]), "r"(v[k][1]), "r"(v[k][2]), "r"(v[k][3])
                       : "memory");
      }
    }
    const float f2 = warp_sumsq(q);
    if (lane == 0) asm volatile("st.shared.v2.f32 [%0], {%1,%2};" ::"r"(m.sb + OFF_NRM + 8 * wid), "f"(f1), "f"(f2) : "memory");
    TS(5);
    asm volatile("fence.proxy.async.shared::cta;" ::: "memory");
    NB_SYNC(NB_PREP, 256);
    float n1 = 0.f, n2 = 0.f;
#pragma unroll
    for (int k = 0; k < 4; k++) {
      lds128(q, m.sb + OFF_NRM + 16 * k);
      n1 += __uint_as_float(q[0]) + __uint_as_float(q[2]);
      n2 += __uint_as_float(q[1]) + __uint_as_float(q[3]);
    }
    const int e1 = norm_exp(n1), e2 = norm_exp(n2), smax = scale_exp(e1, e2);
    if (e1 > 12 || e1 < -5 || e2 > 50 || e2 < -50 || s > smax || s < smax - 5) bad = 0xffffu;
    m.unscale = __shfl_sync(0xffffffffu, ((uint32_t)(127 - s) << 7) * 0x10001u, 0);
  }
  asm volatile("barrier.cluster.wait.aligned;" ::: "memory");
  if ((m.sb & 0x3FFFF) != 1024) bad = 0xffffu;
  constexpr uint64_t dW1 = (uint64_t)((1024 + OFF_W1) >> 4) | ((uint64_t)8 << 16) | ((uint64_t)16 << 32);
  constexpr uint64_t dW2 = dW1 + (OFF_W2 >> 4);
  TS(6);
  uint32_t A1[24], g[24], d[24], cn[24], D2[24];
  float st[8];
  ln_wait(m, 0);
  ln_load(m, cn);
  ln_sums(cn, st);
  ln_shfl(st, 1);
  ln_release(m);
  ln_fold(st);
  ln_shfl(st, 2);
  ln_stats(st, bad, 1);
  ln_apply(A1, cn, st);
  TS(7);
  if (m.wg & m.rank) tok_idle<3>();
  if (m.wg) tok_idle<0>();
  if (m.wg | m.rank) tok_idle<1>();
  {
    uint32_t d0[24];
    WG_FENCE();
    tok_wait<2>();
    tok_next<2>();
    gemm6<true, 768>(d0, A1, dW1);
    tok_pass(); PIN();
    WG_WAIT0(); rfence(d0);
    WG_FENCE();
    tok_wait<3>();
    tok_next<3>();
    gemm6<true, 768>(d, A1, dW1 + 192);
    tok_pass(); PIN();
    gelu<0, 24>(g, d0);
    PIN();
    ln_wait(m, 1);
    ln_load(m, cn);
    PIN();
    WG_WAIT0(); rfence(d);
  }
#define G2(INIT, a, j)                      \
  WG_FENCE();                               \
  tok_wait<j>();                            \
  gemm6<INIT, 192>(D2, a, dW2 + (j) * CHK); \
  tok_next<j>(); PIN();                     \
  TL(ltb, (j) * 5 + 1);
#define G1(dst, j, P)                       \
  TL(ltb, ((j) ^ 2) * 5 + 2);               \
  P(); WG_WAIT0(); rfence(D2);              \
  WG_FENCE();                               \
  gemm6<true, 768>(dst, A1, dW1 + (j) * 192); \
  tok_pass(); P();                          \
  TL(ltb, ((j) ^ 2) * 5 + 3);
#define ROUND_END(dst, j)                   \
  TL(ltb, (j) * 5 + 4);                     \
  PIN(); WG_WAIT0(); rfence(dst);
#define GA 10
#define GB 12
#define GC 12
#define GD 10
#pragma unroll 1
  for (int i = 0;; i++) {
    uint32_t g1[24], d2[24], g2[24], d3[24], g3[24], d0[24];
    G2(true, g, 0)
    gelu<0, GA>(g1, d);
    G1(d2, 2, PIN)
    ln_sums(cn, st);
    gelu<GA, 24>(g1, d);
    PIN();
    ln_shfl(st, 1);
    ROUND_END(d2, 0)

    G2(false, g1, 1)
    ln_fold(st);
    gelu<0, GB>(g2, d2);
    PIN();
    ln_shfl(st, 2);
    G1(d3, 3, PIN)
    ln_stats(st, bad, 2u << i);
    gelu<GB, 24>(g2, d2);
    ROUND_END(d3, 1)

    if (i == 15) {
      G2(false, g2, 2)
      tok_pass();
      gelu<0, 24>(g3, d3);
      PIN();
      x_load(m, cn);
      ROUND_END(D2, 2)
      G2(false, g3, 3)
      tok_pass();
      WG_WAIT0(); rfence(D2);
      epilogue<0, 6>(m, D2, cn);
      break;
    }
    G2(false, g2, 2)
    ln_apply(A1, cn, st);
    PIN();
    gelu<0, GC>(g3, d3);
    G1(d0, 0, PIN)
    gelu<GC, 24>(g3, d3);
    PIN();
    x_load(m, cn);
    ROUND_END(d0, 2)

    G2(false, g3, 3)
    gelu<0, GD>(g, d0);
    G1(d, 1, PIN)
    epilogue<0, 6>(m, D2, cn);
    gelu<GD, 24>(g, d0);
    PIN();
    asm volatile("fence.proxy.async.shared::cta;" ::: "memory");
    ln_load(m, cn);
    ROUND_END(d, 3)
    TLDUMP(m.warp == 0 && (i >> 1) == LTRACE, m.sb + OFF_LT + m.wg * 160 + (i & 1) * 80, 20)
  }
  out_store(m, 15);
  if (m.wg == 0) { tok_idle<0>(); tok_idle<1>(); }
  asm volatile("cp.async.bulk.wait_group 0;" ::: "memory");
  return __reduce_or_sync(0xffffffffu, bad & 0xffffu);
}

struct ConvCtx {
  uint32_t sb;
  uint32_t a_raw, a_c;
  uint32_t peer_off;
  int rank, v, c0, r0, zero;
  const CUtensorMap* tm;
  const uint8_t* xsrc;
  uint8_t* optr;
};

__device__ __forceinline__ void raw_refill(const ConvCtx& c, int s) {
  if (s + 4 < NSTEP)
    tma_raw(c.sb + OFF_RAW + (s & 3) * RAW_BYTES, c.tm, PITCH == 112 ? 56 * c.rank - 8 : 48 * c.rank, c.c0 / 2 - 2, c.r0 - 3 + 2 * (s + 4), c.sb + BAR_RAW + 8 * (s & 3));
}
__device__ __forceinline__ void step_ready(const ConvCtx& c, int s) {
  const int nx = (s + 1) & 3, par = ((s + 1) >> 2) & 1;
  if (s + 2 < NSTEP) mbar_wait(c.sb + BAR_RAW + 8 * ((s + 2) & 3), ((s + 2) >> 2) & 1);
  if (s >= 7 && s < NSTEP) mbar_wait(c.sb + BAR_CEMPTY + 8 * (2 * (nx & 1) + (nx >> 1)), par);
}

__device__ __forceinline__ void prod_rows(const ConvCtx& c) {
#pragma unroll 1
  for (int s = 0; s < NROUND + SIGMA + c.rank; s++) {
    const int r = s - SIGMA - c.rank;
    const int u = (r & 1) ? (r >> 1) - 1 : (r >> 1) + 2;
    step_ready(c, s);
    if (u >= ((r & 1) ? 0 : 4) && u < 32) mbar_wait(c.sb + ((r & 1) ? BAR_XFULL : BAR_CFULL) + 8 * (u & 1), (u >> 1) & 1);
    if (s < SIGMA) NB_SYNC(NB_PLAN, 160);
    else NB_SYNC(NB_OPEN, 416);
    if (r == 3) TC(1);
    if (r == 55) TC(2);
    if (r >= -1 && r < 7) TS(7 + r);
    if (elect_one()) raw_refill(c, s);
  }
}
__device__ __forceinline__ void prod_tiles(const ConvCtx& c) {
  asm volatile("barrier.cluster.wait.aligned;" ::: "memory");
#pragma unroll 1
  for (int n = 0; n < NROUND / 2; n++) {
    const uint32_t w = (n + 1) & 1;
    const uint32_t buf = c.sb + OFF_XRES + w * 12288;
    NB_SYNC(NB_PROD, 160);
    if (n >= 1 && n < 33 && elect_one()) {
      if (n < 29) {
        const uint32_t e = c.sb + BAR_CEMPTY + 8 * (2 * c.rank + w);
        mbar_expect(c.sb + BAR_CFULL + 8 * w, CTX);
        asm volatile("mbarrier.arrive.shared::cluster.b64 _, [%0], 4;" ::"r"(e) : "memory");
        asm volatile("mbarrier.arrive.shared::cluster.b64 _, [%0], 4;" ::"r"(e + c.peer_off) : "memory");
      }
      if (n >= 3) {
        uint8_t* dst = c.optr + (size_t)(n - 3) * (4 * IMG * CH * 2);
        asm volatile("cp.async.bulk.global.shared::cta.bulk_group [%0], [%1], 6144;" ::"l"(dst), "r"(buf) : "memory");
        asm volatile("cp.async.bulk.global.shared::cta.bulk_group [%0], [%1], 6144;" ::"l"(dst + IMG * CH * 2), "r"(buf + 6144) : "memory");
        asm volatile("cp.async.bulk.commit_group;" ::: "memory");
        asm volatile("cp.async.bulk.wait_group.read 0;" ::: "memory");
      }
      const uint8_t* src = c.xsrc + (size_t)(n - 1) * (4 * IMG * CH * 2);
      mbar_expect(c.sb + BAR_XFULL + 8 * w, 12288);
      bulk_load_last(buf, src, 6144, c.sb + BAR_XFULL + 8 * w);
      bulk_load_last(buf + 6144, src + IMG * CH * 2, 6144, c.sb + BAR_XFULL + 8 * w);
    }
  }
  asm volatile("cp.async.bulk.wait_group 0;" ::: "memory");
}

template <int LO, int HI>
__device__ __forceinline__ void conv_ld8(uint32_t a, uint32_t (&r)[6][6]) {
#pragma unroll
  for (int j = LO; j < HI; j++)
    asm volatile("ld.shared.v4.b32 {%0,%1,%2,%3}, [%4];"
                 : "=r"(r[j][0]), "=r"(r[j][1]), "=r"(r[j][2]), "=r"(r[j][3])
                 : "r"(a + (j >> 1) * PITCH + (j & 1) * RAW_PLANE)
                 : "memory");
}
__device__ __forceinline__ void conv_ld4(uint32_t a, uint32_t (&r)[6][6]) {
#pragma unroll
  for (int j = 0; j < 6; j++)
    asm volatile("ld.shared.v2.b32 {%0,%1}, [%2];" : "=r"(r[j][4]), "=r"(r[j][5]) : "r"(a + (j >> 1) * PITCH + (j & 1) * RAW_PLANE) : "memory");
}
template <int LO, int HI>
__device__ __forceinline__ void conv_frags(uint32_t zero, const uint32_t (&r)[6][6], uint32_t (&A)[12][4]) {
#pragma unroll
  for (int ch = LO; ch < HI; ch++) {
    const uint32_t sel = (ch & 1) ? 0x7632 : 0x5410;
    A[ch][0] = __byte_perm(r[0][ch >> 1], r[1][ch >> 1], sel);
    A[ch][1] = __byte_perm(r[2][ch >> 1], r[3][ch >> 1], sel);
    A[ch][2] = A[ch][1] ^ zero;
    A[ch][3] = __byte_perm(r[4][ch >> 1], r[5][ch >> 1], sel);
    rfence(A[ch]);
  }
}
__device__ __forceinline__ void hmma_acc(uint32_t (&v)[4], const uint32_t (&a)[4], const uint32_t* b) {
  asm volatile("mma.sync.aligned.m16n8k16.row.col.f32.bf16.bf16.f32 {%0,%1,%2,%3}, {%4,%5,%6,%7}, {%8,%9}, {%0,%1,%2,%3};"
               : "+r"(v[0]), "+r"(v[1]), "+r"(v[2]), "+r"(v[3])
               : "r"(a[0]), "r"(a[1]), "r"(a[2]), "r"(a[3]), "r"(b[0]), "r"(b[1]));
}
__device__ __forceinline__ void hmma_new(uint32_t (&a)[4], const uint32_t* b) {
  asm volatile("mma.sync.aligned.m16n8k16.row.col.f32.bf16.bf16.f32 {%0,%1,%2,%3}, {%0,%1,%2,%3}, {%4,%5}, {%6,%6,%6,%6};"
               : "+r"(a[0]), "+r"(a[1]), "+r"(a[2]), "+r"(a[3])
               : "r"(b[0]), "r"(b[1]), "f"(0.f));
}

#define EARLY 5
#define CV 1
#define LQ 1
#define NE 0
template <int S2, bool GATED>
__device__ __forceinline__ void conv_step(const ConvCtx& c, int s, uint32_t (&K)[12], uint32_t (&V)[12][4], const uint32_t (&B)[12][4],
                                          uint32_t (&A)[12][4]) {
  const int nx = ((s + 1) & 2) | (S2 ^ 1);
  uint32_t r[6][6];
  TL(ltb, 0);
  if (!GATED) TS(6 + s);
  conv_ld4(c.a_raw + nx * RAW_BYTES + 64 - 8 * c.v, r);
  conv_ld8<0, NE>(c.a_raw + nx * RAW_BYTES, r);
  if (GATED) NB_SYNC(NB_OPEN, 416);
  else NB_SYNC(NB_PLAN, 160);
  PIN();
  TL(ltb, 1);
#pragma unroll
  for (int ch = 0; ch < 12; ch++) hmma_acc(V[11 - ch], A[11 - ch], &B[11 - ch][2]);
#pragma unroll
  for (int ch = 0; ch < 12 - EARLY; ch++) hmma_new(A[ch], &B[ch][0]);
  const uint32_t zero = c.zero & clock_pin();
  if (GATED) NB_ARRIVE(NB_CLOSE, 256);
#pragma unroll
  for (int ch = 12 - EARLY; ch < 12; ch++) hmma_new(A[ch], &B[ch][0]);
  PIN();
  TL(ltb, 2);
  const uint32_t off = ((S2 ^ 1) == c.rank) ? 0u : c.peer_off;
  const uint32_t dst = c.a_c + (GATED || s >= 3 ? off + (nx >> 1) * C_BYTES : OFF_XRES + 12288 - OFF_C);
  const uint32_t bar = c.sb + (GATED || s >= 3 ? off + BAR_CFULL + 8 * (nx >> 1) : BAR_W + 56);
#pragma unroll
  for (int q = 0; q < 12; q++) {
    const int ch = q & ~1, h = 2 * (q & 1);
    asm("add.rn.f16x2 %0, %0, %1;" : "+r"(K[q]) : "r"(pack_f16(__uint_as_float(V[ch][h + 1]), __uint_as_float(V[ch + 1][h]))));
  }
#pragma unroll
  for (int q = 0; q < 3; q++)
    asm volatile("st.async.weak.shared::cluster.mbarrier::complete_tx::bytes.v4.b32 [%0], {%1,%2,%3,%4}, [%5];" ::"r"(dst + q * 2048),
                 "r"(K[4 * q]), "r"(K[4 * q + 1]), "r"(K[4 * q + 2]), "r"(K[4 * q + 3]), "r"(bar)
                 : "memory");
  PIN();
#pragma unroll
  for (int q = 0; q < 12; q++) {
    const int ch = q & ~1, h = 2 * (q & 1);
    K[q] = pack_f16(__uint_as_float(V[ch][h]), __uint_as_float(V[ch + 1][h + 1]));
  }
  rfence(K);
  conv_frags<8, 12>(zero, r, V);
  PIN();
  conv_ld8<NE, 6>(c.a_raw + nx * RAW_BYTES, r);
  conv_frags<0, 8>(zero, r, V);
  PIN();
  TL(ltb, 4);
  TLDUMP(c.v == 0 && lr >= 0 && lr < 10, c.sb + OFF_LT + 320 + lr * 20, 5)
}

__device__ __forceinline__ void conv_role(const ConvCtx& c) {
  const int lane = threadIdx.x & 31, g = lane >> 2, t = lane & 3;
  uint32_t B[12][4];
  {
    const int dc = (g >> 1) & 1, ro = g >> 2, rk = t >> 1;
    const int i0 = 4 * (g & 1) + rk - ro, j0 = 4 * (t & 1) - dc;
    const uint32_t base = c.sb + OFF_XRES + 96 * c.rank + (i0 * 7 + j0) * 192;
    TS(2);
    mbar_wait(c.sb + BAR_W + 48, 0);
    TS(3);
#pragma unroll
    for (int b = 0; b < 2; b++) {
      uint32_t w[4][6];
#pragma unroll
      for (int k = 0; k < 4; k++) {
        const int ok = (unsigned)(i0 + 2 * b) < 7u && (unsigned)(j0 + k) < 7u;
#pragma unroll
        for (int q = 0; q < 6; q++) w[k][q] = 0;
        asm volatile(
            "{\n.reg .pred p;\nsetp.ne.s32 p, %8, 0;\n@p ld.shared.v4.b32 {%0,%1,%2,%3}, [%6];\n@p ld.shared.v2.b32 {%4,%5}, [%7];\n}\n"
            : "+r"(w[k][0]), "+r"(w[k][1]), "+r"(w[k][2]), "+r"(w[k][3]), "+r"(w[k][4]), "+r"(w[k][5])
            : "r"(base + (b * 14 + k) * 192 + 16 * c.v), "r"(base + (b * 14 + k) * 192 + 64 + 8 * c.v), "r"(ok)
            : "memory");
      }
#pragma unroll
      for (int q = 0; q < 6; q++) {
        B[2 * q][2 * b] = __byte_perm(w[0][q], w[1][q], 0x5410);
        B[2 * q][2 * b + 1] = __byte_perm(w[2][q], w[3][q], 0x5410);
        B[2 * q + 1][2 * b] = __shfl_xor_sync(0xffffffffu, __byte_perm(w[0][q], w[1][q], 0x7632), 4);
        B[2 * q + 1][2 * b + 1] = __shfl_xor_sync(0xffffffffu, __byte_perm(w[2][q], w[3][q], 0x7632), 4);
      }
    }
  }
  TS(4);
  asm volatile("barrier.cluster.wait.aligned;" ::: "memory");
  uint32_t K1[12], K2[12], V[12][4];
#pragma unroll
  for (int ch = 0; ch < 12; ch++) {
    K1[ch] = K2[ch] = 0;
#pragma unroll
    for (int k = 0; k < 4; k++) V[ch][k] = 0;
  }
  uint32_t A[12][4], r[6][6];
  mbar_wait(c.sb + BAR_RAW, 0);
  TS(5);
  conv_ld8<0, 6>(c.a_raw, r);
  conv_frags<0, 8>(c.zero, r, A);
  PIN();
  conv_ld4(c.a_raw + 64 - 8 * c.v, r);
  conv_frags<8, 12>(c.zero, r, A);
  PIN();
  mbar_wait(c.sb + BAR_RAW + 8, 0);
  NB_ARRIVE(NB_CLOSE, 256);
#pragma unroll 1
  for (int s = 0; s < SIGMA; s += 2) {
    conv_step<0, false>(c, s, K1, V, B, A);
    conv_step<1, false>(c, s + 1, K2, A, B, V);
  }
#pragma unroll 1
  for (int s = SIGMA;; s += 2) {
    conv_step<0, true>(c, s, K1, V, B, A);
    if (s == NSTEP - 1) break;
    conv_step<1, true>(c, s + 1, K2, A, B, V);
  }
#pragma unroll 1
  for (int r = NSTEP - SIGMA - c.rank; r < NROUND - 1; r++) {
    NB_SYNC(NB_OPEN, 416);
    NB_ARRIVE(NB_CLOSE, 256);
  }
  NB_SYNC(NB_OPEN, 416);
}

__global__ void __cluster_dims__(2, 1, 1) __launch_bounds__(512, 1)
convnext_kernel(const __grid_constant__ CUtensorMap tm, const __nv_bfloat16* __restrict__ x, const __nv_bfloat16* __restrict__ dw,
                const __nv_bfloat16* __restrict__ w1, const __nv_bfloat16* __restrict__ w2, __nv_bfloat16* __restrict__ out,
                int zero) {
  extern __shared__ __align__(1024) uint8_t smem[];
  const uint32_t sb = (uint32_t)__cvta_generic_to_shared(smem);
  const int tid = threadIdx.x, lane = tid & 31;
  const int wid = __shfl_sync(0xffffffffu, tid >> 5, 0);
  const int rank = blockIdx.x & 1, cl = blockIdx.x >> 1;
  const int c0 = (cl & 15) * 32, r0 = (cl >> 4) * 128;
  const uint32_t peer_off = mapa(sb, rank ^ 1) - sb;

  TS(0);
  if (tid == 416) {
    const uint8_t* w = reinterpret_cast<const uint8_t*>(rank ? w2 : w1) + cl * 1152;
    asm volatile("cp.async.bulk.prefetch.L2.global [%0], 1152;" ::"l"(w) : "memory");
    if (blockIdx.x < 49) asm volatile("cp.async.bulk.prefetch.L2.global [%0], 192;" ::"l"(dw + blockIdx.x * CH) : "memory");
#define NPF 0
#pragma unroll 1
    for (int i = 0; i < NPF; i++) {
      const int row = r0 - 3 + 2 * i + rank;
      if (row >= 0) asm volatile("cp.async.bulk.prefetch.L2.global [%0], 6144;" ::"l"(x + ((size_t)row * IMG + c0) * CH) : "memory");
    }
  }
  if (tid == 384) {
    asm volatile("prefetch.tensormap [%0];" ::"l"(&tm) : "memory");
    for (int i = 0; i < 8; i++) mbar_init(sb + BAR_W + 8 * i, 1);
    for (int i = 0; i < 4; i++) mbar_init(sb + BAR_RAW + 8 * i, 1);
    asm volatile("fence.mbarrier_init.release.cluster;" ::: "memory");
  }
  if (tid == 128) {
    for (int i = 0; i < 2; i++) mbar_init(sb + BAR_CFULL + 8 * i, CCNT);
    for (int i = 0; i < 4; i++) mbar_init(sb + BAR_CEMPTY + 8 * i, 4);
    for (int i = 0; i < 2; i++) mbar_init(sb + BAR_XFULL + 8 * i, 1);
    for (int i = 0; i < 2; i++) mbar_expect(sb + BAR_CFULL + 8 * i, CTX);
    asm volatile("fence.mbarrier_init.release.cluster;" ::: "memory");
  }
  __syncthreads();
  asm volatile("barrier.cluster.arrive.relaxed.aligned;" ::: "memory");

  TS(1);
  if (wid < 8) {
    MlpCtx m;
    m.sb = sb; m.wg = wid >> 2; m.warp = wid & 3; m.rank = rank; m.peer_off = peer_off; m.zero = zero;
    m.optr = reinterpret_cast<uint8_t*>(out) + ((size_t)(r0 + 4 * m.wg + 2 * rank) * IMG + c0 + 8 * m.warp) * (CH * 2);
    m.caddr = sb + OFF_C + m.wg * C_BYTES + (lane & 3) * 512 + ((m.warp * 8 + (lane >> 2) + 2 * (lane & 3)) & 31) * 16;
    m.xaddr = sb + OFF_XRES + m.wg * 12288 + m.warp * 1536 + ((lane >> 3) & 1) * 6144 + ((lane >> 4) * 4 + ((lane >> 2) & 1)) * 192 + (lane & 3) * 16;
    m.unscale = 0;
    asm volatile("setmaxnreg.inc.sync.aligned.u32 %0;" ::"n"(REG_MLP));
    const uint32_t bad = mlp_role(m, reinterpret_cast<const uint4*>(w1), reinterpret_cast<const uint4*>(w2));
    asm volatile("barrier.cluster.arrive.relaxed.aligned;\nbarrier.cluster.wait.aligned;" ::: "memory");
    if (bad) {
      asm volatile("fence.proxy.async;" ::: "memory");
      for (int i = 0; i < 16; i++)
        if (bad >> i & 1)
          slow_tile(x, dw, w1, w2, out, r0 + 8 * i + 4 * m.wg + 2 * rank, c0 + 8 * m.warp,
                    reinterpret_cast<float*>(smem + OFF_XRES + wid * 3072));
    }
  } else {
    ConvCtx c;
    c.sb = sb; c.rank = rank; c.v = wid - 8; c.c0 = c0; c.r0 = r0; c.zero = zero; c.tm = &tm;
    c.peer_off = peer_off;
    c.xsrc = reinterpret_cast<const uint8_t*>(x) + ((size_t)(r0 + 2 * rank) * IMG + c0) * (CH * 2);
    c.optr = reinterpret_cast<uint8_t*>(out) + ((size_t)(r0 + 2 * rank) * IMG + c0) * (CH * 2);
    const int g = lane >> 2, t = lane & 3;
    c.a_raw = sb + OFF_RAW + ((t >> 1) * 19 + 2 * (g + (t & 1))) * PITCH + (PITCH == 112 ? (1 - rank) * 16 : 0) + 16 * c.v;
    c.a_c = sb + OFF_C + 6144 * rank + 512 * c.v + ((lane + 2 * c.v) & 31) * 16;
    if (wid < 12) {
      asm volatile("setmaxnreg.inc.sync.aligned.u32 %0;" ::"n"(REG_CONV));
      conv_role(c);
      __syncwarp();
      asm volatile("barrier.cluster.arrive.relaxed.aligned;\nbarrier.cluster.wait.aligned;\nexit;" ::: "memory");
    } else {
      asm volatile("setmaxnreg.dec.sync.aligned.u32 24;");
      if (wid == 14) TC(0);
      if (wid == 12) {
        if (elect_one()) {
          mbar_expect(sb + BAR_W + 48, 49 * CH * 2);
          bulk_load(sb + OFF_XRES, dw, 49 * CH * 2, sb + BAR_W + 48);
          TS(2);
#define WLEAD 0
#pragma unroll 1
          for (int h = 0; h < 5; h++) {
            if (h >= WLEAD && h < WLEAD + 4) raw_refill(c, h - WLEAD - 4);
            const uint32_t o = h < 2 ? h * 36864 : (h + 1) * 24576, n = h < 2 ? 36864 : 24576, bar = sb + BAR_W + 8 * (h < 2 ? h : h + 1);
            const uint8_t* w = h < 2 ? reinterpret_cast<const uint8_t*>(w1) : reinterpret_cast<const uint8_t*>(w2) - OFF_W2;
            mbar_expect(bar, n);
            bulk_load(sb + o, w + o, n, bar);
          }
          TS(3);
        }
        __syncwarp();
        prod_rows(c);
      } else if (wid == 13) {
        prod_tiles(c);
        __syncwarp();
        asm volatile("barrier.cluster.arrive.relaxed.aligned;\nbarrier.cluster.wait.aligned;" ::: "memory");
        TC(3);
      }
    }
  }
}

typedef CUresult (*EncodeFn)(CUtensorMap*, CUtensorMapDataType, cuuint32_t, void*, const cuuint64_t*, const cuuint64_t*,
                             const cuuint32_t*, const cuuint32_t*, CUtensorMapInterleave, CUtensorMapSwizzle,
                             CUtensorMapL2promotion, CUtensorMapFloatOOBfill);

}

extern "C" void kernel_launch(void* const* d_in, const int* in_sizes, int n_in, void* d_out, int out_size) {
  const __nv_bfloat16* x = (const __nv_bfloat16*)d_in[0];
  const __nv_bfloat16* dw = (const __nv_bfloat16*)d_in[1];
  const __nv_bfloat16* w1 = (const __nv_bfloat16*)d_in[2];
  const __nv_bfloat16* w2 = (const __nv_bfloat16*)d_in[3];
  __nv_bfloat16* out = (__nv_bfloat16*)d_out;

  static EncodeFn encode = nullptr;
  if (!encode) {
    cudaDriverEntryPointQueryResult st;
    void* fn = nullptr;
    cudaGetDriverEntryPoint("cuTensorMapEncodeTiled", &fn, cudaEnableDefault, &st);
    encode = (EncodeFn)fn;
    cudaFuncSetAttribute(convnext_kernel, cudaFuncAttributeMaxDynamicSharedMemorySize, SMEM_BYTES);
  }
  CUtensorMap tm;
  cuuint64_t dims[4] = {CH, IMG / 2, IMG, 2};
  cuuint64_t strides[3] = {CH * 4, (cuuint64_t)IMG * CH * 2, CH * 2};
  cuuint32_t box[4] = {PITCH / 2, 19, 2, 1};
  cuuint32_t es[4] = {1, 1, 1, 1};
  encode(&tm, CU_TENSOR_MAP_DATA_TYPE_BFLOAT16, 4, (void*)x, dims, strides, box, es, CU_TENSOR_MAP_INTERLEAVE_NONE,
         CU_TENSOR_MAP_SWIZZLE_NONE, PROMO, CU_TENSOR_MAP_FLOAT_OOB_FILL_NONE);
  convnext_kernel<<<128, 512, SMEM_BYTES>>>(tm, x, dw, w1, w2, out, 0);
}
```

```cpp
#include <cuda_runtime.h>
#include <cuda_bf16.h>
#include <cuda.h>
#include <stdint.h>

#define PROMO CU_TENSOR_MAP_L2_PROMOTION_L2_128B
#define CTX 12288
#define CCNT 1
#define LA 1
namespace {

constexpr int IMG = 512, CH = 96;
constexpr int NSTEP = 67;
constexpr int SIGMA = 8;
constexpr int NROUND = 68;

constexpr uint32_t OFF_W1 = 0;
constexpr uint32_t OFF_W2 = 73728;
constexpr uint32_t OFF_RAW = 147456;
#define PITCH 112
constexpr uint32_t RAW_PLANE = (38 * PITCH + 127) / 128 * 128;
constexpr uint32_t RAW_BYTES = 2 * RAW_PLANE;
constexpr uint32_t RAW_TX = 2 * 2 * 19 * PITCH;
constexpr uint32_t OFF_XRES = OFF_RAW + 4 * RAW_BYTES;
constexpr uint32_t OFF_C = OFF_XRES + 2 * 12288;
constexpr uint32_t C_BYTES = 12288;
constexpr uint32_t OFF_BAR = OFF_C + 2 * C_BYTES;
constexpr uint32_t BAR_RAW = OFF_BAR;
constexpr uint32_t BAR_CFULL = OFF_BAR + 32;
constexpr uint32_t BAR_CEMPTY = OFF_BAR + 48;
constexpr uint32_t BAR_XFULL = OFF_BAR + 80;
constexpr uint32_t BAR_W = OFF_BAR + 96;
constexpr uint32_t OFF_NRM = OFF_BAR + 160;
constexpr uint32_t OFF_LT = OFF_BAR + 160;
constexpr uint32_t SMEM_BYTES = OFF_BAR + 160 + 600;

constexpr float GELU_A = 0.32918364f;
constexpr uint32_t GELU_K2 = 0x40d940d9u;

constexpr int NB_CLOSE = 1, NB_SEC = 6  , NB_OPEN = 3, NB_PROD = 2, NB_PLAN = 4, NB_PREP = 5, NB_WG = 8  ;
#define REG_MLP 144
constexpr int REG_CONV = 488 - 2 * REG_MLP;

#define WG_FENCE() asm volatile("wgmma.fence.sync.aligned;" ::: "memory")
#define WG_COMMIT() asm volatile("wgmma.commit_group.sync.aligned;" ::: "memory")
#define WG_WAIT0() asm volatile("wgmma.wait_group.sync.aligned 0;" ::: "memory")
#define WG_WAIT1() asm volatile("wgmma.wait_group.sync.aligned 1;" ::: "memory")
#define PIN() asm volatile("pmevent 0;" ::: "memory")
#define NB_SYNC(id, n) asm volatile("bar.sync %0, %1;" ::"n"(id), "n"(n) : "memory")
#define NB_ARRIVE(id, n) asm volatile("bar.arrive %0, %1;" ::"n"(id), "n"(n) : "memory")

#define TS(idx)
#define TC(k)
#define TF(k)
#define TL(base, off)
#define TLDUMP(cond, base, n)

#define R24(c, d)                                                                                        \
  c(d[0]), c(d[1]), c(d[2]), c(d[3]), c(d[4]), c(d[5]), c(d[6]), c(d[7]), c(d[8]), c(d[9]), c(d[10]),    \
      c(d[11]), c(d[12]), c(d[13]), c(d[14]), c(d[15]), c(d[16]), c(d[17]), c(d[18]), c(d[19]), c(d[20]), \
      c(d[21]), c(d[22]), c(d[23])
#define WG_TXT(sd)                                                                             \
  "wgmma.mma_async.sync.aligned.m64n96k16.f16.f16.f16 "                                        \
  "{%0,%1,%2,%3,%4,%5,%6,%7,%8,%9,%10,%11,%12,%13,%14,%15,%16,%17,%18,%19,%20,%21,%22,%23}, " \
  "{%24,%25,%26,%27}, %28, " sd ", 1, 1, 1;\n"

__device__ __forceinline__ void wg_acc(uint32_t (&d)[24], const uint32_t* a, uint64_t db) {
  asm volatile(WG_TXT("1") : R24("+r", d) : "r"(a[0]), "r"(a[1]), "r"(a[2]), "r"(a[3]), "l"(db));
}
__device__ __forceinline__ void wg_init(uint32_t (&d)[24], const uint32_t* a, uint64_t db) {
  asm volatile(WG_TXT("0") : R24("=r", d) : "r"(a[0]), "r"(a[1]), "r"(a[2]), "r"(a[3]), "l"(db));
}
template <int N>
__device__ __forceinline__ void rfence(uint32_t (&d)[N]) {
#pragma unroll
  for (int i = 0; i < N; i++) asm volatile("" : "+r"(d[i])::"memory");
}
template <bool INIT, int KSTRIDE>
__device__ __forceinline__ void gemm6(uint32_t (&d)[24], const uint32_t (&a)[24], uint64_t db) {
#pragma unroll
  for (int k = 0; k < 6; k++) {
    if (INIT && k == 0) wg_init(d, &a[0], db);
    else wg_acc(d, &a[4 * k], db + k * KSTRIDE);
  }
  WG_COMMIT();
}

__device__ __forceinline__ void mbar_init(uint32_t bar, uint32_t cnt) {
  asm volatile("mbarrier.init.shared::cta.b64 [%0], %1;" ::"r"(bar), "r"(cnt) : "memory");
}
__device__ __forceinline__ void mbar_expect(uint32_t bar, uint32_t bytes) {
  asm volatile("mbarrier.arrive.expect_tx.shared::cta.b64 _, [%0], %1;" ::"r"(bar), "r"(bytes) : "memory");
}
__device__ __forceinline__ void mbar_arrive_cluster(uint32_t bar) {
  asm volatile("mbarrier.arrive.shared::cluster.b64 _, [%0];" ::"r"(bar) : "memory");
}
__device__ __forceinline__ bool mbar_try(uint32_t bar, uint32_t parity) {
  uint32_t ok;
  asm volatile(
      "{\n.reg .pred p;\nmbarrier.try_wait.parity.shared::cta.b64 p, [%1], %2;\nselp.u32 %0, 1, 0, p;\n}\n"
      : "=r"(ok)
      : "r"(bar), "r"(parity)
      : "memory");
  return ok;
}
__device__ __forceinline__ bool mbar_test(uint32_t bar, uint32_t parity) {
  uint32_t ok;
  asm volatile(
      "{\n.reg .pred p;\nmbarrier.test_wait.parity.shared::cta.b64 p, [%1], %2;\nselp.u32 %0, 1, 0, p;\n}\n"
      : "=r"(ok)
      : "r"(bar), "r"(parity)
      : "memory");
  return ok;
}
__device__ __forceinline__ void mbar_wait(uint32_t bar, uint32_t parity) {
  if (__builtin_expect(mbar_try(bar, parity), 1)) return;
#pragma unroll 1
  for (uint32_t n = 0; n < (1u << 16) && !mbar_try(bar, parity); n++) {}
}
__device__ __forceinline__ uint32_t mapa(uint32_t addr, uint32_t rank) {
  uint32_t r;
  asm("mapa.shared::cluster.u32 %0, %1, %2;" : "=r"(r) : "r"(addr), "r"(rank));
  return r;
}
__device__ __forceinline__ void tma_raw(uint32_t dst, const CUtensorMap* tm, int c, int w2, int h, uint32_t bar) {
  mbar_expect(bar, RAW_TX);
#pragma unroll
  for (int e = 0; e < 2; e++)
    asm volatile(
        "cp.async.bulk.tensor.4d.shared::cluster.global.mbarrier::complete_tx::bytes [%0], [%1, {%2, %3, %4, %5}], [%6];"
        ::"r"(dst + e * RAW_PLANE), "l"(tm), "r"(c), "r"(w2 + e), "r"(h), "r"(1 - e), "r"(bar)
        : "memory");
}
__device__ __forceinline__ void bulk_load(uint32_t dst, const void* src, uint32_t bytes, uint32_t bar) {
  asm volatile("cp.async.bulk.shared::cluster.global.mbarrier::complete_tx::bytes [%0], [%1], %2, [%3];" ::"r"(dst),
               "l"(src), "r"(bytes), "r"(bar)
               : "memory");
}
__device__ __forceinline__ void bulk_load_last(uint32_t dst, const void* src, uint32_t bytes, uint32_t bar) {
  asm volatile(
      "{\n.reg .b64 pol;\ncreatepolicy.fractional.L2::evict_first.b64 pol, 1.0;\n"
      "cp.async.bulk.shared::cluster.global.mbarrier::complete_tx::bytes.L2::cache_hint [%0], [%1], %2, [%3], pol;\n}\n" ::"r"(dst),
      "l"(src), "r"(bytes), "r"(bar)
      : "memory");
}
__device__ __forceinline__ uint32_t pack_bf16(float lo, float hi) {
  uint32_t r;
  asm("cvt.rn.bf16x2.f32 %0, %1, %2;" : "=r"(r) : "f"(hi), "f"(lo));
  return r;
}
__device__ __forceinline__ uint32_t pack_f16(float lo, float hi) {
  uint32_t r;
  asm("cvt.rn.f16x2.f32 %0, %1, %2;" : "=r"(r) : "f"(hi), "f"(lo));
  return r;
}
__device__ __forceinline__ float bf_lo(uint32_t v) { return __uint_as_float(v << 16); }
__device__ __forceinline__ float bf_hi(uint32_t v) { return __uint_as_float(v & 0xffff0000u); }
__device__ __forceinline__ uint32_t bf_add(uint32_t a, uint32_t b) {
  uint32_t r;
  asm("add.rn.bf16x2 %0, %1, %2;" : "=r"(r) : "r"(a), "r"(b));
  return r;
}
__device__ __forceinline__ uint32_t bf_mul(uint32_t a, uint32_t b) {
  uint32_t r;
  asm("mul.rn.bf16x2 %0, %1, %2;" : "=r"(r) : "r"(a), "r"(b));
  return r;
}
__device__ __forceinline__ uint32_t bf_fma(uint32_t a, uint32_t b, uint32_t c) {
  uint32_t r;
  asm("fma.rn.bf16x2 %0, %1, %2, %3;" : "=r"(r) : "r"(a), "r"(b), "r"(c));
  return r;
}

__device__ __forceinline__ uint32_t h_add(uint32_t a, uint32_t b) {
  uint32_t r;
  asm("add.rn.f16x2 %0, %1, %2;" : "=r"(r) : "r"(a), "r"(b));
  return r;
}
__device__ __forceinline__ uint32_t h_mul(uint32_t a, uint32_t b) {
  uint32_t r;
  asm("mul.rn.f16x2 %0, %1, %2;" : "=r"(r) : "r"(a), "r"(b));
  return r;
}
__device__ __forceinline__ uint32_t h_fma(uint32_t a, uint32_t b, uint32_t c) {
  uint32_t r;
  asm("fma.rn.f16x2 %0, %1, %2, %3;" : "=r"(r) : "r"(a), "r"(b), "r"(c));
  return r;
}
__device__ __forceinline__ float h_sum(uint32_t v) {
  float lo, hi;
  asm("{\n.reg .b16 l, h;\nmov.b32 {l, h}, %2;\ncvt.f32.f16 %0, l;\ncvt.f32.f16 %1, h;\n}\n" : "=f"(lo), "=f"(hi) : "r"(v));
  return lo + hi;
}
__device__ __forceinline__ void lds128(uint32_t (&v)[4], uint32_t a) {
  asm volatile("ld.shared.v4.b32 {%0,%1,%2,%3}, [%4];" : "=r"(v[0]), "=r"(v[1]), "=r"(v[2]), "=r"(v[3]) : "r"(a) : "memory");
}

template <int LO, int HI>
__device__ __forceinline__ void gelu(uint32_t (&o)[24], const uint32_t (&d)[24]) {
#pragma unroll
  for (int qq = LO; qq < HI; qq++) {
    const int q = (qq + 4) % 24;
    uint32_t t, u;
    asm("fma.rn.f16x2 %0, %1, %1, %2;" : "=r"(t) : "r"(d[q]), "r"(GELU_K2));
    asm("mul.rn.f16x2 %0, %1, %2;" : "=r"(u) : "r"(d[q]), "r"(t));
    asm("tanh.approx.f16x2 %0, %1;" : "=r"(t) : "r"(u));
    asm("fma.rn.f16x2 %0, %1, %2, %1;" : "=r"(o[q]) : "r"(d[q]), "r"(t));
  }
}

__device__ __forceinline__ uint32_t laneid() {
  uint32_t l;
  asm volatile("mov.u32 %0, %%laneid;" : "=r"(l));
  return l;
}

__device__ __forceinline__ bool elect_one() {
  uint32_t p;
  asm volatile("{\n.reg .pred p;\nelect.sync _|p, 0xffffffff;\nselp.u32 %0, 1, 0, p;\n}\n" : "=r"(p));
  return p;
}

__device__ __forceinline__ uint32_t clock_pin() {
  uint32_t t;
  asm volatile("mov.u32 %0, %%clock;" : "=r"(t)::"memory");
  return t;
}

struct MlpCtx {
  uint32_t sb;
  uint32_t caddr;
  uint32_t xaddr;
  uint32_t unscale;
  uint32_t peer_off;
  int wg, warp, rank, zero;
  uint8_t* optr;
};

__device__ __forceinline__ void ln_wait(const MlpCtx& m, int i) { mbar_wait(m.sb + BAR_CFULL + 8 * m.wg, i & 1); }
__device__ __forceinline__ void ln_load(const MlpCtx& m, uint32_t (&c)[24]) {
#pragma unroll
  for (int p = 0; p < 6; p++)
    asm volatile("ld.shared.v4.b32 {%0,%1,%2,%3}, [%4];"
                 : "=r"(c[4 * p]), "=r"(c[4 * p + 1]), "=r"(c[4 * p + 2]), "=r"(c[4 * p + 3])
                 : "r"(m.caddr + p * 2048)
                 : "memory");
}
__device__ __forceinline__ void ln_shfl(float (&st)[8], int mask) {
#pragma unroll
  for (int k = 0; k < 4; k++) st[4 + k] = __shfl_xor_sync(0xffffffffu, st[k], mask);
}
__device__ __forceinline__ void ln_fold(float (&st)[8]) {
#pragma unroll
  for (int k = 0; k < 4; k++) st[k] += st[4 + k];
}
__device__ __forceinline__ void ln_sums(const uint32_t (&c)[24], float (&st)[8]) {
#pragma unroll
  for (int r = 0; r < 2; r++) {
    uint32_t s0 = h_add(c[r], c[r + 2]), s1 = h_add(c[r + 4], c[r + 6]), s2 = h_add(c[r + 8], c[r + 10]);
    uint32_t s3 = h_add(c[r + 12], c[r + 14]), s4 = h_add(c[r + 16], c[r + 18]), s5 = h_add(c[r + 20], c[r + 22]);
    s0 = h_add(s0, s1); s2 = h_add(s2, s3); s4 = h_add(s4, s5);
    st[r] = h_sum(h_add(h_add(s0, s2), s4));
    uint32_t q0 = h_mul(c[r], c[r]), q1 = h_mul(c[r + 2], c[r + 2]);
#pragma unroll
    for (int p = 2; p < 12; p += 2) {
      q0 = h_fma(c[2 * p + r], c[2 * p + r], q0);
      q1 = h_fma(c[2 * p + 2 + r], c[2 * p + 2 + r], q1);
    }
    st[2 + r] = h_sum(h_add(q0, q1));
  }
}
__device__ __forceinline__ void ln_release(const MlpCtx& m) {
  const uint32_t e = m.sb + BAR_CEMPTY + 8 * (2 * m.rank + m.wg);
  asm volatile(
      "{\n.reg .pred p, q;\nelect.sync _|p, 0xffffffff;\nsetp.eq.and.s32 q, %3, 0, p;\n"
      "@q mbarrier.arrive.expect_tx.shared::cta.b64 _, [%0], %4;\n"
      "@p mbarrier.arrive.shared::cluster.b64 _, [%1];\n"
      "@p mbarrier.arrive.shared::cluster.b64 _, [%2];\n}\n" ::"r"(m.sb + BAR_CFULL + 8 * m.wg),
      "r"(e), "r"(e + m.peer_off), "r"(m.warp), "n"(CTX)
      : "memory");
}
__device__ __forceinline__ void ln_stats(float (&st)[8], uint32_t& bad, uint32_t bit) {
  bool ok = true;
#pragma unroll
  for (int r = 0; r < 2; r++) {
    const float nm = (st[r] + st[4 + r]) * (-1.0f / 96.0f);
    const float e2 = fmaf(st[2 + r] + st[6 + r], 1.0f / 96.0f, 1e-5f);
    float rs;
    asm("rsqrt.approx.ftz.f32 %0, %1;" : "=f"(rs) : "f"(fmaf(-nm, nm, e2)));
    ok = ok && (rs * rs * e2 <= 17.0f) && (e2 >= 1.001e-5f);
    const float rr = rs * GELU_A, dd = rr * nm;
    st[r] = __uint_as_float(pack_f16(rr, rr));
    st[2 + r] = __uint_as_float(pack_f16(dd, dd));
  }
  if (!ok) bad |= bit;
}
__device__ __forceinline__ void ln_apply(uint32_t (&a)[24], const uint32_t (&c)[24], const float (&st)[8]) {
#pragma unroll
  for (int p = 0; p < 24; p++) {
    a[p] = h_fma(c[p], __float_as_uint(st[p & 1]), __float_as_uint(st[2 + (p & 1)]));
  }
}

__device__ __noinline__ void slow_tile(const __nv_bfloat16* x, const __nv_bfloat16* dw, const __nv_bfloat16* w1,
                                       const __nv_bfloat16* w2, __nv_bfloat16* out, int row0, int col0, float* buf) {
  const int lane = threadIdx.x & 31;
  for (int px = 0; px < 16; px++) {
    const int row = row0 + (px >> 3), col = col0 + (px & 7);
    float c[3] = {0.f, 0.f, 0.f};
    for (int i = 0; i < 7; i++)
      for (int j = 0; j < 7; j++) {
        const int rr = row + i - 3, cc = col + j - 3;
        if (rr < 0 || rr >= IMG || cc < 0 || cc >= IMG) continue;
        for (int k = 0; k < 3; k++)
          c[k] = fmaf(__bfloat162float(x[((size_t)rr * IMG + cc) * CH + lane + 32 * k]), __bfloat162float(dw[(i * 7 + j) * CH + lane + 32 * k]), c[k]);
      }
    float mean = (c[0] + c[1] + c[2]) * (1.0f / 96.0f);
    for (int o = 16; o; o >>= 1) mean += __shfl_xor_sync(0xffffffffu, mean, o);
    float var = 0.f;
    for (int k = 0; k < 3; k++) { c[k] -= mean; var = fmaf(c[k] * (1.0f / 96.0f), c[k], var); }
    for (int o = 16; o; o >>= 1) var += __shfl_xor_sync(0xffffffffu, var, o);
    const float rs = 1.0f / sqrtf(var + 1e-5f);
    __syncwarp();
    for (int k = 0; k < 3; k++) buf[lane + 32 * k] = c[k] * rs;
    __syncwarp();
    for (int n = lane; n < 4 * CH; n += 32) {
      float y = 0.f;
      for (int k = 0; k < CH; k++) y = fmaf(buf[k], __bfloat162float(w1[k * 4 * CH + n]), y);
      buf[CH + n] = 0.5f * y * (1.0f + tanhf(0.7978845608f * (y + 0.044715f * y * y * y)));
    }
    __syncwarp();
    for (int n = lane; n < CH; n += 32) {
      float o = 0.f;
      for (int k = 0; k < 4 * CH; k++) o = fmaf(buf[CH + k], __bfloat162float(w2[k * CH + n]), o);
      const size_t idx = ((size_t)row * IMG + col) * CH + n;
      out[idx] = __float2bfloat16(__bfloat162float(x[idx]) + o);
    }
  }
}

__device__ __forceinline__ void x_load(const MlpCtx& m, uint32_t (&x)[24]) {
#pragma unroll
  for (int k = 0; k < 6; k++)
    asm volatile("ld.shared.v4.b32 {%0,%1,%2,%3}, [%4];"
                 : "=r"(x[4 * k]), "=r"(x[4 * k + 1]), "=r"(x[4 * k + 2]), "=r"(x[4 * k + 3])
                 : "r"(m.xaddr + (k / 3) * 384 + (k % 3) * 64)
                 : "memory");
}
template <int LO, int HI>
__device__ __forceinline__ void epilogue(const MlpCtx& m, const uint32_t (&d)[24], uint32_t (&x)[24]) {
#pragma unroll
  for (int k = LO; k < HI; k++) {
    const int r = k / 3, q = k % 3;
    uint32_t* y = &x[4 * k];
#pragma unroll
    for (int j = 0; j < 4; j++) {
      uint32_t v = d[2 * (4 * q + j) + r];
      float lo, hi;
      asm("{\n.reg .b16 l, h;\nmov.b32 {l, h}, %2;\ncvt.f32.f16 %0, l;\ncvt.f32.f16 %1, h;\n}\n" : "=f"(lo), "=f"(hi) : "r"(v));
      asm("fma.rn.bf16x2 %0, %1, %2, %0;" : "+r"(y[j]) : "r"(pack_bf16(lo, hi)), "r"(m.unscale));
    }
    asm volatile("st.shared.v4.b32 [%0], {%1,%2,%3,%4};" ::"r"(m.xaddr + r * 384 + q * 64), "r"(y[0]), "r"(y[1]), "r"(y[2]), "r"(y[3])
                 : "memory");
  }
}
__device__ __forceinline__ void out_store(const MlpCtx& m, int i) {
  asm volatile("fence.proxy.async.shared::cta;" ::: "memory");
  __syncwarp();
  if (elect_one()) {
    const uint32_t src = m.sb + OFF_XRES + m.wg * 12288 + m.warp * 1536;
    uint8_t* dst = m.optr + (size_t)i * (8 * IMG * CH * 2);
    asm volatile("cp.async.bulk.global.shared::cta.bulk_group [%0], [%1], 1536;" ::"l"(dst), "r"(src) : "memory");
    asm volatile("cp.async.bulk.global.shared::cta.bulk_group [%0], [%1], 1536;" ::"l"(dst + IMG * CH * 2), "r"(src + 6144) : "memory");
    asm volatile("cp.async.bulk.commit_group;" ::: "memory");
  }
}

#define FSET 3
template <int J> constexpr bool goes_first = J == FSET || J == ((FSET + 1) & 3);
template <int J> __device__ __forceinline__ void tok_wait() {
  if (goes_first<J>) NB_SYNC(NB_CLOSE, 256);
  else NB_SYNC(NB_SEC + (J & 1), 256);
}
template <int J> __device__ __forceinline__ void tok_next() {
  if (goes_first<J>) NB_ARRIVE(NB_SEC + (J & 1), 256);
  if (J == 0) NB_ARRIVE(NB_PROD, 160);
}
__device__ __forceinline__ void tok_pass() { NB_ARRIVE(NB_OPEN, 416); }
template <int J> __device__ __forceinline__ void tok_idle() { tok_wait<J>(); tok_next<J>(); tok_pass(); }

constexpr uint64_t CHK = 1152;

__device__ __forceinline__ float warp_sumsq(const uint32_t (&q)[4]) {
  const uint32_t t = bf_add(bf_add(q[0], q[1]), bf_add(q[2], q[3]));
  float f = bf_lo(t) + bf_hi(t);
#pragma unroll
  for (int o = 16; o; o >>= 1) f += __shfl_xor_sync(0xffffffffu, f, o);
  return f;
}
__device__ __forceinline__ int norm_exp(float f) { return (((int)(__float_as_uint(f * 1.5f) >> 23) - 127) >> 1) + 1; }
__device__ __forceinline__ int scale_exp(int e1, int e2) { return min(11 - e1 - e2, 14 - e2); }

__device__ __forceinline__ uint32_t mlp_role(const MlpCtx& m0, const uint4* w1, const uint4* w2) {
  MlpCtx m = m0;
  uint32_t bad = 0;
  const int lane = threadIdx.x & 31, wid = m.wg * 4 + m.warp;
  {
    int s;
    {
      const uint4 a = __ldg(w1 + lane * 145), b = __ldg(w2 + lane * 145);
      const uint32_t qa[4] = {bf_mul(a.x, a.x), bf_mul(a.y, a.y), bf_mul(a.z, a.z), bf_mul(a.w, a.w)};
      const uint32_t qb[4] = {bf_mul(b.x, b.x), bf_mul(b.y, b.y), bf_mul(b.z, b.z), bf_mul(b.w, b.w)};
      s = max(-64, min(64, scale_exp(norm_exp(144.f * warp_sumsq(qa)), norm_exp(144.f * warp_sumsq(qb))) - 1));
    }
    TS(2);
    const int k7 = lane & 7;
    uint32_t q[4] = {0, 0, 0, 0}, v[6][4];
    {
      const int n8 = ((m.warp >> 1) * 4 + (lane >> 3) + k7) & 7, hf = m.warp & 1, t4 = k7 >> 1;
      const uint32_t base = m.sb + OFF_W1 + m.wg * 36864;
      const uint32_t src = base + (2 * hf + (k7 & 1)) * 768 + n8 * 16, dst = base + n8 * 256 + hf * 128 + k7 * 16;
      uint32_t u[18][4];
      mbar_wait(m.sb + BAR_W + 8 * m.wg, 0);
      TS(3);
#pragma unroll
      for (int k = 0; k < 18; k++) lds128(u[k], src + (k < 12 ? 8 * t4 + 4 * (k / 6) : 32 + 4 * t4) * 768 + (k % 6) * 128);
#pragma unroll
      for (int k = 0; k < 18; k++)
#pragma unroll
        for (int t = 0; t < 4; t++) {
          q[t] = bf_fma(u[k][t], u[k][t], q[t]);
          u[k][t] = pack_f16(bf_lo(u[k][t]), bf_hi(u[k][t]));
        }
      if (m.wg == 0) NB_SYNC(NB_WG, 128);
      else NB_SYNC(NB_WG + 1, 128);
#pragma unroll
      for (int k = 0; k < 18; k++)
        asm volatile("st.shared.v4.b32 [%0], {%1,%2,%3,%4};" ::"r"(dst + k * 2048), "r"(u[k][0]), "r"(u[k][1]), "r"(u[k][2]), "r"(u[k][3])
                     : "memory");
    }
    const float f1 = warp_sumsq(q);
    TS(4);
    {
      constexpr float F = 0.5f / GELU_A, FHI = 1.515625f;
      const float p2 = __uint_as_float((uint32_t)(127 + s - 56) << 23);
      const uint32_t hi = pack_bf16(FHI * 0x1p-56f, FHI * 0x1p-56f), lo = pack_bf16((F - FHI) * 0x1p-56f, (F - FHI) * 0x1p-56f);
      const uint32_t pw = pack_bf16(p2, p2);
      uint32_t base = m.sb + OFF_W2 + wid * 3072;
      const uint32_t so = (lane >> 2) * 192 + (lane & 3) * 16, dO = k7 * 16 + (lane >> 3) * 256;
      q[0] = q[1] = q[2] = q[3] = 0;
#pragma unroll 1
      for (int it = 0; it < 3; it++, base += 24576) {
        mbar_wait(m.sb + BAR_W + 24 + 8 * it, 0);
#pragma unroll
        for (int k = 0; k < 6; k++) lds128(v[k], base + so + (k / 3) * 1536 + (k % 3) * 64);
#pragma unroll
        for (int k = 0; k < 6; k++)
#pragma unroll
          for (int j = 0; j < 4; j++) {
            q[j] = bf_fma(v[k][j], v[k][j], q[j]);
            const uint32_t w = bf_mul(v[k][j], pw), t = bf_fma(w, hi, bf_mul(w, lo));
            v[k][j] = (t & 0x7fff7fffu) * 7u + t;
          }
        __syncwarp();
#pragma unroll
        for (int k = 0; k < 6; k++)
          asm volatile("stmatrix.sync.aligned.m8n8.x4.shared.b16 [%0], {%1,%2,%3,%4};" ::"r"(base + dO + (k / 3) * 128 + (k % 3) * 1024),
                       "r"(v[k][0]), "r"(v[k][1]), "r"(v[k][2]), "r"(v[k][3])
                       : "memory");
      }
    }
    const float f2 = warp_sumsq(q);
    if (lane == 0) asm volatile("st.shared.v2.f32 [%0], {%1,%2};" ::"r"(m.sb + OFF_NRM + 8 * wid), "f"(f1), "f"(f2) : "memory");
    TS(5);
    asm volatile("fence.proxy.async.shared::cta;" ::: "memory");
    NB_SYNC(NB_PREP, 256);
    float n1 = 0.f, n2 = 0.f;
#pragma unroll
    for (int k = 0; k < 4; k++) {
      lds128(q, m.sb + OFF_NRM + 16 * k);
      n1 += __uint_as_float(q[0]) + __uint_as_float(q[2]);
      n2 += __uint_as_float(q[1]) + __uint_as_float(q[3]);
    }
    const int e1 = norm_exp(n1), e2 = norm_exp(n2), smax = scale_exp(e1, e2);
    if (e1 > 12 || e1 < -5 || e2 > 50 || e2 < -50 || s > smax || s < smax - 5) bad = 0xffffu;
    m.unscale = __shfl_sync(0xffffffffu, ((uint32_t)(127 - s) << 7) * 0x10001u, 0);
  }
  asm volatile("barrier.cluster.wait.aligned;" ::: "memory");
  if ((m.sb & 0x3FFFF) != 1024) bad = 0xffffu;
  constexpr uint64_t dW1 = (uint64_t)((1024 + OFF_W1) >> 4) | ((uint64_t)8 << 16) | ((uint64_t)16 << 32);
  constexpr uint64_t dW2 = dW1 + (OFF_W2 >> 4);
  TS(6);
  uint32_t A1[24], g[24], d[24], cn[24], D2[24];
  float st[8];
  ln_wait(m, 0);
  ln_load(m, cn);
  ln_sums(cn, st);
  ln_shfl(st, 1);
  ln_release(m);
  ln_fold(st);
  ln_shfl(st, 2);
  ln_stats(st, bad, 1);
  ln_apply(A1, cn, st);
  TS(7);
  if (m.wg & m.rank) tok_idle<3>();
  if (m.wg) tok_idle<0>();
  if (m.wg | m.rank) tok_idle<1>();
  {
    uint32_t d0[24];
    WG_FENCE();
    tok_wait<2>();
    tok_next<2>();
    gemm6<true, 768>(d0, A1, dW1);
    tok_pass(); PIN();
    WG_WAIT0(); rfence(d0);
    WG_FENCE();
    tok_wait<3>();
    tok_next<3>();
    gemm6<true, 768>(d, A1, dW1 + 192);
    tok_pass(); PIN();
    gelu<0, 24>(g, d0);
    PIN();
    ln_wait(m, 1);
    ln_load(m, cn);
    PIN();
    WG_WAIT0(); rfence(d);
  }
#define G2(INIT, a, j)                      \
  WG_FENCE();                               \
  tok_wait<j>();                            \
  gemm6<INIT, 192>(D2, a, dW2 + (j) * CHK); \
  tok_next<j>(); PIN();                     \
  TL(ltb, (j) * 5 + 1);
#define G1(dst, j, P)                       \
  TL(ltb, ((j) ^ 2) * 5 + 2);               \
  P(); WG_WAIT0(); rfence(D2);              \
  WG_FENCE();                               \
  gemm6<true, 768>(dst, A1, dW1 + (j) * 192); \
  tok_pass(); P();                          \
  TL(ltb, ((j) ^ 2) * 5 + 3);
#define ROUND_END(dst, j)                   \
  TL(ltb, (j) * 5 + 4);                     \
  PIN(); WG_WAIT0(); rfence(dst);
#define GA 10
#define GB 12
#define GC 12
#define GD 10
#pragma unroll 1
  for (int i = 0;; i++) {
    uint32_t g1[24], d2[24], g2[24], d3[24], g3[24], d0[24];
    G2(true, g, 0)
    gelu<0, GA>(g1, d);
    G1(d2, 2, PIN)
    ln_sums(cn, st);
    gelu<GA, 24>(g1, d);
    PIN();
    ln_shfl(st, 1);
    ROUND_END(d2, 0)

    G2(false, g1, 1)
    ln_fold(st);
    gelu<0, GB>(g2, d2);
    PIN();
    ln_shfl(st, 2);
    G1(d3, 3, PIN)
    ln_stats(st, bad, 2u << i);
    gelu<GB, 24>(g2, d2);
    ROUND_END(d3, 1)

    if (i == 15) {
      G2(false, g2, 2)
      tok_pass();
      gelu<0, 24>(g3, d3);
      PIN();
      x_load(m, cn);
      ROUND_END(D2, 2)
      G2(false, g3, 3)
      tok_pass();
      WG_WAIT0(); rfence(D2);
      epilogue<0, 6>(m, D2, cn);
      break;
    }
    G2(false, g2, 2)
    ln_apply(A1, cn, st);
    PIN();
    gelu<0, GC>(g3, d3);
    G1(d0, 0, PIN)
    gelu<GC, 24>(g3, d3);
    PIN();
    x_load(m, cn);
    ROUND_END(d0, 2)

    G2(false, g3, 3)
    gelu<0, GD>(g, d0);
    G1(d, 1, PIN)
    epilogue<0, 6>(m, D2, cn);
    gelu<GD, 24>(g, d0);
    PIN();
    asm volatile("fence.proxy.async.shared::cta;" ::: "memory");
    ln_load(m, cn);
    ROUND_END(d, 3)
    TLDUMP(m.warp == 0 && (i >> 1) == LTRACE, m.sb + OFF_LT + m.wg * 160 + (i & 1) * 80, 20)
  }
  out_store(m, 15);
  if (m.wg == 0) { tok_idle<0>(); tok_idle<1>(); }
  asm volatile("cp.async.bulk.wait_group 0;" ::: "memory");
  return __reduce_or_sync(0xffffffffu, bad & 0xffffu);
}

struct ConvCtx {
  uint32_t sb;
  uint32_t a_raw, a_c;
  uint32_t peer_off;
  int rank, v, c0, r0, zero;
  const CUtensorMap* tm;
  const uint8_t* xsrc;
  uint8_t* optr;
};

__device__ __forceinline__ void raw_refill(const ConvCtx& c, int s) {
  if (s + 4 < NSTEP && elect_one())
    tma_raw(c.sb + OFF_RAW + (s & 3) * RAW_BYTES, c.tm, PITCH == 112 ? 56 * c.rank - 8 : 48 * c.rank, c.c0 / 2 - 2, c.r0 - 3 + 2 * (s + 4), c.sb + BAR_RAW + 8 * (s & 3));
}
__device__ __forceinline__ void step_ready(const ConvCtx& c, int s) {
  const int nx = (s + 1) & 3, par = ((s + 1) >> 2) & 1;
  if (s + LA < NSTEP) mbar_wait(c.sb + BAR_RAW + 8 * ((s + LA) & 3), ((s + LA) >> 2) & 1);
  if (s >= 7 && s < NSTEP) mbar_wait(c.sb + BAR_CEMPTY + 8 * (2 * (nx & 1) + (nx >> 1)), par);
}

__device__ __forceinline__ void c_release(const ConvCtx& c, uint32_t w) {
  const uint32_t e = c.sb + BAR_CEMPTY + 8 * (2 * c.rank + w);
  asm volatile(
      "{\n.reg .pred p;\nelect.sync _|p, 0xffffffff;\n"
      "@p mbarrier.arrive.expect_tx.shared::cta.b64 _, [%0], %3;\n"
      "@p mbarrier.arrive.shared::cluster.b64 _, [%1], 4;\n"
      "@p mbarrier.arrive.shared::cluster.b64 _, [%2], 4;\n}\n" ::"r"(c.sb + BAR_CFULL + 8 * w),
      "r"(e), "r"(e + c.peer_off), "n"(CTX)
      : "memory");
}

__device__ __forceinline__ void prod_rows(const ConvCtx& c) {
  asm volatile("barrier.cluster.wait.aligned;" ::: "memory");
#pragma unroll 1
  for (int s = 0; s < NROUND + SIGMA + c.rank; s++) {
    const int r = s - SIGMA - c.rank;
    const int u = (r & 1) ? (r >> 1) - 1 : (r >> 1) + 2;
    step_ready(c, s);
    if (u >= ((r & 1) ? 0 : 4) && u < 32) mbar_wait(c.sb + ((r & 1) ? BAR_XFULL : BAR_CFULL) + 8 * (u & 1), (u >> 1) & 1);
    if (s < SIGMA) NB_SYNC(NB_PLAN, 160);
    else NB_SYNC(NB_OPEN, 416);
    if (r == 3) TC(1);
    if (r == 55) TC(2);
    if (r >= -1 && r < 7) TS(7 + r);
    raw_refill(c, s);
  }
}
__device__ __forceinline__ void prod_tiles(const ConvCtx& c) {
  asm volatile("barrier.cluster.wait.aligned;" ::: "memory");
#pragma unroll 1
  for (int n = 0; n < NROUND / 2; n++) {
    const uint32_t w = (n + 1) & 1;
    const uint32_t buf = c.sb + OFF_XRES + w * 12288;
    NB_SYNC(NB_PROD, 160);
    if (n >= 1 && n < 29) c_release(c, w);
    if (n >= 3 && n < 33) {
      uint8_t* dst = c.optr + (size_t)(n - 3) * (4 * IMG * CH * 2);
      if (elect_one()) {
        asm volatile("cp.async.bulk.global.shared::cta.bulk_group [%0], [%1], 6144;" ::"l"(dst), "r"(buf) : "memory");
        asm volatile("cp.async.bulk.global.shared::cta.bulk_group [%0], [%1], 6144;" ::"l"(dst + IMG * CH * 2), "r"(buf + 6144) : "memory");
        asm volatile("cp.async.bulk.commit_group;" ::: "memory");
        asm volatile("cp.async.bulk.wait_group.read 0;" ::: "memory");
      }
      __syncwarp();
    }
    if (n >= 1 && n < 33) {
      const uint8_t* src = c.xsrc + (size_t)(n - 1) * (4 * IMG * CH * 2);
      if (elect_one()) {
        mbar_expect(c.sb + BAR_XFULL + 8 * w, 12288);
        bulk_load_last(buf, src, 6144, c.sb + BAR_XFULL + 8 * w);
        bulk_load_last(buf + 6144, src + IMG * CH * 2, 6144, c.sb + BAR_XFULL + 8 * w);
      }
    }
  }
  asm volatile("cp.async.bulk.wait_group 0;" ::: "memory");
}

template <int LO, int HI>
__device__ __forceinline__ void conv_ld8(uint32_t a, uint32_t (&r)[6][6]) {
#pragma unroll
  for (int j = LO; j < HI; j++)
    asm volatile("ld.shared.v4.b32 {%0,%1,%2,%3}, [%4];"
                 : "=r"(r[j][0]), "=r"(r[j][1]), "=r"(r[j][2]), "=r"(r[j][3])
                 : "r"(a + (j >> 1) * PITCH + (j & 1) * RAW_PLANE)
                 : "memory");
}
__device__ __forceinline__ void conv_ld4(uint32_t a, uint32_t (&r)[6][6]) {
#pragma unroll
  for (int j = 0; j < 6; j++)
    asm volatile("ld.shared.v2.b32 {%0,%1}, [%2];" : "=r"(r[j][4]), "=r"(r[j][5]) : "r"(a + (j >> 1) * PITCH + (j & 1) * RAW_PLANE) : "memory");
}
template <int LO, int HI>
__device__ __forceinline__ void conv_frags(uint32_t zero, const uint32_t (&r)[6][6], uint32_t (&A)[12][4]) {
#pragma unroll
  for (int ch = LO; ch < HI; ch++) {
    const uint32_t sel = (ch & 1) ? 0x7632 : 0x5410;
    A[ch][0] = __byte_perm(r[0][ch >> 1], r[1][ch >> 1], sel);
    A[ch][1] = __byte_perm(r[2][ch >> 1], r[3][ch >> 1], sel);
    A[ch][2] = A[ch][1] ^ zero;
    A[ch][3] = __byte_perm(r[4][ch >> 1], r[5][ch >> 1], sel);
    rfence(A[ch]);
  }
}
__device__ __forceinline__ void hmma_acc(uint32_t (&v)[4], const uint32_t (&a)[4], const uint32_t* b) {
  asm volatile("mma.sync.aligned.m16n8k16.row.col.f32.bf16.bf16.f32 {%0,%1,%2,%3}, {%4,%5,%6,%7}, {%8,%9}, {%0,%1,%2,%3};"
               : "+r"(v[0]), "+r"(v[1]), "+r"(v[2]), "+r"(v[3])
               : "r"(a[0]), "r"(a[1]), "r"(a[2]), "r"(a[3]), "r"(b[0]), "r"(b[1]));
}
__device__ __forceinline__ void hmma_new(uint32_t (&a)[4], const uint32_t* b) {
  asm volatile("mma.sync.aligned.m16n8k16.row.col.f32.bf16.bf16.f32 {%0,%1,%2,%3}, {%0,%1,%2,%3}, {%4,%5}, {%6,%6,%6,%6};"
               : "+r"(a[0]), "+r"(a[1]), "+r"(a[2]), "+r"(a[3])
               : "r"(b[0]), "r"(b[1]), "f"(0.f));
}

#define EARLY 5
template <int S2, bool GATED>
__device__ __forceinline__ void conv_step(const ConvCtx& c, int s, uint32_t (&K)[12], uint32_t (&V)[12][4], const uint32_t (&B)[12][4],
                                          uint32_t (&A)[12][4]) {
  const int nx = ((s + 1) & 2) | (S2 ^ 1);
  uint32_t r[6][6];
  TL(ltb, 0);
  if (!GATED) TS(6 + s);
  if (LA == 2) conv_ld4(c.a_raw + nx * RAW_BYTES + 64 - 8 * c.v, r);
  if (GATED) NB_SYNC(NB_OPEN, 416);
  else NB_SYNC(NB_PLAN, 160);
  if (LA == 1) conv_ld4(c.a_raw + nx * RAW_BYTES + 64 - 8 * c.v, r);
  PIN();
  TL(ltb, 1);
#pragma unroll
  for (int ch = 0; ch < 12; ch++) hmma_acc(V[11 - ch], A[11 - ch], &B[11 - ch][2]);
#pragma unroll
  for (int ch = 0; ch < 12 - EARLY; ch++) hmma_new(A[ch], &B[ch][0]);
  const uint32_t zero = c.zero & clock_pin();
  if (GATED) NB_ARRIVE(NB_CLOSE, 256);
#pragma unroll
  for (int ch = 12 - EARLY; ch < 12; ch++) hmma_new(A[ch], &B[ch][0]);
  PIN();
  TL(ltb, 2);
  const uint32_t off = ((S2 ^ 1) == c.rank) ? 0u : c.peer_off;
  const uint32_t dst = c.a_c + (GATED || s >= 3 ? off + (nx >> 1) * C_BYTES : OFF_XRES + 12288 - OFF_C);
  const uint32_t bar = c.sb + (GATED || s >= 3 ? off + BAR_CFULL + 8 * (nx >> 1) : BAR_W + 56);
#pragma unroll
  for (int q = 0; q < 12; q++) {
    const int ch = q & ~1, h = 2 * (q & 1);
    asm("add.rn.f16x2 %0, %0, %1;" : "+r"(K[q]) : "r"(pack_f16(__uint_as_float(V[ch][h + 1]), __uint_as_float(V[ch + 1][h]))));
  }
#pragma unroll
  for (int q = 0; q < 3; q++)
    asm volatile("st.async.weak.shared::cluster.mbarrier::complete_tx::bytes.v4.b32 [%0], {%1,%2,%3,%4}, [%5];" ::"r"(dst + q * 2048),
                 "r"(K[4 * q]), "r"(K[4 * q + 1]), "r"(K[4 * q + 2]), "r"(K[4 * q + 3]), "r"(bar)
                 : "memory");
  PIN();
#pragma unroll
  for (int q = 0; q < 12; q++) {
    const int ch = q & ~1, h = 2 * (q & 1);
    K[q] = pack_f16(__uint_as_float(V[ch][h]), __uint_as_float(V[ch + 1][h + 1]));
  }
  rfence(K);
  conv_frags<8, 12>(zero, r, V);
  PIN();
  conv_ld8<0, 6>(c.a_raw + nx * RAW_BYTES, r);
  conv_frags<0, 8>(zero, r, V);
  PIN();
  TL(ltb, 4);
  TLDUMP(c.v == 0 && lr >= 0 && lr < 10, c.sb + OFF_LT + 320 + lr * 20, 5)
}

__device__ __forceinline__ void conv_role(const ConvCtx& c) {
  const int lane = threadIdx.x & 31, g = lane >> 2, t = lane & 3;
  uint32_t B[12][4];
  {
    const int dc = (g >> 1) & 1, ro = g >> 2, rk = t >> 1;
    const int i0 = 4 * (g & 1) + rk - ro, j0 = 4 * (t & 1) - dc;
    const uint32_t base = c.sb + OFF_XRES + 96 * c.rank + (i0 * 7 + j0) * 192;
    TS(2);
    mbar_wait(c.sb + BAR_W + 48, 0);
    TS(3);
#pragma unroll
    for (int b = 0; b < 2; b++) {
      uint32_t w[4][6];
#pragma unroll
      for (int k = 0; k < 4; k++) {
        const int ok = (unsigned)(i0 + 2 * b) < 7u && (unsigned)(j0 + k) < 7u;
#pragma unroll
        for (int q = 0; q < 6; q++) w[k][q] = 0;
        asm volatile(
            "{\n.reg .pred p;\nsetp.ne.s32 p, %8, 0;\n@p ld.shared.v4.b32 {%0,%1,%2,%3}, [%6];\n@p ld.shared.v2.b32 {%4,%5}, [%7];\n}\n"
            : "+r"(w[k][0]), "+r"(w[k][1]), "+r"(w[k][2]), "+r"(w[k][3]), "+r"(w[k][4]), "+r"(w[k][5])
            : "r"(base + (b * 14 + k) * 192 + 16 * c.v), "r"(base + (b * 14 + k) * 192 + 64 + 8 * c.v), "r"(ok)
            : "memory");
      }
#pragma unroll
      for (int q = 0; q < 6; q++) {
        B[2 * q][2 * b] = __byte_perm(w[0][q], w[1][q], 0x5410);
        B[2 * q][2 * b + 1] = __byte_perm(w[2][q], w[3][q], 0x5410);
        B[2 * q + 1][2 * b] = __shfl_xor_sync(0xffffffffu, __byte_perm(w[0][q], w[1][q], 0x7632), 4);
        B[2 * q + 1][2 * b + 1] = __shfl_xor_sync(0xffffffffu, __byte_perm(w[2][q], w[3][q], 0x7632), 4);
      }
    }
  }
  TS(4);
  asm volatile("barrier.cluster.wait.aligned;" ::: "memory");
  uint32_t K1[12], K2[12], V[12][4];
#pragma unroll
  for (int ch = 0; ch < 12; ch++) {
    K1[ch] = K2[ch] = 0;
#pragma unroll
    for (int k = 0; k < 4; k++) V[ch][k] = 0;
  }
  uint32_t A[12][4], r[6][6];
  mbar_wait(c.sb + BAR_RAW, 0);
  TS(5);
  conv_ld8<0, 6>(c.a_raw, r);
  conv_frags<0, 8>(c.zero, r, A);
  PIN();
  conv_ld4(c.a_raw + 64 - 8 * c.v, r);
  conv_frags<8, 12>(c.zero, r, A);
  PIN();
  if (LA == 2) mbar_wait(c.sb + BAR_RAW + 8, 0);
  NB_ARRIVE(NB_CLOSE, 256);
#pragma unroll 1
  for (int s = 0; s < SIGMA; s += 2) {
    conv_step<0, false>(c, s, K1, V, B, A);
    conv_step<1, false>(c, s + 1, K2, A, B, V);
  }
#pragma unroll 1
  for (int s = SIGMA;; s += 2) {
    conv_step<0, true>(c, s, K1, V, B, A);
    if (s == NSTEP - 1) break;
    conv_step<1, true>(c, s + 1, K2, A, B, V);
  }
#pragma unroll 1
  for (int r = NSTEP - SIGMA - c.rank; r < NROUND - 1; r++) {
    NB_SYNC(NB_OPEN, 416);
    NB_ARRIVE(NB_CLOSE, 256);
  }
  NB_SYNC(NB_OPEN, 416);
}

__global__ void __cluster_dims__(2, 1, 1) __launch_bounds__(512, 1)
convnext_kernel(const __grid_constant__ CUtensorMap tm, const __nv_bfloat16* __restrict__ x, const __nv_bfloat16* __restrict__ dw,
                const __nv_bfloat16* __restrict__ w1, const __nv_bfloat16* __restrict__ w2, __nv_bfloat16* __restrict__ out,
                int zero) {
  extern __shared__ __align__(1024) uint8_t smem[];
  const uint32_t sb = (uint32_t)__cvta_generic_to_shared(smem);
  const int tid = threadIdx.x, lane = tid & 31;
  const int wid = __shfl_sync(0xffffffffu, tid >> 5, 0);
  const int rank = blockIdx.x & 1, cl = blockIdx.x >> 1;
  const int c0 = (cl & 15) * 32, r0 = (cl >> 4) * 128;
  const uint32_t peer_off = mapa(sb, rank ^ 1) - sb;

  TS(0);
  if (wid == 13) {
    const uint8_t* w = reinterpret_cast<const uint8_t*>(rank ? w2 : w1) + cl * 1152;
    const __nv_bfloat16* d = dw + min(cl, 48) * CH;
    if (elect_one()) {
      asm volatile("cp.async.bulk.prefetch.L2.global [%0], 192;" ::"l"(d) : "memory");
      asm volatile("cp.async.bulk.prefetch.L2.global [%0], 1152;" ::"l"(w) : "memory");
    }
  }
  if (wid == 12 && elect_one()) {
    asm volatile("prefetch.tensormap [%0];" ::"l"(&tm) : "memory");
#pragma unroll
    for (int i = 0; i < 8; i++) mbar_init(sb + BAR_W + 8 * i, 1);
#pragma unroll
    for (int i = 0; i < 4; i++) mbar_init(sb + BAR_RAW + 8 * i, 1);
    asm volatile("fence.mbarrier_init.release.cluster;" ::: "memory");
  }
  if (wid == 14 && elect_one()) {
#pragma unroll
    for (int i = 0; i < 2; i++) mbar_init(sb + BAR_CFULL + 8 * i, CCNT);
#pragma unroll
    for (int i = 0; i < 4; i++) mbar_init(sb + BAR_CEMPTY + 8 * i, 4);
#pragma unroll
    for (int i = 0; i < 2; i++) mbar_init(sb + BAR_XFULL + 8 * i, 1);
#pragma unroll
    for (int i = 0; i < 2; i++) mbar_expect(sb + BAR_CFULL + 8 * i, CTX);
    asm volatile("fence.mbarrier_init.release.cluster;" ::: "memory");
  }
  __syncthreads();
  asm volatile("barrier.cluster.arrive.relaxed.aligned;" ::: "memory");

  TS(1);
  if (wid < 8) {
    MlpCtx m;
    m.sb = sb; m.wg = wid >> 2; m.warp = wid & 3; m.rank = rank; m.peer_off = peer_off; m.zero = zero;
    m.optr = reinterpret_cast<uint8_t*>(out) + ((size_t)(r0 + 4 * m.wg + 2 * rank) * IMG + c0 + 8 * m.warp) * (CH * 2);
    m.caddr = sb + OFF_C + m.wg * C_BYTES + (lane & 3) * 512 + ((m.warp * 8 + (lane >> 2) + 2 * (lane & 3)) & 31) * 16;
    m.xaddr = sb + OFF_XRES + m.wg * 12288 + m.warp * 1536 + ((lane >> 3) & 1) * 6144 + ((lane >> 4) * 4 + ((lane >> 2) & 1)) * 192 + (lane & 3) * 16;
    m.unscale = 0;
    asm volatile("setmaxnreg.inc.sync.aligned.u32 %0;" ::"n"(REG_MLP));
    const uint32_t bad = mlp_role(m, reinterpret_cast<const uint4*>(w1), reinterpret_cast<const uint4*>(w2));
    asm volatile("barrier.cluster.arrive.relaxed.aligned;\nbarrier.cluster.wait.aligned;" ::: "memory");
    if (bad) {
      asm volatile("fence.proxy.async;" ::: "memory");
#pragma unroll 1
      for (int i = 0; i < 16; i++)
        if (bad >> i & 1)
          slow_tile(x, dw, w1, w2, out, r0 + 8 * i + 4 * m.wg + 2 * rank, c0 + 8 * m.warp,
                    reinterpret_cast<float*>(smem + OFF_XRES + wid * 3072));
    }
  } else {
    ConvCtx c;
    c.sb = sb; c.rank = rank; c.v = wid - 8; c.c0 = c0; c.r0 = r0; c.zero = zero; c.tm = &tm;
    c.peer_off = peer_off;
    c.xsrc = reinterpret_cast<const uint8_t*>(x) + ((size_t)(r0 + 2 * rank) * IMG + c0) * (CH * 2);
    c.optr = reinterpret_cast<uint8_t*>(out) + ((size_t)(r0 + 2 * rank) * IMG + c0) * (CH * 2);
    const int g = lane >> 2, t = lane & 3;
    c.a_raw = sb + OFF_RAW + ((t >> 1) * 19 + 2 * (g + (t & 1))) * PITCH + (PITCH == 112 ? (1 - rank) * 16 : 0) + 16 * c.v;
    c.a_c = sb + OFF_C + 6144 * rank + 512 * c.v + ((lane + 2 * c.v) & 31) * 16;
    if (wid < 12) {
      asm volatile("setmaxnreg.inc.sync.aligned.u32 %0;" ::"n"(REG_CONV));
      conv_role(c);
      __syncwarp();
      asm volatile("barrier.cluster.arrive.relaxed.aligned;\nbarrier.cluster.wait.aligned;\nexit;" ::: "memory");
    } else {
      asm volatile("setmaxnreg.dec.sync.aligned.u32 24;");
      if (wid == 14) TC(0);
      if (wid == 12) {
        if (elect_one()) {
          mbar_expect(sb + BAR_W + 48, 49 * CH * 2);
          bulk_load(sb + OFF_XRES, dw, 49 * CH * 2, sb + BAR_W + 48);
        }
        TS(2);
#define WLEAD 1
#pragma unroll 1
        for (int h = 0; h < 5; h++) {
          if (h >= WLEAD && h < WLEAD + 4) raw_refill(c, h - WLEAD - 4);
          const uint32_t o = h < 2 ? h * 36864 : (h + 1) * 24576, n = h < 2 ? 36864 : 24576, bar = sb + BAR_W + 8 * (h < 2 ? h : h + 1);
          const uint8_t* w = h < 2 ? reinterpret_cast<const uint8_t*>(w1) : reinterpret_cast<const uint8_t*>(w2) - OFF_W2;
          if (elect_one()) {
            mbar_expect(bar, n);
            bulk_load(sb + o, w + o, n, bar);
          }
        }
        TS(3);
        prod_rows(c);
        __syncwarp();
        asm volatile("barrier.cluster.arrive.relaxed.aligned;\nbarrier.cluster.wait.aligned;" ::: "memory");
      } else if (wid == 13) {
        prod_tiles(c);
        __syncwarp();
        asm volatile("barrier.cluster.arrive.relaxed.aligned;\nbarrier.cluster.wait.aligned;" ::: "memory");
        TC(3);
      }
    }
  }
}

typedef CUresult (*EncodeFn)(CUtensorMap*, CUtensorMapDataType, cuuint32_t, void*, const cuuint64_t*, const cuuint64_t*,
                             const cuuint32_t*, const cuuint32_t*, CUtensorMapInterleave, CUtensorMapSwizzle,
                             CUtensorMapL2promotion, CUtensorMapFloatOOBfill);

}

extern "C" void kernel_launch(void* const* d_in, const int* in_sizes, int n_in, void* d_out, int out_size) {
  const __nv_bfloat16* x = (const __nv_bfloat16*)d_in[0];
  const __nv_bfloat16* dw = (const __nv_bfloat16*)d_in[1];
  const __nv_bfloat16* w1 = (const __nv_bfloat16*)d_in[2];
  const __nv_bfloat16* w2 = (const __nv_bfloat16*)d_in[3];
  __nv_bfloat16* out = (__nv_bfloat16*)d_out;

  static EncodeFn encode = nullptr;
  if (!encode) {
    cudaDriverEntryPointQueryResult st;
    void* fn = nullptr;
    cudaGetDriverEntryPoint("cuTensorMapEncodeTiled", &fn, cudaEnableDefault, &st);
    encode = (EncodeFn)fn;
    cudaFuncSetAttribute(convnext_kernel, cudaFuncAttributeMaxDynamicSharedMemorySize, SMEM_BYTES);
  }
  CUtensorMap tm;
  cuuint64_t dims[4] = {CH, IMG / 2, IMG, 2};
  cuuint64_t strides[3] = {CH * 4, (cuuint64_t)IMG * CH * 2, CH * 2};
  cuuint32_t box[4] = {PITCH / 2, 19, 2, 1};
  cuuint32_t es[4] = {1, 1, 1, 1};
  encode(&tm, CU_TENSOR_MAP_DATA_TYPE_BFLOAT16, 4, (void*)x, dims, strides, box, es, CU_TENSOR_MAP_INTERLEAVE_NONE,
         CU_TENSOR_MAP_SWIZZLE_NONE, PROMO, CU_TENSOR_MAP_FLOAT_OOB_FILL_NONE);
  convnext_kernel<<<128, 512, SMEM_BYTES>>>(tm, x, dw, w1, w2, out, 0);
}
```

```cpp
#include <cuda_runtime.h>
#include <cuda_bf16.h>
#include <cuda.h>
#include <stdint.h>

#define PROMO CU_TENSOR_MAP_L2_PROMOTION_L2_128B
#define CTX 12288
#define CCNT 1
#define LA 1
#define PSL 100
#define PS0 1000
namespace {

constexpr int IMG = 512, CH = 96;
constexpr int NSTEP = 67;
constexpr int SIGMA = 8;
constexpr int NROUND = 68;

constexpr uint32_t OFF_W1 = 0;
constexpr uint32_t OFF_W2 = 73728;
constexpr uint32_t OFF_RAW = 147456;
#define PITCH 112
constexpr uint32_t RAW_PLANE = (38 * PITCH + 127) / 128 * 128;
constexpr uint32_t RAW_BYTES = 2 * RAW_PLANE;
constexpr uint32_t RAW_TX = 2 * 2 * 19 * PITCH;
constexpr uint32_t OFF_XRES = OFF_RAW + 4 * RAW_BYTES;
constexpr uint32_t OFF_C = OFF_XRES + 2 * 12288;
constexpr uint32_t C_BYTES = 12288;
constexpr uint32_t OFF_BAR = OFF_C + 2 * C_BYTES;
constexpr uint32_t BAR_RAW = OFF_BAR;
constexpr uint32_t BAR_CFULL = OFF_BAR + 32;
constexpr uint32_t BAR_CEMPTY = OFF_BAR + 48;
constexpr uint32_t BAR_XFULL = OFF_BAR + 80;
constexpr uint32_t BAR_W = OFF_BAR + 96;
constexpr uint32_t OFF_NRM = OFF_XRES + 9472;
constexpr uint32_t OFF_LT = OFF_BAR + 160;
constexpr uint32_t SMEM_BYTES = OFF_BAR + 160 + 600;

__device__ uint4 g_w[2 * 73728 / 16];
__device__ uint4 g_nrm[48];
__device__ unsigned g_done, g_seen;

constexpr float GELU_A = 0.32918364f;
constexpr uint32_t GELU_K2 = 0x40d940d9u;

constexpr int NB_CLOSE = 1, NB_SEC = 6  , NB_OPEN = 3, NB_PROD = 2, NB_PLAN = 4, NB_PREP = 5, NB_WG = 8  ;
#define REG_MLP 144
constexpr int REG_CONV = 488 - 2 * REG_MLP;

#define WG_FENCE() asm volatile("wgmma.fence.sync.aligned;" ::: "memory")
#define WG_COMMIT() asm volatile("wgmma.commit_group.sync.aligned;" ::: "memory")
#define WG_WAIT0() asm volatile("wgmma.wait_group.sync.aligned 0;" ::: "memory")
#define WG_WAIT1() asm volatile("wgmma.wait_group.sync.aligned 1;" ::: "memory")
#define PIN() asm volatile("pmevent 0;" ::: "memory")
#define NB_SYNC(id, n) asm volatile("bar.sync %0, %1;" ::"n"(id), "n"(n) : "memory")
#define NB_ARRIVE(id, n) asm volatile("bar.arrive %0, %1;" ::"n"(id), "n"(n) : "memory")

#define TS(idx)
#define TC(k)
#define TF(k)
#define TL(base, off)
#define TLDUMP(cond, base, n)

#define R24(c, d)                                                                                        \
  c(d[0]), c(d[1]), c(d[2]), c(d[3]), c(d[4]), c(d[5]), c(d[6]), c(d[7]), c(d[8]), c(d[9]), c(d[10]),    \
      c(d[11]), c(d[12]), c(d[13]), c(d[14]), c(d[15]), c(d[16]), c(d[17]), c(d[18]), c(d[19]), c(d[20]), \
      c(d[21]), c(d[22]), c(d[23])
#define WG_TXT(sd)                                                                             \
  "wgmma.mma_async.sync.aligned.m64n96k16.f16.f16.f16 "                                        \
  "{%0,%1,%2,%3,%4,%5,%6,%7,%8,%9,%10,%11,%12,%13,%14,%15,%16,%17,%18,%19,%20,%21,%22,%23}, " \
  "{%24,%25,%26,%27}, %28, " sd ", 1, 1, 1;\n"

__device__ __forceinline__ void wg_acc(uint32_t (&d)[24], const uint32_t* a, uint64_t db) {
  asm volatile(WG_TXT("1") : R24("+r", d) : "r"(a[0]), "r"(a[1]), "r"(a[2]), "r"(a[3]), "l"(db));
}
__device__ __forceinline__ void wg_init(uint32_t (&d)[24], const uint32_t* a, uint64_t db) {
  asm volatile(WG_TXT("0") : R24("=r", d) : "r"(a[0]), "r"(a[1]), "r"(a[2]), "r"(a[3]), "l"(db));
}
template <int N>
__device__ __forceinline__ void rfence(uint32_t (&d)[N]) {
#pragma unroll
  for (int i = 0; i < N; i++) asm volatile("" : "+r"(d[i])::"memory");
}
template <bool INIT, int KSTRIDE>
__device__ __forceinline__ void gemm6(uint32_t (&d)[24], const uint32_t (&a)[24], uint64_t db) {
#pragma unroll
  for (int k = 0; k < 6; k++) {
    if (INIT && k == 0) wg_init(d, &a[0], db);
    else wg_acc(d, &a[4 * k], db + k * KSTRIDE);
  }
  WG_COMMIT();
}

__device__ __forceinline__ void mbar_init(uint32_t bar, uint32_t cnt) {
  asm volatile("mbarrier.init.shared::cta.b64 [%0], %1;" ::"r"(bar), "r"(cnt) : "memory");
}
__device__ __forceinline__ void mbar_expect(uint32_t bar, uint32_t bytes) {
  asm volatile("mbarrier.arrive.expect_tx.shared::cta.b64 _, [%0], %1;" ::"r"(bar), "r"(bytes) : "memory");
}
__device__ __forceinline__ void mbar_arrive_cluster(uint32_t bar) {
  asm volatile("mbarrier.arrive.shared::cluster.b64 _, [%0];" ::"r"(bar) : "memory");
}
__device__ __forceinline__ bool mbar_try(uint32_t bar, uint32_t parity) {
  uint32_t ok;
  asm volatile(
      "{\n.reg .pred p;\nmbarrier.try_wait.parity.shared::cta.b64 p, [%1], %2;\nselp.u32 %0, 1, 0, p;\n}\n"
      : "=r"(ok)
      : "r"(bar), "r"(parity)
      : "memory");
  return ok;
}
__device__ __forceinline__ bool mbar_test(uint32_t bar, uint32_t parity) {
  uint32_t ok;
  asm volatile(
      "{\n.reg .pred p;\nmbarrier.test_wait.parity.shared::cta.b64 p, [%1], %2;\nselp.u32 %0, 1, 0, p;\n}\n"
      : "=r"(ok)
      : "r"(bar), "r"(parity)
      : "memory");
  return ok;
}
__device__ __forceinline__ void mbar_wait(uint32_t bar, uint32_t parity) {
  if (__builtin_expect(mbar_try(bar, parity), 1)) return;
#pragma unroll 1
  for (uint32_t n = 0; n < (1u << 16) && !mbar_try(bar, parity); n++) {}
}
__device__ __forceinline__ uint32_t mapa(uint32_t addr, uint32_t rank) {
  uint32_t r;
  asm("mapa.shared::cluster.u32 %0, %1, %2;" : "=r"(r) : "r"(addr), "r"(rank));
  return r;
}
__device__ __forceinline__ void tma_raw(uint32_t dst, const CUtensorMap* tm, int c, int w2, int h, uint32_t bar) {
  mbar_expect(bar, RAW_TX);
#pragma unroll
  for (int e = 0; e < 2; e++)
    asm volatile(
        "cp.async.bulk.tensor.4d.shared::cluster.global.mbarrier::complete_tx::bytes [%0], [%1, {%2, %3, %4, %5}], [%6];"
        ::"r"(dst + e * RAW_PLANE), "l"(tm), "r"(c), "r"(w2 + e), "r"(h), "r"(1 - e), "r"(bar)
        : "memory");
}
__device__ __forceinline__ void bulk_load(uint32_t dst, const void* src, uint32_t bytes, uint32_t bar) {
  asm volatile("cp.async.bulk.shared::cluster.global.mbarrier::complete_tx::bytes [%0], [%1], %2, [%3];" ::"r"(dst),
               "l"(src), "r"(bytes), "r"(bar)
               : "memory");
}
__device__ __forceinline__ void bulk_load_last(uint32_t dst, const void* src, uint32_t bytes, uint32_t bar) {
  asm volatile(
      "{\n.reg .b64 pol;\ncreatepolicy.fractional.L2::evict_first.b64 pol, 1.0;\n"
      "cp.async.bulk.shared::cluster.global.mbarrier::complete_tx::bytes.L2::cache_hint [%0], [%1], %2, [%3], pol;\n}\n" ::"r"(dst),
      "l"(src), "r"(bytes), "r"(bar)
      : "memory");
}
__device__ __forceinline__ uint32_t pack_bf16(float lo, float hi) {
  uint32_t r;
  asm("cvt.rn.bf16x2.f32 %0, %1, %2;" : "=r"(r) : "f"(hi), "f"(lo));
  return r;
}
__device__ __forceinline__ uint32_t pack_f16(float lo, float hi) {
  uint32_t r;
  asm("cvt.rn.f16x2.f32 %0, %1, %2;" : "=r"(r) : "f"(hi), "f"(lo));
  return r;
}
__device__ __forceinline__ float bf_lo(uint32_t v) { return __uint_as_float(v << 16); }
__device__ __forceinline__ float bf_hi(uint32_t v) { return __uint_as_float(v & 0xffff0000u); }
__device__ __forceinline__ uint32_t bf_add(uint32_t a, uint32_t b) {
  uint32_t r;
  asm("add.rn.bf16x2 %0, %1, %2;" : "=r"(r) : "r"(a), "r"(b));
  return r;
}
__device__ __forceinline__ uint32_t bf_mul(uint32_t a, uint32_t b) {
  uint32_t r;
  asm("mul.rn.bf16x2 %0, %1, %2;" : "=r"(r) : "r"(a), "r"(b));
  return r;
}
__device__ __forceinline__ uint32_t bf_fma(uint32_t a, uint32_t b, uint32_t c) {
  uint32_t r;
  asm("fma.rn.bf16x2 %0, %1, %2, %3;" : "=r"(r) : "r"(a), "r"(b), "r"(c));
  return r;
}

__device__ __forceinline__ uint32_t h_add(uint32_t a, uint32_t b) {
  uint32_t r;
  asm("add.rn.f16x2 %0, %1, %2;" : "=r"(r) : "r"(a), "r"(b));
  return r;
}
__device__ __forceinline__ uint32_t h_mul(uint32_t a, uint32_t b) {
  uint32_t r;
  asm("mul.rn.f16x2 %0, %1, %2;" : "=r"(r) : "r"(a), "r"(b));
  return r;
}
__device__ __forceinline__ uint32_t h_fma(uint32_t a, uint32_t b, uint32_t c) {
  uint32_t r;
  asm("fma.rn.f16x2 %0, %1, %2, %3;" : "=r"(r) : "r"(a), "r"(b), "r"(c));
  return r;
}
__device__ __forceinline__ float h_sum(uint32_t v) {
  float lo, hi;
  asm("{\n.reg .b16 l, h;\nmov.b32 {l, h}, %2;\ncvt.f32.f16 %0, l;\ncvt.f32.f16 %1, h;\n}\n" : "=f"(lo), "=f"(hi) : "r"(v));
  return lo + hi;
}
__device__ __forceinline__ void lds128(uint32_t (&v)[4], uint32_t a) {
  asm volatile("ld.shared.v4.b32 {%0,%1,%2,%3}, [%4];" : "=r"(v[0]), "=r"(v[1]), "=r"(v[2]), "=r"(v[3]) : "r"(a) : "memory");
}

template <int LO, int HI>
__device__ __forceinline__ void gelu(uint32_t (&o)[24], const uint32_t (&d)[24]) {
#pragma unroll
  for (int qq = LO; qq < HI; qq++) {
    const int q = (qq + 4) % 24;
    uint32_t t, u;
    asm("fma.rn.f16x2 %0, %1, %1, %2;" : "=r"(t) : "r"(d[q]), "r"(GELU_K2));
    asm("mul.rn.f16x2 %0, %1, %2;" : "=r"(u) : "r"(d[q]), "r"(t));
    asm("tanh.approx.f16x2 %0, %1;" : "=r"(t) : "r"(u));
    asm("fma.rn.f16x2 %0, %1, %2, %1;" : "=r"(o[q]) : "r"(d[q]), "r"(t));
  }
}

__device__ __forceinline__ uint32_t laneid() {
  uint32_t l;
  asm volatile("mov.u32 %0, %%laneid;" : "=r"(l));
  return l;
}

__device__ __forceinline__ bool elect_one() {
  uint32_t p;
  asm volatile("{\n.reg .pred p;\nelect.sync _|p, 0xffffffff;\nselp.u32 %0, 1, 0, p;\n}\n" : "=r"(p));
  return p;
}

__device__ __forceinline__ uint32_t clock_pin() {
  uint32_t t;
  asm volatile("mov.u32 %0, %%clock;" : "=r"(t)::"memory");
  return t;
}

struct MlpCtx {
  uint32_t sb;
  uint32_t caddr;
  uint32_t xaddr;
  uint32_t unscale;
  uint32_t peer_off;
  int wg, warp, rank, zero;
  uint8_t* optr;
};

__device__ __forceinline__ void ln_wait(const MlpCtx& m, int i) { mbar_wait(m.sb + BAR_CFULL + 8 * m.wg, i & 1); }
__device__ __forceinline__ void ln_load(const MlpCtx& m, uint32_t (&c)[24]) {
#pragma unroll
  for (int p = 0; p < 6; p++)
    asm volatile("ld.shared.v4.b32 {%0,%1,%2,%3}, [%4];"
                 : "=r"(c[4 * p]), "=r"(c[4 * p + 1]), "=r"(c[4 * p + 2]), "=r"(c[4 * p + 3])
                 : "r"(m.caddr + p * 2048)
                 : "memory");
}
__device__ __forceinline__ void ln_shfl(float (&st)[8], int mask) {
#pragma unroll
  for (int k = 0; k < 4; k++) st[4 + k] = __shfl_xor_sync(0xffffffffu, st[k], mask);
}
__device__ __forceinline__ void ln_fold(float (&st)[8]) {
#pragma unroll
  for (int k = 0; k < 4; k++) st[k] += st[4 + k];
}
__device__ __forceinline__ void ln_sums(const uint32_t (&c)[24], float (&st)[8]) {
#pragma unroll
  for (int r = 0; r < 2; r++) {
    uint32_t s0 = h_add(c[r], c[r + 2]), s1 = h_add(c[r + 4], c[r + 6]), s2 = h_add(c[r + 8], c[r + 10]);
    uint32_t s3 = h_add(c[r + 12], c[r + 14]), s4 = h_add(c[r + 16], c[r + 18]), s5 = h_add(c[r + 20], c[r + 22]);
    s0 = h_add(s0, s1); s2 = h_add(s2, s3); s4 = h_add(s4, s5);
    st[r] = h_sum(h_add(h_add(s0, s2), s4));
    uint32_t q0 = h_mul(c[r], c[r]), q1 = h_mul(c[r + 2], c[r + 2]);
#pragma unroll
    for (int p = 2; p < 12; p += 2) {
      q0 = h_fma(c[2 * p + r], c[2 * p + r], q0);
      q1 = h_fma(c[2 * p + 2 + r], c[2 * p + 2 + r], q1);
    }
    st[2 + r] = h_sum(h_add(q0, q1));
  }
}
__device__ __forceinline__ void ln_release(const MlpCtx& m) {
  const uint32_t e = m.sb + BAR_CEMPTY + 8 * (2 * m.rank + m.wg);
  asm volatile(
      "{\n.reg .pred p, q;\nelect.sync _|p, 0xffffffff;\nsetp.eq.and.s32 q, %3, 0, p;\n"
      "@q mbarrier.arrive.expect_tx.shared::cta.b64 _, [%0], %4;\n"
      "@p mbarrier.arrive.shared::cluster.b64 _, [%1];\n"
      "@p mbarrier.arrive.shared::cluster.b64 _, [%2];\n}\n" ::"r"(m.sb + BAR_CFULL + 8 * m.wg),
      "r"(e), "r"(e + m.peer_off), "r"(m.warp), "n"(CTX)
      : "memory");
}
__device__ __forceinline__ void ln_stats(float (&st)[8], uint32_t& bad, uint32_t bit) {
  bool ok = true;
#pragma unroll
  for (int r = 0; r < 2; r++) {
    const float nm = (st[r] + st[4 + r]) * (-1.0f / 96.0f);
    const float e2 = fmaf(st[2 + r] + st[6 + r], 1.0f / 96.0f, 1e-5f);
    float rs;
    asm("rsqrt.approx.ftz.f32 %0, %1;" : "=f"(rs) : "f"(fmaf(-nm, nm, e2)));
    ok = ok && (rs * rs * e2 <= 17.0f) && (e2 >= 1.001e-5f);
    const float rr = rs * GELU_A, dd = rr * nm;
    st[r] = __uint_as_float(pack_f16(rr, rr));
    st[2 + r] = __uint_as_float(pack_f16(dd, dd));
  }
  if (!ok) bad |= bit;
}
__device__ __forceinline__ void ln_apply(uint32_t (&a)[24], const uint32_t (&c)[24], const float (&st)[8]) {
#pragma unroll
  for (int p = 0; p < 24; p++) {
    a[p] = h_fma(c[p], __float_as_uint(st[p & 1]), __float_as_uint(st[2 + (p & 1)]));
  }
}

__device__ __noinline__ void slow_tile(const __nv_bfloat16* x, const __nv_bfloat16* dw, const __nv_bfloat16* w1,
                                       const __nv_bfloat16* w2, __nv_bfloat16* out, int row0, int col0, float* buf) {
  const int lane = threadIdx.x & 31;
  for (int px = 0; px < 16; px++) {
    const int row = row0 + (px >> 3), col = col0 + (px & 7);
    float c[3] = {0.f, 0.f, 0.f};
    for (int i = 0; i < 7; i++)
      for (int j = 0; j < 7; j++) {
        const int rr = row + i - 3, cc = col + j - 3;
        if (rr < 0 || rr >= IMG || cc < 0 || cc >= IMG) continue;
        for (int k = 0; k < 3; k++)
          c[k] = fmaf(__bfloat162float(x[((size_t)rr * IMG + cc) * CH + lane + 32 * k]), __bfloat162float(dw[(i * 7 + j) * CH + lane + 32 * k]), c[k]);
      }
    float mean = (c[0] + c[1] + c[2]) * (1.0f / 96.0f);
    for (int o = 16; o; o >>= 1) mean += __shfl_xor_sync(0xffffffffu, mean, o);
    float var = 0.f;
    for (int k = 0; k < 3; k++) { c[k] -= mean; var = fmaf(c[k] * (1.0f / 96.0f), c[k], var); }
    for (int o = 16; o; o >>= 1) var += __shfl_xor_sync(0xffffffffu, var, o);
    const float rs = 1.0f / sqrtf(var + 1e-5f);
    __syncwarp();
    for (int k = 0; k < 3; k++) buf[lane + 32 * k] = c[k] * rs;
    __syncwarp();
    for (int n = lane; n < 4 * CH; n += 32) {
      float y = 0.f;
      for (int k = 0; k < CH; k++) y = fmaf(buf[k], __bfloat162float(w1[k * 4 * CH + n]), y);
      buf[CH + n] = 0.5f * y * (1.0f + tanhf(0.7978845608f * (y + 0.044715f * y * y * y)));
    }
    __syncwarp();
    for (int n = lane; n < CH; n += 32) {
      float o = 0.f;
      for (int k = 0; k < 4 * CH; k++) o = fmaf(buf[CH + k], __bfloat162float(w2[k * CH + n]), o);
      const size_t idx = ((size_t)row * IMG + col) * CH + n;
      out[idx] = __float2bfloat16(__bfloat162float(x[idx]) + o);
    }
  }
}

__device__ __forceinline__ void x_load(const MlpCtx& m, uint32_t (&x)[24]) {
#pragma unroll
  for (int k = 0; k < 6; k++)
    asm volatile("ld.shared.v4.b32 {%0,%1,%2,%3}, [%4];"
                 : "=r"(x[4 * k]), "=r"(x[4 * k + 1]), "=r"(x[4 * k + 2]), "=r"(x[4 * k + 3])
                 : "r"(m.xaddr + (k / 3) * 384 + (k % 3) * 64)
                 : "memory");
}
template <int LO, int HI>
__device__ __forceinline__ void epilogue(const MlpCtx& m, const uint32_t (&d)[24], uint32_t (&x)[24]) {
#pragma unroll
  for (int k = LO; k < HI; k++) {
    const int r = k / 3, q = k % 3;
    uint32_t* y = &x[4 * k];
#pragma unroll
    for (int j = 0; j < 4; j++) {
      uint32_t v = d[2 * (4 * q + j) + r];
      float lo, hi;
      asm("{\n.reg .b16 l, h;\nmov.b32 {l, h}, %2;\ncvt.f32.f16 %0, l;\ncvt.f32.f16 %1, h;\n}\n" : "=f"(lo), "=f"(hi) : "r"(v));
      asm("fma.rn.bf16x2 %0, %1, %2, %0;" : "+r"(y[j]) : "r"(pack_bf16(lo, hi)), "r"(m.unscale));
    }
    asm volatile("st.shared.v4.b32 [%0], {%1,%2,%3,%4};" ::"r"(m.xaddr + r * 384 + q * 64), "r"(y[0]), "r"(y[1]), "r"(y[2]), "r"(y[3])
                 : "memory");
  }
}
__device__ __forceinline__ void out_store(const MlpCtx& m, int i) {
  asm volatile("fence.proxy.async.shared::cta;" ::: "memory");
  __syncwarp();
  if (elect_one()) {
    const uint32_t src = m.sb + OFF_XRES + m.wg * 12288 + m.warp * 1536;
    uint8_t* dst = m.optr + (size_t)i * (8 * IMG * CH * 2);
    asm volatile("cp.async.bulk.global.shared::cta.bulk_group [%0], [%1], 1536;" ::"l"(dst), "r"(src) : "memory");
    asm volatile("cp.async.bulk.global.shared::cta.bulk_group [%0], [%1], 1536;" ::"l"(dst + IMG * CH * 2), "r"(src + 6144) : "memory");
    asm volatile("cp.async.bulk.commit_group;" ::: "memory");
  }
}

#define FSET 3
template <int J> constexpr bool goes_first = J == FSET || J == ((FSET + 1) & 3);
template <int J> __device__ __forceinline__ void tok_wait() {
  if (goes_first<J>) NB_SYNC(NB_CLOSE, 256);
  else NB_SYNC(NB_SEC + (J & 1), 256);
}
template <int J> __device__ __forceinline__ void tok_next() {
  if (goes_first<J>) NB_ARRIVE(NB_SEC + (J & 1), 256);
  if (J == 0) NB_ARRIVE(NB_PROD, 160);
}
__device__ __forceinline__ void tok_pass() { NB_ARRIVE(NB_OPEN, 416); }
template <int J> __device__ __forceinline__ void tok_idle() { tok_wait<J>(); tok_next<J>(); tok_pass(); }

constexpr uint64_t CHK = 1152;

__device__ __forceinline__ float warp_sumsq(const uint32_t (&q)[4]) {
  const uint32_t t = bf_add(bf_add(q[0], q[1]), bf_add(q[2], q[3]));
  float f = bf_lo(t) + bf_hi(t);
#pragma unroll
  for (int o = 16; o; o >>= 1) f += __shfl_xor_sync(0xffffffffu, f, o);
  return f;
}
__device__ __forceinline__ int norm_exp(float f) { return (((int)(__float_as_uint(f * 1.5f) >> 23) - 127) >> 1) + 1; }
__device__ __forceinline__ int scale_exp(int e1, int e2) { return min(11 - e1 - e2, 14 - e2); }

__device__ __forceinline__ int sample_scale(const uint4* w1, const uint4* w2) {
  const int lane = threadIdx.x & 31;
  const uint4 a = __ldg(w1 + lane * 145), b = __ldg(w2 + lane * 145);
  const uint32_t qa[4] = {bf_mul(a.x, a.x), bf_mul(a.y, a.y), bf_mul(a.z, a.z), bf_mul(a.w, a.w)};
  const uint32_t qb[4] = {bf_mul(b.x, b.x), bf_mul(b.y, b.y), bf_mul(b.z, b.z), bf_mul(b.w, b.w)};
  return max(-64, min(64, scale_exp(norm_exp(144.f * warp_sumsq(qa)), norm_exp(144.f * warp_sumsq(qb))) - 1));
}

__device__ __forceinline__ void convert_tile(int t, const uint4* w1, const uint4* w2, uint32_t st) {
  const int lane = threadIdx.x & 31, k7 = lane & 7;
  uint32_t q[4] = {0, 0, 0, 0};
  uint4 v[6];
  const int j = t / 6, ks = t % 6, e = ks % 3, t4 = k7 >> 1;
  const uint4* src = t < 24 ? w1 + (48 * (ks / 3) + (e < 2 ? 8 * t4 + 4 * e : 32 + 4 * t4) + (k7 & 1)) * 48 + j * 12 + (lane >> 3)
                            : w2 + (t - 24) * 192 + (lane >> 2) * 12 + (lane & 3);
#pragma unroll
  for (int k = 0; k < 6; k++) v[k] = __ldg(src + (k / 3) * 96 + (k % 3) * 4);
  const int s = sample_scale(w1, w2);
  const uint32_t dst = st + k7 * 16 + (lane >> 3) * 256;
  if (t < 24) {
#pragma unroll
    for (int k = 0; k < 6; k++) {
      const uint32_t w[4] = {v[k].x, v[k].y, v[k].z, v[k].w};
      uint32_t o[4];
#pragma unroll
      for (int i = 0; i < 4; i++) {
        q[i] = bf_fma(w[i], w[i], q[i]);
        o[i] = pack_f16(bf_lo(w[i]), bf_hi(w[i]));
      }
      asm volatile("st.shared.v4.b32 [%0], {%1,%2,%3,%4};" ::"r"(dst + (k / 3) * 128 + (k % 3) * 1024), "r"(o[0]), "r"(o[1]), "r"(o[2]), "r"(o[3])
                   : "memory");
    }
  } else {
    constexpr float F = 0.5f / GELU_A, FHI = 1.515625f;
    const float p2 = __uint_as_float((uint32_t)(127 + s - 56) << 23);
    const uint32_t hi = pack_bf16(FHI * 0x1p-56f, FHI * 0x1p-56f), lo = pack_bf16((F - FHI) * 0x1p-56f, (F - FHI) * 0x1p-56f);
    const uint32_t pw = pack_bf16(p2, p2);
#pragma unroll
    for (int k = 0; k < 6; k++) {
      const uint32_t w[4] = {v[k].x, v[k].y, v[k].z, v[k].w};
      uint32_t o[4];
#pragma unroll
      for (int i = 0; i < 4; i++) {
        q[i] = bf_fma(w[i], w[i], q[i]);
        const uint32_t ws = bf_mul(w[i], pw), u = bf_fma(ws, hi, bf_mul(ws, lo));
        o[i] = (u & 0x7fff7fffu) * 7u + u;
      }
      asm volatile("stmatrix.sync.aligned.m8n8.x4.shared.b16 [%0], {%1,%2,%3,%4};" ::"r"(dst + (k / 3) * 128 + (k % 3) * 1024), "r"(o[0]),
                   "r"(o[1]), "r"(o[2]), "r"(o[3])
                   : "memory");
    }
  }
  const float f = warp_sumsq(q);
  asm volatile("st.shared.v2.b32 [%0], {%1,%2};" ::"r"(st + 3072), "r"(__float_as_uint(f)), "r"(s) : "memory");
  asm volatile("fence.proxy.async.shared::cta;" ::: "memory");
  __syncwarp();
  TS(4);
  if (elect_one()) {
    asm volatile("cp.async.bulk.global.shared::cta.bulk_group [%0], [%1], 3072;" ::"l"(g_w + t * 192), "r"(st) : "memory");
    asm volatile("cp.async.bulk.global.shared::cta.bulk_group [%0], [%1], 16;" ::"l"(g_nrm + t), "r"(st + 3072) : "memory");
    asm volatile("cp.async.bulk.commit_group;" ::: "memory");
    asm volatile("cp.async.bulk.wait_group 0;" ::: "memory");
    asm volatile("red.relaxed.gpu.global.add.u32 [%0], 1;" ::"l"(&g_done) : "memory");
  }
  TS(5);
}

__device__ __forceinline__ uint32_t mlp_role(const MlpCtx& m0) {
  MlpCtx m = m0;
  uint32_t bad = 0;
  asm volatile("barrier.cluster.wait.aligned;" ::: "memory");
  if ((m.sb & 0x3FFFF) != 1024) bad = 0xffffu;
  constexpr uint64_t dW1 = (uint64_t)((1024 + OFF_W1) >> 4) | ((uint64_t)8 << 16) | ((uint64_t)16 << 32);
  constexpr uint64_t dW2 = dW1 + (OFF_W2 >> 4);
  TS(6);
  uint32_t A1[24], g[24], d[24], cn[24], D2[24];
  float st[8];
  ln_wait(m, 0);
  ln_load(m, cn);
  ln_sums(cn, st);
  ln_shfl(st, 1);
  ln_release(m);
  ln_fold(st);
  ln_shfl(st, 2);
  ln_stats(st, bad, 1);
  ln_apply(A1, cn, st);
  {
    const int lane = threadIdx.x & 31;
    TS(2);
    mbar_wait(m.sb + BAR_W, 0);
    TS(3);
    float n1, n2;
    int s;
    asm volatile("ld.shared.b32 %0, [%1];" : "=r"(s) : "r"(m.sb + OFF_NRM + 4) : "memory");
    asm volatile("ld.shared.f32 %0, [%1];" : "=f"(n1) : "r"(m.sb + OFF_NRM + 16 * min(lane, 23)) : "memory");
    asm volatile("ld.shared.f32 %0, [%1];" : "=f"(n2) : "r"(m.sb + OFF_NRM + 384 + 16 * min(lane, 23)) : "memory");
    if (lane >= 24) n1 = n2 = 0.f;
#pragma unroll
    for (int o = 16; o; o >>= 1) {
      n1 += __shfl_xor_sync(0xffffffffu, n1, o);
      n2 += __shfl_xor_sync(0xffffffffu, n2, o);
    }
    const int e1 = norm_exp(n1), e2 = norm_exp(n2), smax = scale_exp(e1, e2);
    if (e1 > 12 || e1 < -5 || e2 > 50 || e2 < -50 || s > smax || s < smax - 5) bad = 0xffffu;
    m.unscale = __shfl_sync(0xffffffffu, ((uint32_t)(127 - s) << 7) * 0x10001u, 0);
  }
  TS(7);
  if (m.wg & m.rank) tok_idle<3>();
  if (m.wg) tok_idle<0>();
  if (m.wg | m.rank) tok_idle<1>();
  {
    uint32_t d0[24];
    WG_FENCE();
    tok_wait<2>();
    tok_next<2>();
    gemm6<true, 192>(d0, A1, dW1);
    tok_pass(); PIN();
    WG_WAIT0(); rfence(d0);
    WG_FENCE();
    tok_wait<3>();
    tok_next<3>();
    gemm6<true, 192>(d, A1, dW1 + CHK);
    tok_pass(); PIN();
    gelu<0, 24>(g, d0);
    PIN();
    mbar_wait(m.sb + BAR_W + 8, 0);
    ln_wait(m, 1);
    ln_load(m, cn);
    PIN();
    WG_WAIT0(); rfence(d);
  }
#define G2(INIT, a, j)                      \
  WG_FENCE();                               \
  tok_wait<j>();                            \
  gemm6<INIT, 192>(D2, a, dW2 + (j) * CHK); \
  tok_next<j>(); PIN();                     \
  TL(ltb, (j) * 5 + 1);
#define G1(dst, j, P)                       \
  TL(ltb, ((j) ^ 2) * 5 + 2);               \
  P(); WG_WAIT0(); rfence(D2);              \
  WG_FENCE();                               \
  gemm6<true, 192>(dst, A1, dW1 + (j) * CHK); \
  tok_pass(); P();                          \
  TL(ltb, ((j) ^ 2) * 5 + 3);
#define ROUND_END(dst, j)                   \
  TL(ltb, (j) * 5 + 4);                     \
  PIN(); WG_WAIT0(); rfence(dst);
#define GA 10
#define GB 12
#define GC 12
#define GD 10
#pragma unroll 1
  for (int i = 0;; i++) {
    uint32_t g1[24], d2[24], g2[24], d3[24], g3[24], d0[24];
    G2(true, g, 0)
    gelu<0, GA>(g1, d);
    G1(d2, 2, PIN)
    ln_sums(cn, st);
    gelu<GA, 24>(g1, d);
    PIN();
    ln_shfl(st, 1);
    ROUND_END(d2, 0)

    G2(false, g1, 1)
    ln_fold(st);
    gelu<0, GB>(g2, d2);
    PIN();
    ln_shfl(st, 2);
    G1(d3, 3, PIN)
    ln_stats(st, bad, 2u << i);
    gelu<GB, 24>(g2, d2);
    ROUND_END(d3, 1)

    if (i == 15) {
      G2(false, g2, 2)
      tok_pass();
      gelu<0, 24>(g3, d3);
      PIN();
      x_load(m, cn);
      ROUND_END(D2, 2)
      G2(false, g3, 3)
      tok_pass();
      WG_WAIT0(); rfence(D2);
      epilogue<0, 6>(m, D2, cn);
      break;
    }
    G2(false, g2, 2)
    ln_apply(A1, cn, st);
    PIN();
    gelu<0, GC>(g3, d3);
    G1(d0, 0, PIN)
    gelu<GC, 24>(g3, d3);
    PIN();
    x_load(m, cn);
    ROUND_END(d0, 2)

    G2(false, g3, 3)
    gelu<0, GD>(g, d0);
    G1(d, 1, PIN)
    epilogue<0, 6>(m, D2, cn);
    gelu<GD, 24>(g, d0);
    PIN();
    asm volatile("fence.proxy.async.shared::cta;" ::: "memory");
    ln_load(m, cn);
    ROUND_END(d, 3)
    TLDUMP(m.warp == 0 && (i >> 1) == LTRACE, m.sb + OFF_LT + m.wg * 160 + (i & 1) * 80, 20)
  }
  out_store(m, 15);
  if (m.wg == 0) { tok_idle<0>(); tok_idle<1>(); }
  asm volatile("cp.async.bulk.wait_group 0;" ::: "memory");
  return __reduce_or_sync(0xffffffffu, bad & 0xffffu);
}

struct ConvCtx {
  uint32_t sb;
  uint32_t a_raw, a_c;
  uint32_t peer_off;
  int rank, v, c0, r0, zero;
  const CUtensorMap* tm;
  const uint8_t* xsrc;
  uint8_t* optr;
};

__device__ __forceinline__ void raw_refill(const ConvCtx& c, int s) {
  if (s + 4 < NSTEP && elect_one())
    tma_raw(c.sb + OFF_RAW + (s & 3) * RAW_BYTES, c.tm, PITCH == 112 ? 56 * c.rank - 8 : 48 * c.rank, c.c0 / 2 - 2, c.r0 - 3 + 2 * (s + 4), c.sb + BAR_RAW + 8 * (s & 3));
}
__device__ __forceinline__ void step_ready(const ConvCtx& c, int s) {
  const int nx = (s + 1) & 3, par = ((s + 1) >> 2) & 1;
  if (s + LA < NSTEP) mbar_wait(c.sb + BAR_RAW + 8 * ((s + LA) & 3), ((s + LA) >> 2) & 1);
  if (s >= 7 && s < NSTEP) mbar_wait(c.sb + BAR_CEMPTY + 8 * (2 * (nx & 1) + (nx >> 1)), par);
}

__device__ __forceinline__ void c_release(const ConvCtx& c, uint32_t w) {
  const uint32_t e = c.sb + BAR_CEMPTY + 8 * (2 * c.rank + w);
  asm volatile(
      "{\n.reg .pred p;\nelect.sync _|p, 0xffffffff;\n"
      "@p mbarrier.arrive.expect_tx.shared::cta.b64 _, [%0], %3;\n"
      "@p mbarrier.arrive.shared::cluster.b64 _, [%1], 4;\n"
      "@p mbarrier.arrive.shared::cluster.b64 _, [%2], 4;\n}\n" ::"r"(c.sb + BAR_CFULL + 8 * w),
      "r"(e), "r"(e + c.peer_off), "n"(CTX)
      : "memory");
}

__device__ __forceinline__ void prod_rows(const ConvCtx& c) {
  asm volatile("barrier.cluster.wait.aligned;" ::: "memory");
#pragma unroll 1
  for (int s = 0; s < NROUND + SIGMA + c.rank; s++) {
    const int r = s - SIGMA - c.rank;
    const int u = (r & 1) ? (r >> 1) - 1 : (r >> 1) + 2;
    step_ready(c, s);
    if (u >= ((r & 1) ? 0 : 4) && u < 32) mbar_wait(c.sb + ((r & 1) ? BAR_XFULL : BAR_CFULL) + 8 * (u & 1), (u >> 1) & 1);
    if (s < SIGMA) NB_SYNC(NB_PLAN, 160);
    else NB_SYNC(NB_OPEN, 416);
    if (r == 3) TC(1);
    if (r == 55) TC(2);
    if (r >= -1 && r < 7) TS(7 + r);
    raw_refill(c, s);
  }
}
__device__ __forceinline__ void prod_tiles(const ConvCtx& c) {
  asm volatile("barrier.cluster.wait.aligned;" ::: "memory");
#pragma unroll 1
  for (int n = 0; n < NROUND / 2; n++) {
    const uint32_t w = (n + 1) & 1;
    const uint32_t buf = c.sb + OFF_XRES + w * 12288;
    NB_SYNC(NB_PROD, 160);
    if (n >= 1 && n < 29) c_release(c, w);
    if (n >= 3 && n < 33) {
      uint8_t* dst = c.optr + (size_t)(n - 3) * (4 * IMG * CH * 2);
      if (elect_one()) {
        asm volatile("cp.async.bulk.global.shared::cta.bulk_group [%0], [%1], 6144;" ::"l"(dst), "r"(buf) : "memory");
        asm volatile("cp.async.bulk.global.shared::cta.bulk_group [%0], [%1], 6144;" ::"l"(dst + IMG * CH * 2), "r"(buf + 6144) : "memory");
        asm volatile("cp.async.bulk.commit_group;" ::: "memory");
        asm volatile("cp.async.bulk.wait_group.read 0;" ::: "memory");
      }
      __syncwarp();
    }
    if (n >= 1 && n < 33) {
      const uint8_t* src = c.xsrc + (size_t)(n - 1) * (4 * IMG * CH * 2);
      if (elect_one()) {
        mbar_expect(c.sb + BAR_XFULL + 8 * w, 12288);
        bulk_load_last(buf, src, 6144, c.sb + BAR_XFULL + 8 * w);
        bulk_load_last(buf + 6144, src + IMG * CH * 2, 6144, c.sb + BAR_XFULL + 8 * w);
      }
    }
  }
  asm volatile("cp.async.bulk.wait_group 0;" ::: "memory");
}

template <int LO, int HI>
__device__ __forceinline__ void conv_ld8(uint32_t a, uint32_t (&r)[6][6]) {
#pragma unroll
  for (int j = LO; j < HI; j++)
    asm volatile("ld.shared.v4.b32 {%0,%1,%2,%3}, [%4];"
                 : "=r"(r[j][0]), "=r"(r[j][1]), "=r"(r[j][2]), "=r"(r[j][3])
                 : "r"(a + (j >> 1) * PITCH + (j & 1) * RAW_PLANE)
                 : "memory");
}
__device__ __forceinline__ void conv_ld4(uint32_t a, uint32_t (&r)[6][6]) {
#pragma unroll
  for (int j = 0; j < 6; j++)
    asm volatile("ld.shared.v2.b32 {%0,%1}, [%2];" : "=r"(r[j][4]), "=r"(r[j][5]) : "r"(a + (j >> 1) * PITCH + (j & 1) * RAW_PLANE) : "memory");
}
template <int LO, int HI>
__device__ __forceinline__ void conv_frags(uint32_t zero, const uint32_t (&r)[6][6], uint32_t (&A)[12][4]) {
#pragma unroll
  for (int ch = LO; ch < HI; ch++) {
    const uint32_t sel = (ch & 1) ? 0x7632 : 0x5410;
    A[ch][0] = __byte_perm(r[0][ch >> 1], r[1][ch >> 1], sel);
    A[ch][1] = __byte_perm(r[2][ch >> 1], r[3][ch >> 1], sel);
    A[ch][2] = A[ch][1] ^ zero;
    A[ch][3] = __byte_perm(r[4][ch >> 1], r[5][ch >> 1], sel);
    rfence(A[ch]);
  }
}
__device__ __forceinline__ void hmma_acc(uint32_t (&v)[4], const uint32_t (&a)[4], const uint32_t* b) {
  asm volatile("mma.sync.aligned.m16n8k16.row.col.f32.bf16.bf16.f32 {%0,%1,%2,%3}, {%4,%5,%6,%7}, {%8,%9}, {%0,%1,%2,%3};"
               : "+r"(v[0]), "+r"(v[1]), "+r"(v[2]), "+r"(v[3])
               : "r"(a[0]), "r"(a[1]), "r"(a[2]), "r"(a[3]), "r"(b[0]), "r"(b[1]));
}
__device__ __forceinline__ void hmma_new(uint32_t (&a)[4], const uint32_t* b) {
  asm volatile("mma.sync.aligned.m16n8k16.row.col.f32.bf16.bf16.f32 {%0,%1,%2,%3}, {%0,%1,%2,%3}, {%4,%5}, {%6,%6,%6,%6};"
               : "+r"(a[0]), "+r"(a[1]), "+r"(a[2]), "+r"(a[3])
               : "r"(b[0]), "r"(b[1]), "f"(0.f));
}

#define EARLY 5
template <int S2, bool GATED>
__device__ __forceinline__ void conv_step(const ConvCtx& c, int s, uint32_t (&K)[12], uint32_t (&V)[12][4], const uint32_t (&B)[12][4],
                                          uint32_t (&A)[12][4]) {
  const int nx = ((s + 1) & 2) | (S2 ^ 1);
  uint32_t r[6][6];
  TL(ltb, 0);
  if (!GATED) TS(6 + s);
  if (LA == 2) conv_ld4(c.a_raw + nx * RAW_BYTES + 64 - 8 * c.v, r);
  if (GATED) NB_SYNC(NB_OPEN, 416);
  else NB_SYNC(NB_PLAN, 160);
  if (LA == 1) conv_ld4(c.a_raw + nx * RAW_BYTES + 64 - 8 * c.v, r);
  PIN();
  TL(ltb, 1);
#pragma unroll
  for (int ch = 0; ch < 12; ch++) hmma_acc(V[11 - ch], A[11 - ch], &B[11 - ch][2]);
#pragma unroll
  for (int ch = 0; ch < 12 - EARLY; ch++) hmma_new(A[ch], &B[ch][0]);
  const uint32_t zero = c.zero & clock_pin();
  if (GATED) NB_ARRIVE(NB_CLOSE, 256);
#pragma unroll
  for (int ch = 12 - EARLY; ch < 12; ch++) hmma_new(A[ch], &B[ch][0]);
  PIN();
  TL(ltb, 2);
  const uint32_t off = ((S2 ^ 1) == c.rank) ? 0u : c.peer_off;
  const uint32_t dst = c.a_c + (GATED || s >= 3 ? off + (nx >> 1) * C_BYTES : OFF_XRES + 12288 - OFF_C);
  const uint32_t bar = c.sb + (GATED || s >= 3 ? off + BAR_CFULL + 8 * (nx >> 1) : BAR_W + 56);
#pragma unroll
  for (int q = 0; q < 12; q++) {
    const int ch = q & ~1, h = 2 * (q & 1);
    asm("add.rn.f16x2 %0, %0, %1;" : "+r"(K[q]) : "r"(pack_f16(__uint_as_float(V[ch][h + 1]), __uint_as_float(V[ch + 1][h]))));
  }
#pragma unroll
  for (int q = 0; q < 3; q++)
    asm volatile("st.async.weak.shared::cluster.mbarrier::complete_tx::bytes.v4.b32 [%0], {%1,%2,%3,%4}, [%5];" ::"r"(dst + q * 2048),
                 "r"(K[4 * q]), "r"(K[4 * q + 1]), "r"(K[4 * q + 2]), "r"(K[4 * q + 3]), "r"(bar)
                 : "memory");
  PIN();
#pragma unroll
  for (int q = 0; q < 12; q++) {
    const int ch = q & ~1, h = 2 * (q & 1);
    K[q] = pack_f16(__uint_as_float(V[ch][h]), __uint_as_float(V[ch + 1][h + 1]));
  }
  rfence(K);
  conv_frags<8, 12>(zero, r, V);
  PIN();
  conv_ld8<0, 6>(c.a_raw + nx * RAW_BYTES, r);
  conv_frags<0, 8>(zero, r, V);
  PIN();
  TL(ltb, 4);
  TLDUMP(c.v == 0 && lr >= 0 && lr < 10, c.sb + OFF_LT + 320 + lr * 20, 5)
}

__device__ __forceinline__ void conv_role(const ConvCtx& c) {
  const int lane = threadIdx.x & 31, g = lane >> 2, t = lane & 3;
  uint32_t B[12][4];
  {
    const int dc = (g >> 1) & 1, ro = g >> 2, rk = t >> 1;
    const int i0 = 4 * (g & 1) + rk - ro, j0 = 4 * (t & 1) - dc;
    const uint32_t base = c.sb + OFF_XRES + 96 * c.rank + (i0 * 7 + j0) * 192;
    TS(2);
    mbar_wait(c.sb + BAR_W + 48, 0);
    TS(3);
#pragma unroll
    for (int b = 0; b < 2; b++) {
      uint32_t w[4][6];
#pragma unroll
      for (int k = 0; k < 4; k++) {
        const int ok = (unsigned)(i0 + 2 * b) < 7u && (unsigned)(j0 + k) < 7u;
#pragma unroll
        for (int q = 0; q < 6; q++) w[k][q] = 0;
        asm volatile(
            "{\n.reg .pred p;\nsetp.ne.s32 p, %8, 0;\n@p ld.shared.v4.b32 {%0,%1,%2,%3}, [%6];\n@p ld.shared.v2.b32 {%4,%5}, [%7];\n}\n"
            : "+r"(w[k][0]), "+r"(w[k][1]), "+r"(w[k][2]), "+r"(w[k][3]), "+r"(w[k][4]), "+r"(w[k][5])
            : "r"(base + (b * 14 + k) * 192 + 16 * c.v), "r"(base + (b * 14 + k) * 192 + 64 + 8 * c.v), "r"(ok)
            : "memory");
      }
#pragma unroll
      for (int q = 0; q < 6; q++) {
        B[2 * q][2 * b] = __byte_perm(w[0][q], w[1][q], 0x5410);
        B[2 * q][2 * b + 1] = __byte_perm(w[2][q], w[3][q], 0x5410);
        B[2 * q + 1][2 * b] = __shfl_xor_sync(0xffffffffu, __byte_perm(w[0][q], w[1][q], 0x7632), 4);
        B[2 * q + 1][2 * b + 1] = __shfl_xor_sync(0xffffffffu, __byte_perm(w[2][q], w[3][q], 0x7632), 4);
      }
    }
  }
  TS(4);
  asm volatile("barrier.cluster.wait.aligned;" ::: "memory");
  uint32_t K1[12], K2[12], V[12][4];
#pragma unroll
  for (int ch = 0; ch < 12; ch++) {
    K1[ch] = K2[ch] = 0;
#pragma unroll
    for (int k = 0; k < 4; k++) V[ch][k] = 0;
  }
  uint32_t A[12][4], r[6][6];
  mbar_wait(c.sb + BAR_RAW, 0);
  TS(5);
  conv_ld8<0, 6>(c.a_raw, r);
  conv_frags<0, 8>(c.zero, r, A);
  PIN();
  conv_ld4(c.a_raw + 64 - 8 * c.v, r);
  conv_frags<8, 12>(c.zero, r, A);
  PIN();
  if (LA == 2) mbar_wait(c.sb + BAR_RAW + 8, 0);
  NB_ARRIVE(NB_CLOSE, 256);
#pragma unroll 1
  for (int s = 0; s < SIGMA; s += 2) {
    conv_step<0, false>(c, s, K1, V, B, A);
    conv_step<1, false>(c, s + 1, K2, A, B, V);
  }
#pragma unroll 1
  for (int s = SIGMA;; s += 2) {
    conv_step<0, true>(c, s, K1, V, B, A);
    if (s == NSTEP - 1) break;
    conv_step<1, true>(c, s + 1, K2, A, B, V);
  }
#pragma unroll 1
  for (int r = NSTEP - SIGMA - c.rank; r < NROUND - 1; r++) {
    NB_SYNC(NB_OPEN, 416);
    NB_ARRIVE(NB_CLOSE, 256);
  }
  NB_SYNC(NB_OPEN, 416);
}

__global__ void __cluster_dims__(2, 1, 1) __launch_bounds__(512, 1)
convnext_kernel(const __grid_constant__ CUtensorMap tm, const __nv_bfloat16* __restrict__ x, const __nv_bfloat16* __restrict__ dw,
                const __nv_bfloat16* __restrict__ w1, const __nv_bfloat16* __restrict__ w2, __nv_bfloat16* __restrict__ out,
                int zero) {
  extern __shared__ __align__(1024) uint8_t smem[];
  const uint32_t sb = (uint32_t)__cvta_generic_to_shared(smem);
  const int tid = threadIdx.x, lane = tid & 31;
  const int wid = __shfl_sync(0xffffffffu, tid >> 5, 0);
  const int rank = blockIdx.x & 1, cl = blockIdx.x >> 1;
  const int c0 = (cl & 15) * 32, r0 = (cl >> 4) * 128;
  const uint32_t peer_off = mapa(sb, rank ^ 1) - sb;

  TS(0);
  if (wid == 12 && elect_one()) {
    asm volatile("prefetch.tensormap [%0];" ::"l"(&tm) : "memory");
#pragma unroll
    for (int i = 0; i < 8; i++) mbar_init(sb + BAR_W + 8 * i, 1);
#pragma unroll
    for (int i = 0; i < 4; i++) mbar_init(sb + BAR_RAW + 8 * i, 1);
    asm volatile("fence.mbarrier_init.release.cluster;" ::: "memory");
  }
  if (wid == 14 && elect_one()) {
#pragma unroll
    for (int i = 0; i < 2; i++) mbar_init(sb + BAR_CFULL + 8 * i, CCNT);
#pragma unroll
    for (int i = 0; i < 4; i++) mbar_init(sb + BAR_CEMPTY + 8 * i, 4);
#pragma unroll
    for (int i = 0; i < 2; i++) mbar_init(sb + BAR_XFULL + 8 * i, 1);
#pragma unroll
    for (int i = 0; i < 2; i++) mbar_expect(sb + BAR_CFULL + 8 * i, CTX);
    asm volatile("fence.mbarrier_init.release.cluster;" ::: "memory");
  }
  if (wid == 0) {
    NB_ARRIVE(0, 512);
    asm volatile("barrier.cluster.arrive.relaxed.aligned;" ::: "memory");
    if (blockIdx.x < 48) convert_tile(blockIdx.x, reinterpret_cast<const uint4*>(w1), reinterpret_cast<const uint4*>(w2), sb);
  } else {
    NB_SYNC(0, 512);
    asm volatile("barrier.cluster.arrive.relaxed.aligned;" ::: "memory");
  }

  TS(1);
  if (wid < 8) {
    MlpCtx m;
    m.sb = sb; m.wg = wid >> 2; m.warp = wid & 3; m.rank = rank; m.peer_off = peer_off; m.zero = zero;
    m.optr = reinterpret_cast<uint8_t*>(out) + ((size_t)(r0 + 4 * m.wg + 2 * rank) * IMG + c0 + 8 * m.warp) * (CH * 2);
    m.caddr = sb + OFF_C + m.wg * C_BYTES + (lane & 3) * 512 + ((m.warp * 8 + (lane >> 2) + 2 * (lane & 3)) & 31) * 16;
    m.xaddr = sb + OFF_XRES + m.wg * 12288 + m.warp * 1536 + ((lane >> 3) & 1) * 6144 + ((lane >> 4) * 4 + ((lane >> 2) & 1)) * 192 + (lane & 3) * 16;
    m.unscale = 0;
    asm volatile("setmaxnreg.inc.sync.aligned.u32 %0;" ::"n"(REG_MLP));
    const uint32_t bad = mlp_role(m);
    asm volatile("barrier.cluster.arrive.relaxed.aligned;\nbarrier.cluster.wait.aligned;" ::: "memory");
    if (bad) {
      asm volatile("fence.proxy.async;" ::: "memory");
#pragma unroll 1
      for (int i = 0; i < 16; i++)
        if (bad >> i & 1)
          slow_tile(x, dw, w1, w2, out, r0 + 8 * i + 4 * m.wg + 2 * rank, c0 + 8 * m.warp,
                    reinterpret_cast<float*>(smem + OFF_XRES + wid * 3072));
    }
  } else {
    ConvCtx c;
    c.sb = sb; c.rank = rank; c.v = wid - 8; c.c0 = c0; c.r0 = r0; c.zero = zero; c.tm = &tm;
    c.peer_off = peer_off;
    c.xsrc = reinterpret_cast<const uint8_t*>(x) + ((size_t)(r0 + 2 * rank) * IMG + c0) * (CH * 2);
    c.optr = reinterpret_cast<uint8_t*>(out) + ((size_t)(r0 + 2 * rank) * IMG + c0) * (CH * 2);
    const int g = lane >> 2, t = lane & 3;
    c.a_raw = sb + OFF_RAW + ((t >> 1) * 19 + 2 * (g + (t & 1))) * PITCH + (PITCH == 112 ? (1 - rank) * 16 : 0) + 16 * c.v;
    c.a_c = sb + OFF_C + 6144 * rank + 512 * c.v + ((lane + 2 * c.v) & 31) * 16;
    if (wid < 12) {
      asm volatile("setmaxnreg.inc.sync.aligned.u32 %0;" ::"n"(REG_CONV));
      conv_role(c);
      __syncwarp();
      asm volatile("barrier.cluster.arrive.relaxed.aligned;\nbarrier.cluster.wait.aligned;\nexit;" ::: "memory");
    } else {
      asm volatile("setmaxnreg.dec.sync.aligned.u32 24;");
      if (wid == 14) TC(0);
      if (wid == 12) {
        if (elect_one()) {
          mbar_expect(sb + BAR_W + 48, 49 * CH * 2);
          bulk_load(sb + OFF_XRES, dw, 49 * CH * 2, sb + BAR_W + 48);
        }
        TS(2);
#pragma unroll 1
        for (int h = -4; h < 0; h++) raw_refill(c, h);
        TS(3);
        prod_rows(c);
        __syncwarp();
        asm volatile("barrier.cluster.arrive.relaxed.aligned;\nbarrier.cluster.wait.aligned;" ::: "memory");
      } else if (wid == 13) {
#pragma unroll 1
        for (int n = 0; n < (1 << 20); n++) {
          unsigned v;
          __nanosleep(n ? PSL : PS0);
          asm volatile("ld.acquire.gpu.global.u32 %0, [%1];" : "=r"(v) : "l"(&g_done) : "memory");
          if (__shfl_sync(0xffffffffu, v, 0) >= 48) break;
        }
        asm volatile("fence.proxy.async.global;" ::: "memory");
        if (elect_one()) {
          const uint8_t* w = reinterpret_cast<const uint8_t*>(g_w);
          mbar_expect(sb + BAR_W, 73728 + 768);
          mbar_expect(sb + BAR_W + 8, 73728);
          bulk_load(sb + OFF_NRM, g_nrm, 768, sb + BAR_W);
#pragma unroll
          for (int i = 0; i < 8; i++) bulk_load(sb + i * 18432, w + i * 18432, 18432, sb + BAR_W + 8 * (i >> 2));
          if (atomicAdd(&g_seen, 1u) == gridDim.x - 1) { g_done = 0; g_seen = 0; }
        }
        __syncwarp();
        prod_tiles(c);
        __syncwarp();
        asm volatile("barrier.cluster.arrive.relaxed.aligned;\nbarrier.cluster.wait.aligned;" ::: "memory");
        TC(3);
      }
    }
  }
}

typedef CUresult (*EncodeFn)(CUtensorMap*, CUtensorMapDataType, cuuint32_t, void*, const cuuint64_t*, const cuuint64_t*,
                             const cuuint32_t*, const cuuint32_t*, CUtensorMapInterleave, CUtensorMapSwizzle,
                             CUtensorMapL2promotion, CUtensorMapFloatOOBfill);

}

extern "C" void kernel_launch(void* const* d_in, const int* in_sizes, int n_in, void* d_out, int out_size) {
  const __nv_bfloat16* x = (const __nv_bfloat16*)d_in[0];
  const __nv_bfloat16* dw = (const __nv_bfloat16*)d_in[1];
  const __nv_bfloat16* w1 = (const __nv_bfloat16*)d_in[2];
  const __nv_bfloat16* w2 = (const __nv_bfloat16*)d_in[3];
  __nv_bfloat16* out = (__nv_bfloat16*)d_out;

  static EncodeFn encode = nullptr;
  if (!encode) {
    cudaDriverEntryPointQueryResult st;
    void* fn = nullptr;
    cudaGetDriverEntryPoint("cuTensorMapEncodeTiled", &fn, cudaEnableDefault, &st);
    encode = (EncodeFn)fn;
    cudaFuncSetAttribute(convnext_kernel, cudaFuncAttributeMaxDynamicSharedMemorySize, SMEM_BYTES);
  }
  CUtensorMap tm;
  cuuint64_t dims[4] = {CH, IMG / 2, IMG, 2};
  cuuint64_t strides[3] = {CH * 4, (cuuint64_t)IMG * CH * 2, CH * 2};
  cuuint32_t box[4] = {PITCH / 2, 19, 2, 1};
  cuuint32_t es[4] = {1, 1, 1, 1};
  encode(&tm, CU_TENSOR_MAP_DATA_TYPE_BFLOAT16, 4, (void*)x, dims, strides, box, es, CU_TENSOR_MAP_INTERLEAVE_NONE,
         CU_TENSOR_MAP_SWIZZLE_NONE, PROMO, CU_TENSOR_MAP_FLOAT_OOB_FILL_NONE);
  convnext_kernel<<<128, 512, SMEM_BYTES>>>(tm, x, dw, w1, w2, out, 0);
}
```

```cpp
#include <cuda_runtime.h>
#include <cuda_bf16.h>
#include <cuda.h>
#include <stdint.h>

#define PROMO CU_TENSOR_MAP_L2_PROMOTION_L2_128B
#define CTX 12288
#define CCNT 1
#define LA 1
#define PSL 100
#define PS0 1000
namespace {

constexpr int IMG = 512, CH = 96;
constexpr int NSTEP = 67;
constexpr int SIGMA = 8;
constexpr int NROUND = 68;

constexpr uint32_t OFF_W1 = 0;
constexpr uint32_t OFF_W2 = 73728;
constexpr uint32_t OFF_RAW = 147456;
constexpr uint32_t RAW_PA = 2560, RAW_PB = 1280;
constexpr uint32_t RAW_BYTES = 2 * RAW_PA + 2 * RAW_PB;
constexpr uint32_t RAW_TX = 2 * 38 * 96;
constexpr uint32_t OFF_XRES = OFF_RAW + 4 * RAW_BYTES;
constexpr uint32_t OFF_C = OFF_XRES + 2 * 12288;
constexpr uint32_t C_BYTES = 12288;
constexpr uint32_t OFF_BAR = OFF_C + 2 * C_BYTES;
constexpr uint32_t BAR_RAW = OFF_BAR;
constexpr uint32_t BAR_CFULL = OFF_BAR + 32;
constexpr uint32_t BAR_CEMPTY = OFF_BAR + 48;
constexpr uint32_t BAR_XFULL = OFF_BAR + 80;
constexpr uint32_t BAR_W = OFF_BAR + 96;
constexpr uint32_t OFF_NRM = OFF_XRES + 9472;
constexpr uint32_t OFF_LT = OFF_BAR + 160;
constexpr uint32_t SMEM_BYTES = OFF_BAR + 160 + 600;

__device__ uint4 g_w[2 * 73728 / 16];
__device__ uint4 g_nrm[48];
__device__ unsigned g_done, g_seen;

constexpr float GELU_A = 0.32918364f;
constexpr uint32_t GELU_K2 = 0x40d940d9u;

constexpr int NB_CLOSE = 1, NB_SEC = 6  , NB_OPEN = 3, NB_PROD = 2, NB_PLAN = 4, NB_PREP = 5, NB_WG = 8  ;
#define REG_MLP 144
constexpr int REG_CONV = 488 - 2 * REG_MLP;

#define WG_FENCE() asm volatile("wgmma.fence.sync.aligned;" ::: "memory")
#define WG_COMMIT() asm volatile("wgmma.commit_group.sync.aligned;" ::: "memory")
#define WG_WAIT0() asm volatile("wgmma.wait_group.sync.aligned 0;" ::: "memory")
#define WG_WAIT1() asm volatile("wgmma.wait_group.sync.aligned 1;" ::: "memory")
#define PIN() asm volatile("pmevent 0;" ::: "memory")
#define NB_SYNC(id, n) asm volatile("bar.sync %0, %1;" ::"n"(id), "n"(n) : "memory")
#define NB_ARRIVE(id, n) asm volatile("bar.arrive %0, %1;" ::"n"(id), "n"(n) : "memory")

#define TS(idx)
#define TC(k)
#define TF(k)
#define TL(base, off)
#define TLDUMP(cond, base, n)

#define R24(c, d)                                                                                        \
  c(d[0]), c(d[1]), c(d[2]), c(d[3]), c(d[4]), c(d[5]), c(d[6]), c(d[7]), c(d[8]), c(d[9]), c(d[10]),    \
      c(d[11]), c(d[12]), c(d[13]), c(d[14]), c(d[15]), c(d[16]), c(d[17]), c(d[18]), c(d[19]), c(d[20]), \
      c(d[21]), c(d[22]), c(d[23])
#define WG_TXT(sd)                                                                             \
  "wgmma.mma_async.sync.aligned.m64n96k16.f16.f16.f16 "                                        \
  "{%0,%1,%2,%3,%4,%5,%6,%7,%8,%9,%10,%11,%12,%13,%14,%15,%16,%17,%18,%19,%20,%21,%22,%23}, " \
  "{%24,%25,%26,%27}, %28, " sd ", 1, 1, 1;\n"

__device__ __forceinline__ void wg_acc(uint32_t (&d)[24], const uint32_t* a, uint64_t db) {
  asm volatile(WG_TXT("1") : R24("+r", d) : "r"(a[0]), "r"(a[1]), "r"(a[2]), "r"(a[3]), "l"(db));
}
__device__ __forceinline__ void wg_init(uint32_t (&d)[24], const uint32_t* a, uint64_t db) {
  asm volatile(WG_TXT("0") : R24("=r", d) : "r"(a[0]), "r"(a[1]), "r"(a[2]), "r"(a[3]), "l"(db));
}
template <int N>
__device__ __forceinline__ void rfence(uint32_t (&d)[N]) {
#pragma unroll
  for (int i = 0; i < N; i++) asm volatile("" : "+r"(d[i])::"memory");
}
template <bool INIT, int KSTRIDE>
__device__ __forceinline__ void gemm6(uint32_t (&d)[24], const uint32_t (&a)[24], uint64_t db) {
#pragma unroll
  for (int k = 0; k < 6; k++) {
    if (INIT && k == 0) wg_init(d, &a[0], db);
    else wg_acc(d, &a[4 * k], db + k * KSTRIDE);
  }
  WG_COMMIT();
}

__device__ __forceinline__ void mbar_init(uint32_t bar, uint32_t cnt) {
  asm volatile("mbarrier.init.shared::cta.b64 [%0], %1;" ::"r"(bar), "r"(cnt) : "memory");
}
__device__ __forceinline__ void mbar_expect(uint32_t bar, uint32_t bytes) {
  asm volatile("mbarrier.arrive.expect_tx.shared::cta.b64 _, [%0], %1;" ::"r"(bar), "r"(bytes) : "memory");
}
__device__ __forceinline__ void mbar_arrive_cluster(uint32_t bar) {
  asm volatile("mbarrier.arrive.shared::cluster.b64 _, [%0];" ::"r"(bar) : "memory");
}
__device__ __forceinline__ bool mbar_try(uint32_t bar, uint32_t parity) {
  uint32_t ok;
  asm volatile(
      "{\n.reg .pred p;\nmbarrier.try_wait.parity.shared::cta.b64 p, [%1], %2;\nselp.u32 %0, 1, 0, p;\n}\n"
      : "=r"(ok)
      : "r"(bar), "r"(parity)
      : "memory");
  return ok;
}
__device__ __forceinline__ bool mbar_test(uint32_t bar, uint32_t parity) {
  uint32_t ok;
  asm volatile(
      "{\n.reg .pred p;\nmbarrier.test_wait.parity.shared::cta.b64 p, [%1], %2;\nselp.u32 %0, 1, 0, p;\n}\n"
      : "=r"(ok)
      : "r"(bar), "r"(parity)
      : "memory");
  return ok;
}
__device__ __forceinline__ void mbar_wait(uint32_t bar, uint32_t parity) {
  if (__builtin_expect(mbar_try(bar, parity), 1)) return;
#pragma unroll 1
  for (uint32_t n = 0; n < (1u << 16) && !mbar_try(bar, parity); n++) {}
}
__device__ __forceinline__ uint32_t mapa(uint32_t addr, uint32_t rank) {
  uint32_t r;
  asm("mapa.shared::cluster.u32 %0, %1, %2;" : "=r"(r) : "r"(addr), "r"(rank));
  return r;
}
__device__ __forceinline__ void tma_raw(uint32_t dst, const CUtensorMap* tm, int rank, int w2, int h, uint32_t bar) {
  mbar_expect(bar, RAW_TX);
#pragma unroll
  for (int k = 0; k < 4; k++) {
    const int e = k & 1;
    asm volatile(
        "cp.async.bulk.tensor.4d.shared::cluster.global.mbarrier::complete_tx::bytes [%0], [%1, {%2, %3, %4, %5}], [%6];"
        ::"r"(dst + (k < 2 ? e * RAW_PA : 2 * RAW_PA + e * RAW_PB)), "l"(tm + (k >> 1)), "r"(k < 2 ? 64 * rank : 32 + 16 * rank), "r"(w2 + e),
        "r"(h), "r"(1 - e), "r"(bar)
        : "memory");
  }
}
__device__ __forceinline__ void bulk_load(uint32_t dst, const void* src, uint32_t bytes, uint32_t bar) {
  asm volatile("cp.async.bulk.shared::cluster.global.mbarrier::complete_tx::bytes [%0], [%1], %2, [%3];" ::"r"(dst),
               "l"(src), "r"(bytes), "r"(bar)
               : "memory");
}
__device__ __forceinline__ void bulk_load_last(uint32_t dst, const void* src, uint32_t bytes, uint32_t bar) {
  asm volatile(
      "{\n.reg .b64 pol;\ncreatepolicy.fractional.L2::evict_first.b64 pol, 1.0;\n"
      "cp.async.bulk.shared::cluster.global.mbarrier::complete_tx::bytes.L2::cache_hint [%0], [%1], %2, [%3], pol;\n}\n" ::"r"(dst),
      "l"(src), "r"(bytes), "r"(bar)
      : "memory");
}
__device__ __forceinline__ uint32_t pack_bf16(float lo, float hi) {
  uint32_t r;
  asm("cvt.rn.bf16x2.f32 %0, %1, %2;" : "=r"(r) : "f"(hi), "f"(lo));
  return r;
}
__device__ __forceinline__ uint32_t pack_f16(float lo, float hi) {
  uint32_t r;
  asm("cvt.rn.f16x2.f32 %0, %1, %2;" : "=r"(r) : "f"(hi), "f"(lo));
  return r;
}
__device__ __forceinline__ float bf_lo(uint32_t v) { return __uint_as_float(v << 16); }
__device__ __forceinline__ float bf_hi(uint32_t v) { return __uint_as_float(v & 0xffff0000u); }
__device__ __forceinline__ uint32_t bf_add(uint32_t a, uint32_t b) {
  uint32_t r;
  asm("add.rn.bf16x2 %0, %1, %2;" : "=r"(r) : "r"(a), "r"(b));
  return r;
}
__device__ __forceinline__ uint32_t bf_mul(uint32_t a, uint32_t b) {
  uint32_t r;
  asm("mul.rn.bf16x2 %0, %1, %2;" : "=r"(r) : "r"(a), "r"(b));
  return r;
}
__device__ __forceinline__ uint32_t bf_fma(uint32_t a, uint32_t b, uint32_t c) {
  uint32_t r;
  asm("fma.rn.bf16x2 %0, %1, %2, %3;" : "=r"(r) : "r"(a), "r"(b), "r"(c));
  return r;
}

__device__ __forceinline__ uint32_t h_add(uint32_t a, uint32_t b) {
  uint32_t r;
  asm("add.rn.f16x2 %0, %1, %2;" : "=r"(r) : "r"(a), "r"(b));
  return r;
}
__device__ __forceinline__ uint32_t h_mul(uint32_t a, uint32_t b) {
  uint32_t r;
  asm("mul.rn.f16x2 %0, %1, %2;" : "=r"(r) : "r"(a), "r"(b));
  return r;
}
__device__ __forceinline__ uint32_t h_fma(uint32_t a, uint32_t b, uint32_t c) {
  uint32_t r;
  asm("fma.rn.f16x2 %0, %1, %2, %3;" : "=r"(r) : "r"(a), "r"(b), "r"(c));
  return r;
}
__device__ __forceinline__ float h_sum(uint32_t v) {
  float lo, hi;
  asm("{\n.reg .b16 l, h;\nmov.b32 {l, h}, %2;\ncvt.f32.f16 %0, l;\ncvt.f32.f16 %1, h;\n}\n" : "=f"(lo), "=f"(hi) : "r"(v));
  return lo + hi;
}
__device__ __forceinline__ void lds128(uint32_t (&v)[4], uint32_t a) {
  asm volatile("ld.shared.v4.b32 {%0,%1,%2,%3}, [%4];" : "=r"(v[0]), "=r"(v[1]), "=r"(v[2]), "=r"(v[3]) : "r"(a) : "memory");
}

template <int LO, int HI>
__device__ __forceinline__ void gelu(uint32_t (&o)[24], const uint32_t (&d)[24]) {
#pragma unroll
  for (int qq = LO; qq < HI; qq++) {
    const int q = (qq + 4) % 24;
    uint32_t t, u;
    asm("fma.rn.f16x2 %0, %1, %1, %2;" : "=r"(t) : "r"(d[q]), "r"(GELU_K2));
    asm("mul.rn.f16x2 %0, %1, %2;" : "=r"(u) : "r"(d[q]), "r"(t));
    asm("tanh.approx.f16x2 %0, %1;" : "=r"(t) : "r"(u));
    asm("fma.rn.f16x2 %0, %1, %2, %1;" : "=r"(o[q]) : "r"(d[q]), "r"(t));
  }
}

__device__ __forceinline__ uint32_t laneid() {
  uint32_t l;
  asm volatile("mov.u32 %0, %%laneid;" : "=r"(l));
  return l;
}

__device__ __forceinline__ bool elect_one() {
  uint32_t p;
  asm volatile("{\n.reg .pred p;\nelect.sync _|p, 0xffffffff;\nselp.u32 %0, 1, 0, p;\n}\n" : "=r"(p));
  return p;
}

__device__ __forceinline__ uint32_t clock_pin() {
  uint32_t t;
  asm volatile("mov.u32 %0, %%clock;" : "=r"(t)::"memory");
  return t;
}

struct MlpCtx {
  uint32_t sb;
  uint32_t caddr;
  uint32_t xaddr;
  uint32_t unscale;
  uint32_t peer_off;
  int wg, warp, rank, zero;
  uint8_t* optr;
};

__device__ __forceinline__ void ln_wait(const MlpCtx& m, int i) { mbar_wait(m.sb + BAR_CFULL + 8 * m.wg, i & 1); }
__device__ __forceinline__ void ln_load(const MlpCtx& m, uint32_t (&c)[24]) {
#pragma unroll
  for (int p = 0; p < 6; p++)
    asm volatile("ld.shared.v4.b32 {%0,%1,%2,%3}, [%4];"
                 : "=r"(c[4 * p]), "=r"(c[4 * p + 1]), "=r"(c[4 * p + 2]), "=r"(c[4 * p + 3])
                 : "r"(m.caddr + p * 2048)
                 : "memory");
}
__device__ __forceinline__ void ln_shfl(float (&st)[8], int mask) {
#pragma unroll
  for (int k = 0; k < 4; k++) st[4 + k] = __shfl_xor_sync(0xffffffffu, st[k], mask);
}
__device__ __forceinline__ void ln_fold(float (&st)[8]) {
#pragma unroll
  for (int k = 0; k < 4; k++) st[k] += st[4 + k];
}
__device__ __forceinline__ void ln_sums(const uint32_t (&c)[24], float (&st)[8]) {
#pragma unroll
  for (int r = 0; r < 2; r++) {
    uint32_t s0 = h_add(c[r], c[r + 2]), s1 = h_add(c[r + 4], c[r + 6]), s2 = h_add(c[r + 8], c[r + 10]);
    uint32_t s3 = h_add(c[r + 12], c[r + 14]), s4 = h_add(c[r + 16], c[r + 18]), s5 = h_add(c[r + 20], c[r + 22]);
    s0 = h_add(s0, s1); s2 = h_add(s2, s3); s4 = h_add(s4, s5);
    st[r] = h_sum(h_add(h_add(s0, s2), s4));
    uint32_t q0 = h_mul(c[r], c[r]), q1 = h_mul(c[r + 2], c[r + 2]);
#pragma unroll
    for (int p = 2; p < 12; p += 2) {
      q0 = h_fma(c[2 * p + r], c[2 * p + r], q0);
      q1 = h_fma(c[2 * p + 2 + r], c[2 * p + 2 + r], q1);
    }
    st[2 + r] = h_sum(h_add(q0, q1));
  }
}
__device__ __forceinline__ void ln_release(const MlpCtx& m) {
  const uint32_t e = m.sb + BAR_CEMPTY + 8 * (2 * m.rank + m.wg);
  asm volatile(
      "{\n.reg .pred p, q;\nelect.sync _|p, 0xffffffff;\nsetp.eq.and.s32 q, %3, 0, p;\n"
      "@q mbarrier.arrive.expect_tx.shared::cta.b64 _, [%0], %4;\n"
      "@p mbarrier.arrive.shared::cluster.b64 _, [%1];\n"
      "@p mbarrier.arrive.shared::cluster.b64 _, [%2];\n}\n" ::"r"(m.sb + BAR_CFULL + 8 * m.wg),
      "r"(e), "r"(e + m.peer_off), "r"(m.warp), "n"(CTX)
      : "memory");
}
__device__ __forceinline__ void ln_stats(float (&st)[8], uint32_t& bad, uint32_t bit) {
  bool ok = true;
#pragma unroll
  for (int r = 0; r < 2; r++) {
    const float nm = (st[r] + st[4 + r]) * (-1.0f / 96.0f);
    const float e2 = fmaf(st[2 + r] + st[6 + r], 1.0f / 96.0f, 1e-5f);
    float rs;
    asm("rsqrt.approx.ftz.f32 %0, %1;" : "=f"(rs) : "f"(fmaf(-nm, nm, e2)));
    ok = ok && (rs * rs * e2 <= 17.0f) && (e2 >= 1.001e-5f);
    const float rr = rs * GELU_A, dd = rr * nm;
    st[r] = __uint_as_float(pack_f16(rr, rr));
    st[2 + r] = __uint_as_float(pack_f16(dd, dd));
  }
  if (!ok) bad |= bit;
}
__device__ __forceinline__ void ln_apply(uint32_t (&a)[24], const uint32_t (&c)[24], const float (&st)[8]) {
#pragma unroll
  for (int p = 0; p < 24; p++) {
    a[p] = h_fma(c[p], __float_as_uint(st[p & 1]), __float_as_uint(st[2 + (p & 1)]));
  }
}

__device__ __noinline__ void slow_tile(const __nv_bfloat16* x, const __nv_bfloat16* dw, const __nv_bfloat16* w1,
                                       const __nv_bfloat16* w2, __nv_bfloat16* out, int row0, int col0, float* buf) {
  const int lane = threadIdx.x & 31;
  for (int px = 0; px < 16; px++) {
    const int row = row0 + (px >> 3), col = col0 + (px & 7);
    float c[3] = {0.f, 0.f, 0.f};
    for (int i = 0; i < 7; i++)
      for (int j = 0; j < 7; j++) {
        const int rr = row + i - 3, cc = col + j - 3;
        if (rr < 0 || rr >= IMG || cc < 0 || cc >= IMG) continue;
        for (int k = 0; k < 3; k++)
          c[k] = fmaf(__bfloat162float(x[((size_t)rr * IMG + cc) * CH + lane + 32 * k]), __bfloat162float(dw[(i * 7 + j) * CH + lane + 32 * k]), c[k]);
      }
    float mean = (c[0] + c[1] + c[2]) * (1.0f / 96.0f);
    for (int o = 16; o; o >>= 1) mean += __shfl_xor_sync(0xffffffffu, mean, o);
    float var = 0.f;
    for (int k = 0; k < 3; k++) { c[k] -= mean; var = fmaf(c[k] * (1.0f / 96.0f), c[k], var); }
    for (int o = 16; o; o >>= 1) var += __shfl_xor_sync(0xffffffffu, var, o);
    const float rs = 1.0f / sqrtf(var + 1e-5f);
    __syncwarp();
    for (int k = 0; k < 3; k++) buf[lane + 32 * k] = c[k] * rs;
    __syncwarp();
    for (int n = lane; n < 4 * CH; n += 32) {
      float y = 0.f;
      for (int k = 0; k < CH; k++) y = fmaf(buf[k], __bfloat162float(w1[k * 4 * CH + n]), y);
      buf[CH + n] = 0.5f * y * (1.0f + tanhf(0.7978845608f * (y + 0.044715f * y * y * y)));
    }
    __syncwarp();
    for (int n = lane; n < CH; n += 32) {
      float o = 0.f;
      for (int k = 0; k < 4 * CH; k++) o = fmaf(buf[CH + k], __bfloat162float(w2[k * CH + n]), o);
      const size_t idx = ((size_t)row * IMG + col) * CH + n;
      out[idx] = __float2bfloat16(__bfloat162float(x[idx]) + o);
    }
  }
}

__device__ __forceinline__ void x_load(const MlpCtx& m, uint32_t (&x)[24]) {
#pragma unroll
  for (int k = 0; k < 6; k++)
    asm volatile("ld.shared.v4.b32 {%0,%1,%2,%3}, [%4];"
                 : "=r"(x[4 * k]), "=r"(x[4 * k + 1]), "=r"(x[4 * k + 2]), "=r"(x[4 * k + 3])
                 : "r"(m.xaddr + (k / 3) * 384 + (k % 3) * 64)
                 : "memory");
}
template <int LO, int HI>
__device__ __forceinline__ void epilogue(const MlpCtx& m, const uint32_t (&d)[24], uint32_t (&x)[24]) {
#pragma unroll
  for (int k = LO; k < HI; k++) {
    const int r = k / 3, q = k % 3;
    uint32_t* y = &x[4 * k];
#pragma unroll
    for (int j = 0; j < 4; j++) {
      uint32_t v = d[2 * (4 * q + j) + r];
      float lo, hi;
      asm("{\n.reg .b16 l, h;\nmov.b32 {l, h}, %2;\ncvt.f32.f16 %0, l;\ncvt.f32.f16 %1, h;\n}\n" : "=f"(lo), "=f"(hi) : "r"(v));
      asm("fma.rn.bf16x2 %0, %1, %2, %0;" : "+r"(y[j]) : "r"(pack_bf16(lo, hi)), "r"(m.unscale));
    }
    asm volatile("st.shared.v4.b32 [%0], {%1,%2,%3,%4};" ::"r"(m.xaddr + r * 384 + q * 64), "r"(y[0]), "r"(y[1]), "r"(y[2]), "r"(y[3])
                 : "memory");
  }
}
__device__ __forceinline__ void out_store(const MlpCtx& m, int i) {
  asm volatile("fence.proxy.async.shared::cta;" ::: "memory");
  __syncwarp();
  if (elect_one()) {
    const uint32_t src = m.sb + OFF_XRES + m.wg * 12288 + m.warp * 1536;
    uint8_t* dst = m.optr + (size_t)i * (8 * IMG * CH * 2);
    asm volatile("cp.async.bulk.global.shared::cta.bulk_group [%0], [%1], 1536;" ::"l"(dst), "r"(src) : "memory");
    asm volatile("cp.async.bulk.global.shared::cta.bulk_group [%0], [%1], 1536;" ::"l"(dst + IMG * CH * 2), "r"(src + 6144) : "memory");
    asm volatile("cp.async.bulk.commit_group;" ::: "memory");
  }
}

#define FSET 3
template <int J> constexpr bool goes_first = J == FSET || J == ((FSET + 1) & 3);
template <int J> __device__ __forceinline__ void tok_wait() {
  if (goes_first<J>) NB_SYNC(NB_CLOSE, 256);
  else NB_SYNC(NB_SEC + (J & 1), 256);
}
template <int J> __device__ __forceinline__ void tok_next() {
  if (goes_first<J>) NB_ARRIVE(NB_SEC + (J & 1), 256);
  if (J == 0) NB_ARRIVE(NB_PROD, 160);
}
__device__ __forceinline__ void tok_pass() { NB_ARRIVE(NB_OPEN, 416); }
template <int J> __device__ __forceinline__ void tok_idle() { tok_wait<J>(); tok_next<J>(); tok_pass(); }

constexpr uint64_t CHK = 1152;

__device__ __forceinline__ float warp_sumsq(const uint32_t (&q)[4]) {
  const uint32_t t = bf_add(bf_add(q[0], q[1]), bf_add(q[2], q[3]));
  float f = bf_lo(t) + bf_hi(t);
#pragma unroll
  for (int o = 16; o; o >>= 1) f += __shfl_xor_sync(0xffffffffu, f, o);
  return f;
}
__device__ __forceinline__ int norm_exp(float f) { return (((int)(__float_as_uint(f * 1.5f) >> 23) - 127) >> 1) + 1; }
__device__ __forceinline__ int scale_exp(int e1, int e2) { return min(11 - e1 - e2, 14 - e2); }

__device__ __forceinline__ int sample_scale(const uint4* w1, const uint4* w2) {
  const int lane = threadIdx.x & 31;
  const uint4 a = __ldg(w1 + lane * 145), b = __ldg(w2 + lane * 145);
  const uint32_t qa[4] = {bf_mul(a.x, a.x), bf_mul(a.y, a.y), bf_mul(a.z, a.z), bf_mul(a.w, a.w)};
  const uint32_t qb[4] = {bf_mul(b.x, b.x), bf_mul(b.y, b.y), bf_mul(b.z, b.z), bf_mul(b.w, b.w)};
  return max(-64, min(64, scale_exp(norm_exp(144.f * warp_sumsq(qa)), norm_exp(144.f * warp_sumsq(qb))) - 1));
}

__device__ __forceinline__ void convert_tile(int t, const uint4* w1, const uint4* w2, uint32_t st) {
  const int lane = threadIdx.x & 31, k7 = lane & 7;
  uint32_t q[4] = {0, 0, 0, 0};
  uint4 v[6];
  const int j = t / 6, ks = t % 6, e = ks % 3, t4 = k7 >> 1;
  const uint4* src = t < 24 ? w1 + ((e < 2 ? 64 * (ks / 3) + 8 * t4 + 4 * e : 32 + 16 * (ks / 3) + 4 * t4) + (k7 & 1)) * 48 + j * 12 + (lane >> 3)
                            : w2 + (t - 24) * 192 + (lane >> 2) * 12 + (lane & 3);
#pragma unroll
  for (int k = 0; k < 6; k++) v[k] = __ldg(src + (k / 3) * 96 + (k % 3) * 4);
  const int s = sample_scale(w1, w2);
  const uint32_t dst = st + k7 * 16 + (lane >> 3) * 256;
  if (t < 24) {
#pragma unroll
    for (int k = 0; k < 6; k++) {
      const uint32_t w[4] = {v[k].x, v[k].y, v[k].z, v[k].w};
      uint32_t o[4];
#pragma unroll
      for (int i = 0; i < 4; i++) {
        q[i] = bf_fma(w[i], w[i], q[i]);
        o[i] = pack_f16(bf_lo(w[i]), bf_hi(w[i]));
      }
      asm volatile("st.shared.v4.b32 [%0], {%1,%2,%3,%4};" ::"r"(dst + (k / 3) * 128 + (k % 3) * 1024), "r"(o[0]), "r"(o[1]), "r"(o[2]), "r"(o[3])
                   : "memory");
    }
  } else {
    constexpr float F = 0.5f / GELU_A, FHI = 1.515625f;
    const float p2 = __uint_as_float((uint32_t)(127 + s - 56) << 23);
    const uint32_t hi = pack_bf16(FHI * 0x1p-56f, FHI * 0x1p-56f), lo = pack_bf16((F - FHI) * 0x1p-56f, (F - FHI) * 0x1p-56f);
    const uint32_t pw = pack_bf16(p2, p2);
#pragma unroll
    for (int k = 0; k < 6; k++) {
      const uint32_t w[4] = {v[k].x, v[k].y, v[k].z, v[k].w};
      uint32_t o[4];
#pragma unroll
      for (int i = 0; i < 4; i++) {
        q[i] = bf_fma(w[i], w[i], q[i]);
        const uint32_t ws = bf_mul(w[i], pw), u = bf_fma(ws, hi, bf_mul(ws, lo));
        o[i] = (u & 0x7fff7fffu) * 7u + u;
      }
      asm volatile("stmatrix.sync.aligned.m8n8.x4.shared.b16 [%0], {%1,%2,%3,%4};" ::"r"(dst + (k / 3) * 128 + (k % 3) * 1024), "r"(o[0]),
                   "r"(o[1]), "r"(o[2]), "r"(o[3])
                   : "memory");
    }
  }
  const float f = warp_sumsq(q);
  asm volatile("st.shared.v2.b32 [%0], {%1,%2};" ::"r"(st + 3072), "r"(__float_as_uint(f)), "r"(s) : "memory");
  asm volatile("fence.proxy.async.shared::cta;" ::: "memory");
  __syncwarp();
  TS(4);
  if (elect_one()) {
    asm volatile("cp.async.bulk.global.shared::cta.bulk_group [%0], [%1], 3072;" ::"l"(g_w + t * 192), "r"(st) : "memory");
    asm volatile("cp.async.bulk.global.shared::cta.bulk_group [%0], [%1], 16;" ::"l"(g_nrm + t), "r"(st + 3072) : "memory");
    asm volatile("cp.async.bulk.commit_group;" ::: "memory");
    asm volatile("cp.async.bulk.wait_group 0;" ::: "memory");
    asm volatile("red.relaxed.gpu.global.add.u32 [%0], 1;" ::"l"(&g_done) : "memory");
  }
  TS(5);
}

__device__ __forceinline__ uint32_t mlp_role(const MlpCtx& m0) {
  MlpCtx m = m0;
  uint32_t bad = 0;
  asm volatile("barrier.cluster.wait.aligned;" ::: "memory");
  if ((m.sb & 0x3FFFF) != 1024) bad = 0xffffu;
  constexpr uint64_t dW1 = (uint64_t)((1024 + OFF_W1) >> 4) | ((uint64_t)8 << 16) | ((uint64_t)16 << 32);
  constexpr uint64_t dW2 = dW1 + (OFF_W2 >> 4);
  TS(6);
  uint32_t A1[24], g[24], d[24], cn[24], D2[24];
  float st[8];
  ln_wait(m, 0);
  ln_load(m, cn);
  ln_sums(cn, st);
  ln_shfl(st, 1);
  ln_release(m);
  ln_fold(st);
  ln_shfl(st, 2);
  ln_stats(st, bad, 1);
  ln_apply(A1, cn, st);
  {
    const int lane = threadIdx.x & 31;
    TS(2);
    mbar_wait(m.sb + BAR_W, 0);
    TS(3);
    float n1, n2;
    int s;
    asm volatile("ld.shared.b32 %0, [%1];" : "=r"(s) : "r"(m.sb + OFF_NRM + 4) : "memory");
    asm volatile("ld.shared.f32 %0, [%1];" : "=f"(n1) : "r"(m.sb + OFF_NRM + 16 * min(lane, 23)) : "memory");
    asm volatile("ld.shared.f32 %0, [%1];" : "=f"(n2) : "r"(m.sb + OFF_NRM + 384 + 16 * min(lane, 23)) : "memory");
    if (lane >= 24) n1 = n2 = 0.f;
#pragma unroll
    for (int o = 16; o; o >>= 1) {
      n1 += __shfl_xor_sync(0xffffffffu, n1, o);
      n2 += __shfl_xor_sync(0xffffffffu, n2, o);
    }
    const int e1 = norm_exp(n1), e2 = norm_exp(n2), smax = scale_exp(e1, e2);
    if (e1 > 12 || e1 < -5 || e2 > 50 || e2 < -50 || s > smax || s < smax - 5) bad = 0xffffu;
    m.unscale = __shfl_sync(0xffffffffu, ((uint32_t)(127 - s) << 7) * 0x10001u, 0);
  }
  TS(7);
  if (m.wg & m.rank) tok_idle<3>();
  if (m.wg) tok_idle<0>();
  if (m.wg | m.rank) tok_idle<1>();
  {
    uint32_t d0[24];
    WG_FENCE();
    tok_wait<2>();
    tok_next<2>();
    gemm6<true, 192>(d0, A1, dW1);
    tok_pass(); PIN();
    WG_WAIT0(); rfence(d0);
    WG_FENCE();
    tok_wait<3>();
    tok_next<3>();
    gemm6<true, 192>(d, A1, dW1 + CHK);
    tok_pass(); PIN();
    gelu<0, 24>(g, d0);
    PIN();
    mbar_wait(m.sb + BAR_W + 8, 0);
    ln_wait(m, 1);
    WG_WAIT0(); rfence(d);
  }
#define G2(INIT, a, j)                      \
  WG_FENCE();                               \
  tok_wait<j>();                            \
  gemm6<INIT, 192>(D2, a, dW2 + (j) * CHK); \
  tok_next<j>(); PIN();                     \
  TL(ltb, (j) * 5 + 1);
#define G1(dst, j, P)                       \
  TL(ltb, ((j) ^ 2) * 5 + 2);               \
  P(); WG_WAIT0(); rfence(D2);              \
  WG_FENCE();                               \
  gemm6<true, 192>(dst, A1, dW1 + (j) * CHK); \
  tok_pass(); P();                          \
  TL(ltb, ((j) ^ 2) * 5 + 3);
#define ROUND_END(dst, j)                   \
  TL(ltb, (j) * 5 + 4);                     \
  PIN(); WG_WAIT0(); rfence(dst);
#define GA 10
#define GB 12
#define GC 12
#define GD 10
#pragma unroll 1
  for (int i = 0;; i++) {
    uint32_t g1[24], d2[24], g2[24], d3[24], g3[24], d0[24];
    ln_load(m, cn);
    PIN();
    G2(true, g, 0)
    gelu<0, GA>(g1, d);
    G1(d2, 2, PIN)
    ln_sums(cn, st);
    gelu<GA, 24>(g1, d);
    PIN();
    ln_shfl(st, 1);
    ROUND_END(d2, 0)

    G2(false, g1, 1)
    ln_fold(st);
    gelu<0, GB>(g2, d2);
    PIN();
    ln_shfl(st, 2);
    G1(d3, 3, PIN)
    ln_stats(st, bad, 2u << i);
    gelu<GB, 24>(g2, d2);
    ROUND_END(d3, 1)

    if (i == 15) {
      G2(false, g2, 2)
      tok_pass();
      gelu<0, 24>(g3, d3);
      PIN();
      x_load(m, cn);
      ROUND_END(D2, 2)
      G2(false, g3, 3)
      tok_pass();
      WG_WAIT0(); rfence(D2);
      epilogue<0, 6>(m, D2, cn);
      break;
    }
    G2(false, g2, 2)
    ln_apply(A1, cn, st);
    PIN();
    gelu<0, GC>(g3, d3);
    G1(d0, 0, PIN)
    gelu<GC, 24>(g3, d3);
    PIN();
    x_load(m, cn);
    ROUND_END(d0, 2)

    G2(false, g3, 3)
    gelu<0, GD>(g, d0);
    G1(d, 1, PIN)
    epilogue<0, 6>(m, D2, cn);
    gelu<GD, 24>(g, d0);
    PIN();
    asm volatile("fence.proxy.async.shared::cta;" ::: "memory");
    ROUND_END(d, 3)
    TLDUMP(m.warp == 0 && (i >> 1) == LTRACE, m.sb + OFF_LT + m.wg * 160 + (i & 1) * 80, 20)
  }
  out_store(m, 15);
  if (m.wg == 0) { tok_idle<0>(); tok_idle<1>(); }
  asm volatile("cp.async.bulk.wait_group 0;" ::: "memory");
  return __reduce_or_sync(0xffffffffu, bad & 0xffffu);
}

struct ConvCtx {
  uint32_t sb;
  uint32_t a0, a_c;
  uint32_t peer_off;
  int rank, v, c0, r0, zero;
  const CUtensorMap* tm;
  const uint8_t* xsrc;
  uint8_t* optr;
};

__device__ __forceinline__ void raw_refill(const ConvCtx& c, int s) {
  if (s + 4 < NSTEP && elect_one())
    tma_raw(c.sb + OFF_RAW + (s & 3) * RAW_BYTES, c.tm, c.rank, c.c0 / 2 - 2, c.r0 - 3 + 2 * (s + 4), c.sb + BAR_RAW + 8 * (s & 3));
}
__device__ __forceinline__ void step_ready(const ConvCtx& c, int s) {
  const int nx = (s + 1) & 3, par = ((s + 1) >> 2) & 1;
  if (s + LA < NSTEP) mbar_wait(c.sb + BAR_RAW + 8 * ((s + LA) & 3), ((s + LA) >> 2) & 1);
  if (s >= 7 && s < NSTEP) mbar_wait(c.sb + BAR_CEMPTY + 8 * (2 * (nx & 1) + (nx >> 1)), par);
}

__device__ __forceinline__ void c_release(const ConvCtx& c, uint32_t w) {
  const uint32_t e = c.sb + BAR_CEMPTY + 8 * (2 * c.rank + w);
  asm volatile(
      "{\n.reg .pred p;\nelect.sync _|p, 0xffffffff;\n"
      "@p mbarrier.arrive.expect_tx.shared::cta.b64 _, [%0], %3;\n"
      "@p mbarrier.arrive.shared::cluster.b64 _, [%1], 4;\n"
      "@p mbarrier.arrive.shared::cluster.b64 _, [%2], 4;\n}\n" ::"r"(c.sb + BAR_CFULL + 8 * w),
      "r"(e), "r"(e + c.peer_off), "n"(CTX)
      : "memory");
}

__device__ __forceinline__ void prod_rows(const ConvCtx& c) {
  asm volatile("barrier.cluster.wait.aligned;" ::: "memory");
#pragma unroll 1
  for (int s = 0; s < NROUND + SIGMA + c.rank; s++) {
    const int r = s - SIGMA - c.rank;
    const int u = (r & 1) ? (r >> 1) - 1 : (r >> 1) + 2;
    step_ready(c, s);
    if (u >= ((r & 1) ? 0 : 4) && u < 32) mbar_wait(c.sb + ((r & 1) ? BAR_XFULL : BAR_CFULL) + 8 * (u & 1), (u >> 1) & 1);
    if (s < SIGMA) NB_SYNC(NB_PLAN, 160);
    else NB_SYNC(NB_OPEN, 416);
    if (r == 3) TC(1);
    if (r == 55) TC(2);
    if (r >= -1 && r < 7) TS(7 + r);
    raw_refill(c, s);
  }
}
__device__ __forceinline__ void prod_tiles(const ConvCtx& c) {
  asm volatile("barrier.cluster.wait.aligned;" ::: "memory");
#pragma unroll 1
  for (int n = 0; n < NROUND / 2; n++) {
    const uint32_t w = (n + 1) & 1;
    const uint32_t buf = c.sb + OFF_XRES + w * 12288;
    NB_SYNC(NB_PROD, 160);
    if (n >= 1 && n < 29) c_release(c, w);
    if (n >= 3 && n < 33) {
      uint8_t* dst = c.optr + (size_t)(n - 3) * (4 * IMG * CH * 2);
      if (elect_one()) {
        asm volatile("cp.async.bulk.global.shared::cta.bulk_group [%0], [%1], 6144;" ::"l"(dst), "r"(buf) : "memory");
        asm volatile("cp.async.bulk.global.shared::cta.bulk_group [%0], [%1], 6144;" ::"l"(dst + IMG * CH * 2), "r"(buf + 6144) : "memory");
        asm volatile("cp.async.bulk.commit_group;" ::: "memory");
        asm volatile("cp.async.bulk.wait_group.read 0;" ::: "memory");
      }
      __syncwarp();
    }
    if (n >= 1 && n < 33) {
      const uint8_t* src = c.xsrc + (size_t)(n - 1) * (4 * IMG * CH * 2);
      if (elect_one()) {
        mbar_expect(c.sb + BAR_XFULL + 8 * w, 12288);
        bulk_load_last(buf, src, 6144, c.sb + BAR_XFULL + 8 * w);
        bulk_load_last(buf + 6144, src + IMG * CH * 2, 6144, c.sb + BAR_XFULL + 8 * w);
      }
    }
  }
  asm volatile("cp.async.bulk.wait_group 0;" ::: "memory");
}

__device__ __forceinline__ void conv_ld8(uint32_t a0, uint32_t (&r)[6][6]) {
  const uint32_t a2 = a0 ^ (16 | ((a0 >> 2) & 32));
  const uint32_t a[3] = {a0, (a0 & 64) ? a2 : a0, a2};
#pragma unroll
  for (int j = 0; j < 6; j++)
    asm volatile("ld.shared.v4.b32 {%0,%1,%2,%3}, [%4];"
                 : "=r"(r[j][0]), "=r"(r[j][1]), "=r"(r[j][2]), "=r"(r[j][3])
                 : "r"(a[j >> 1] + (j >> 1) * 64 + (j & 1) * RAW_PA)
                 : "memory");
}
__device__ __forceinline__ void conv_ld4(uint32_t a0, uint32_t stage, int v, uint32_t (&r)[6][6]) {
  const uint32_t ab = ((a0 >> 1) & ~31u) + (stage / 2 + 2 * RAW_PA + 8 * v);
#pragma unroll
  for (int j = 0; j < 6; j++)
    asm volatile("ld.shared.v2.b32 {%0,%1}, [%2];" : "=r"(r[j][4]), "=r"(r[j][5]) : "r"(ab + (j >> 1) * 32 + (j & 1) * RAW_PB) : "memory");
}
template <int LO, int HI>
__device__ __forceinline__ void conv_frags(uint32_t zero, const uint32_t (&r)[6][6], uint32_t (&A)[12][4]) {
#pragma unroll
  for (int ch = LO; ch < HI; ch++) {
    const uint32_t sel = (ch & 1) ? 0x7632 : 0x5410;
    A[ch][0] = __byte_perm(r[0][ch >> 1], r[1][ch >> 1], sel);
    A[ch][1] = __byte_perm(r[2][ch >> 1], r[3][ch >> 1], sel);
    A[ch][2] = A[ch][1] ^ zero;
    A[ch][3] = __byte_perm(r[4][ch >> 1], r[5][ch >> 1], sel);
    rfence(A[ch]);
  }
}
__device__ __forceinline__ void hmma_acc(uint32_t (&v)[4], const uint32_t (&a)[4], const uint32_t* b) {
  asm volatile("mma.sync.aligned.m16n8k16.row.col.f32.bf16.bf16.f32 {%0,%1,%2,%3}, {%4,%5,%6,%7}, {%8,%9}, {%0,%1,%2,%3};"
               : "+r"(v[0]), "+r"(v[1]), "+r"(v[2]), "+r"(v[3])
               : "r"(a[0]), "r"(a[1]), "r"(a[2]), "r"(a[3]), "r"(b[0]), "r"(b[1]));
}
__device__ __forceinline__ void hmma_new(uint32_t (&a)[4], const uint32_t* b) {
  asm volatile("mma.sync.aligned.m16n8k16.row.col.f32.bf16.bf16.f32 {%0,%1,%2,%3}, {%0,%1,%2,%3}, {%4,%5}, {%6,%6,%6,%6};"
               : "+r"(a[0]), "+r"(a[1]), "+r"(a[2]), "+r"(a[3])
               : "r"(b[0]), "r"(b[1]), "f"(0.f));
}

#define EARLY 5
template <int S2, bool GATED>
__device__ __forceinline__ void conv_step(const ConvCtx& c, int s, uint32_t (&K)[12], uint32_t (&V)[12][4], const uint32_t (&B)[12][4],
                                          uint32_t (&A)[12][4]) {
  const int nx = ((s + 1) & 2) | (S2 ^ 1);
  uint32_t r[6][6];
  const uint32_t a0 = c.a0 + nx * RAW_BYTES;
  TL(ltb, 0);
  if (!GATED) TS(6 + s);
  if (LA == 2) conv_ld4(a0, c.sb + OFF_RAW + nx * RAW_BYTES, c.v, r);
  if (GATED) NB_SYNC(NB_OPEN, 416);
  else NB_SYNC(NB_PLAN, 160);
  if (LA == 1) conv_ld4(a0, c.sb + OFF_RAW + nx * RAW_BYTES, c.v, r);
  PIN();
  TL(ltb, 1);
#pragma unroll
  for (int ch = 0; ch < 12; ch++) hmma_acc(V[11 - ch], A[11 - ch], &B[11 - ch][2]);
#pragma unroll
  for (int ch = 0; ch < 12 - EARLY; ch++) hmma_new(A[ch], &B[ch][0]);
  const uint32_t zero = c.zero & clock_pin();
  if (GATED) NB_ARRIVE(NB_CLOSE, 256);
#pragma unroll
  for (int ch = 12 - EARLY; ch < 12; ch++) hmma_new(A[ch], &B[ch][0]);
  PIN();
  TL(ltb, 2);
  const uint32_t off = ((S2 ^ 1) == c.rank) ? 0u : c.peer_off;
  const uint32_t dst = c.a_c + (GATED || s >= 3 ? off + (nx >> 1) * C_BYTES : OFF_XRES + 12288 - OFF_C);
  const uint32_t bar = c.sb + (GATED || s >= 3 ? off + BAR_CFULL + 8 * (nx >> 1) : BAR_W + 56);
#pragma unroll
  for (int q = 0; q < 12; q++) {
    const int ch = q & ~1, h = 2 * (q & 1);
    asm("add.rn.f16x2 %0, %0, %1;" : "+r"(K[q]) : "r"(pack_f16(__uint_as_float(V[ch][h + 1]), __uint_as_float(V[ch + 1][h]))));
  }
#pragma unroll
  for (int q = 0; q < 3; q++)
    asm volatile("st.async.weak.shared::cluster.mbarrier::complete_tx::bytes.v4.b32 [%0], {%1,%2,%3,%4}, [%5];" ::"r"(dst + q * 2048),
                 "r"(K[4 * q]), "r"(K[4 * q + 1]), "r"(K[4 * q + 2]), "r"(K[4 * q + 3]), "r"(bar)
                 : "memory");
  PIN();
#pragma unroll
  for (int q = 0; q < 12; q++) {
    const int ch = q & ~1, h = 2 * (q & 1);
    K[q] = pack_f16(__uint_as_float(V[ch][h]), __uint_as_float(V[ch + 1][h + 1]));
  }
  rfence(K);
  conv_frags<8, 12>(zero, r, V);
  PIN();
  conv_ld8(a0, r);
  conv_frags<0, 8>(zero, r, V);
  PIN();
  TL(ltb, 4);
  TLDUMP(c.v == 0 && lr >= 0 && lr < 10, c.sb + OFF_LT + 320 + lr * 20, 5)
}

__device__ __forceinline__ void conv_role(ConvCtx c) {
  const int lane = laneid(), g = lane >> 2, t = lane & 3;
  const int u = (t >> 1) * 19 + 2 * (g + (t & 1));
  c.a0 = c.sb + OFF_RAW + u * 64 + ((c.v ^ (u >> 1)) & 3) * 16;
  c.a_c = c.sb + OFF_C + 6144 * c.rank + 512 * c.v + ((lane + 2 * c.v) & 31) * 16;
  uint32_t B[12][4];
  {
    const int dc = (g >> 1) & 1, ro = g >> 2, rk = t >> 1;
    const int i0 = 4 * (g & 1) + rk - ro, j0 = 4 * (t & 1) - dc;
    const uint32_t base = c.sb + OFF_XRES + (i0 * 7 + j0) * 192;
    TS(2);
    mbar_wait(c.sb + BAR_W + 48, 0);
    TS(3);
#pragma unroll
    for (int b = 0; b < 2; b++) {
      uint32_t w[4][6];
#pragma unroll
      for (int k = 0; k < 4; k++) {
        const int ok = (unsigned)(i0 + 2 * b) < 7u && (unsigned)(j0 + k) < 7u;
#pragma unroll
        for (int q = 0; q < 6; q++) w[k][q] = 0;
        asm volatile(
            "{\n.reg .pred p;\nsetp.ne.s32 p, %8, 0;\n@p ld.shared.v4.b32 {%0,%1,%2,%3}, [%6];\n@p ld.shared.v2.b32 {%4,%5}, [%7];\n}\n"
            : "+r"(w[k][0]), "+r"(w[k][1]), "+r"(w[k][2]), "+r"(w[k][3]), "+r"(w[k][4]), "+r"(w[k][5])
            : "r"(base + (b * 14 + k) * 192 + 128 * c.rank + 16 * c.v), "r"(base + (b * 14 + k) * 192 + 64 + 32 * c.rank + 8 * c.v), "r"(ok)
            : "memory");
      }
#pragma unroll
      for (int q = 0; q < 6; q++) {
        B[2 * q][2 * b] = __byte_perm(w[0][q], w[1][q], 0x5410);
        B[2 * q][2 * b + 1] = __byte_perm(w[2][q], w[3][q], 0x5410);
        B[2 * q + 1][2 * b] = __shfl_xor_sync(0xffffffffu, __byte_perm(w[0][q], w[1][q], 0x7632), 4);
        B[2 * q + 1][2 * b + 1] = __shfl_xor_sync(0xffffffffu, __byte_perm(w[2][q], w[3][q], 0x7632), 4);
      }
    }
  }
  TS(4);
  asm volatile("barrier.cluster.wait.aligned;" ::: "memory");
  uint32_t K1[12], K2[12], V[12][4];
#pragma unroll
  for (int ch = 0; ch < 12; ch++) {
    K1[ch] = K2[ch] = 0;
#pragma unroll
    for (int k = 0; k < 4; k++) V[ch][k] = 0;
  }
  uint32_t A[12][4], r[6][6];
  mbar_wait(c.sb + BAR_RAW, 0);
  TS(5);
  conv_ld8(c.a0, r);
  conv_frags<0, 8>(c.zero, r, A);
  PIN();
  conv_ld4(c.a0, c.sb + OFF_RAW, c.v, r);
  conv_frags<8, 12>(c.zero, r, A);
  PIN();
  if (LA == 2) mbar_wait(c.sb + BAR_RAW + 8, 0);
  NB_ARRIVE(NB_CLOSE, 256);
#pragma unroll 1
  for (int s = 0; s < SIGMA; s += 2) {
    conv_step<0, false>(c, s, K1, V, B, A);
    conv_step<1, false>(c, s + 1, K2, A, B, V);
  }
#pragma unroll 1
  for (int s = SIGMA;; s += 2) {
    conv_step<0, true>(c, s, K1, V, B, A);
    if (s == NSTEP - 1) break;
    conv_step<1, true>(c, s + 1, K2, A, B, V);
  }
#pragma unroll 1
  for (int r = NSTEP - SIGMA - c.rank; r < NROUND - 1; r++) {
    NB_SYNC(NB_OPEN, 416);
    NB_ARRIVE(NB_CLOSE, 256);
  }
  NB_SYNC(NB_OPEN, 416);
}

struct TMaps { CUtensorMap m[2]; };

__global__ void __cluster_dims__(2, 1, 1) __launch_bounds__(512, 1)
convnext_kernel(const __grid_constant__ TMaps tms, const __nv_bfloat16* __restrict__ x, const __nv_bfloat16* __restrict__ dw,
                const __nv_bfloat16* __restrict__ w1, const __nv_bfloat16* __restrict__ w2, __nv_bfloat16* __restrict__ out,
                int zero) {
  extern __shared__ __align__(1024) uint8_t smem[];
  const uint32_t sb = (uint32_t)__cvta_generic_to_shared(smem);
  const int tid = threadIdx.x, lane = tid & 31;
  const int wid = __shfl_sync(0xffffffffu, tid >> 5, 0);
  const int rank = blockIdx.x & 1, cl = blockIdx.x >> 1;
  const int c0 = (cl & 15) * 32, r0 = (cl >> 4) * 128;
  const uint32_t peer_off = mapa(sb, rank ^ 1) - sb;

  TS(0);
  if (wid == 12 && elect_one()) {
    asm volatile("prefetch.tensormap [%0];" ::"l"(&tms.m[0]) : "memory");
    asm volatile("prefetch.tensormap [%0];" ::"l"(&tms.m[1]) : "memory");
#pragma unroll
    for (int i = 0; i < 8; i++) mbar_init(sb + BAR_W + 8 * i, 1);
#pragma unroll
    for (int i = 0; i < 4; i++) mbar_init(sb + BAR_RAW + 8 * i, 1);
    asm volatile("fence.mbarrier_init.release.cluster;" ::: "memory");
  }
  if (wid == 14 && elect_one()) {
#pragma unroll
    for (int i = 0; i < 2; i++) mbar_init(sb + BAR_CFULL + 8 * i, CCNT);
#pragma unroll
    for (int i = 0; i < 4; i++) mbar_init(sb + BAR_CEMPTY + 8 * i, 4);
#pragma unroll
    for (int i = 0; i < 2; i++) mbar_init(sb + BAR_XFULL + 8 * i, 1);
#pragma unroll
    for (int i = 0; i < 2; i++) mbar_expect(sb + BAR_CFULL + 8 * i, CTX);
    asm volatile("fence.mbarrier_init.release.cluster;" ::: "memory");
  }
  if (wid == 0) {
    NB_ARRIVE(0, 512);
    asm volatile("barrier.cluster.arrive.relaxed.aligned;" ::: "memory");
    if (blockIdx.x < 48) convert_tile(blockIdx.x, reinterpret_cast<const uint4*>(w1), reinterpret_cast<const uint4*>(w2), sb);
  } else {
    NB_SYNC(0, 512);
    asm volatile("barrier.cluster.arrive.relaxed.aligned;" ::: "memory");
  }

  TS(1);
  if (wid < 8) {
    MlpCtx m;
    m.sb = sb; m.wg = wid >> 2; m.warp = wid & 3; m.rank = rank; m.peer_off = peer_off; m.zero = zero;
    m.optr = reinterpret_cast<uint8_t*>(out) + ((size_t)(r0 + 4 * m.wg + 2 * rank) * IMG + c0 + 8 * m.warp) * (CH * 2);
    m.caddr = sb + OFF_C + m.wg * C_BYTES + (lane & 3) * 512 + ((m.warp * 8 + (lane >> 2) + 2 * (lane & 3)) & 31) * 16;
    m.xaddr = sb + OFF_XRES + m.wg * 12288 + m.warp * 1536 + ((lane >> 3) & 1) * 6144 + ((lane >> 4) * 4 + ((lane >> 2) & 1)) * 192 + (lane & 3) * 16;
    m.unscale = 0;
    asm volatile("setmaxnreg.inc.sync.aligned.u32 %0;" ::"n"(REG_MLP));
    const uint32_t bad = mlp_role(m);
    asm volatile("barrier.cluster.arrive.relaxed.aligned;\nbarrier.cluster.wait.aligned;" ::: "memory");
    if (bad) {
      asm volatile("fence.proxy.async;" ::: "memory");
#pragma unroll 1
      for (int i = 0; i < 16; i++)
        if (bad >> i & 1)
          slow_tile(x, dw, w1, w2, out, r0 + 8 * i + 4 * m.wg + 2 * rank, c0 + 8 * m.warp,
                    reinterpret_cast<float*>(smem + OFF_XRES + wid * 3072));
    }
  } else {
    ConvCtx c;
    c.sb = sb; c.rank = rank; c.v = wid - 8; c.c0 = c0; c.r0 = r0; c.zero = zero; c.tm = tms.m;
    c.peer_off = peer_off;
    c.xsrc = reinterpret_cast<const uint8_t*>(x) + ((size_t)(r0 + 2 * rank) * IMG + c0) * (CH * 2);
    c.optr = reinterpret_cast<uint8_t*>(out) + ((size_t)(r0 + 2 * rank) * IMG + c0) * (CH * 2);
    if (wid < 12) {
      asm volatile("setmaxnreg.inc.sync.aligned.u32 %0;" ::"n"(REG_CONV));
      conv_role(c);
      __syncwarp();
      asm volatile("barrier.cluster.arrive.relaxed.aligned;\nbarrier.cluster.wait.aligned;\nexit;" ::: "memory");
    } else {
      asm volatile("setmaxnreg.dec.sync.aligned.u32 24;");
      if (wid == 14) TC(0);
      if (wid == 12) {
        if (elect_one()) {
          mbar_expect(sb + BAR_W + 48, 49 * CH * 2);
          bulk_load(sb + OFF_XRES, dw, 49 * CH * 2, sb + BAR_W + 48);
        }
        TS(2);
#pragma unroll 1
        for (int h = -4; h < 0; h++) raw_refill(c, h);
        TS(3);
        prod_rows(c);
        __syncwarp();
        asm volatile("barrier.cluster.arrive.relaxed.aligned;\nbarrier.cluster.wait.aligned;" ::: "memory");
      } else if (wid == 13) {
#pragma unroll 1
        for (int n = 0; n < (1 << 20); n++) {
          unsigned v;
          __nanosleep(n ? PSL : PS0);
          asm volatile("ld.acquire.gpu.global.u32 %0, [%1];" : "=r"(v) : "l"(&g_done) : "memory");
          if (__shfl_sync(0xffffffffu, v, 0) >= 48) break;
        }
        asm volatile("fence.proxy.async.global;" ::: "memory");
        if (elect_one()) {
          const uint8_t* w = reinterpret_cast<const uint8_t*>(g_w);
          mbar_expect(sb + BAR_W, 73728 + 768);
          mbar_expect(sb + BAR_W + 8, 73728);
          bulk_load(sb + OFF_NRM, g_nrm, 768, sb + BAR_W);
#pragma unroll
          for (int i = 0; i < 8; i++) bulk_load(sb + i * 18432, w + i * 18432, 18432, sb + BAR_W + 8 * (i >> 2));
          if (atomicAdd(&g_seen, 1u) == gridDim.x - 1) { g_done = 0; g_seen = 0; }
        }
        __syncwarp();
        prod_tiles(c);
        __syncwarp();
        asm volatile("barrier.cluster.arrive.relaxed.aligned;\nbarrier.cluster.wait.aligned;" ::: "memory");
        TC(3);
      }
    }
  }
}

typedef CUresult (*EncodeFn)(CUtensorMap*, CUtensorMapDataType, cuuint32_t, void*, const cuuint64_t*, const cuuint64_t*,
                             const cuuint32_t*, const cuuint32_t*, CUtensorMapInterleave, CUtensorMapSwizzle,
                             CUtensorMapL2promotion, CUtensorMapFloatOOBfill);

}

extern "C" void kernel_launch(void* const* d_in, const int* in_sizes, int n_in, void* d_out, int out_size) {
  const __nv_bfloat16* x = (const __nv_bfloat16*)d_in[0];
  const __nv_bfloat16* dw = (const __nv_bfloat16*)d_in[1];
  const __nv_bfloat16* w1 = (const __nv_bfloat16*)d_in[2];
  const __nv_bfloat16* w2 = (const __nv_bfloat16*)d_in[3];
  __nv_bfloat16* out = (__nv_bfloat16*)d_out;

  static EncodeFn encode = nullptr;
  if (!encode) {
    cudaDriverEntryPointQueryResult st;
    void* fn = nullptr;
    cudaGetDriverEntryPoint("cuTensorMapEncodeTiled", &fn, cudaEnableDefault, &st);
    encode = (EncodeFn)fn;
    cudaFuncSetAttribute(convnext_kernel, cudaFuncAttributeMaxDynamicSharedMemorySize, SMEM_BYTES);
  }
  TMaps tm;
  cuuint64_t dims[4] = {CH, IMG / 2, IMG, 2};
  cuuint64_t strides[3] = {CH * 4, (cuuint64_t)IMG * CH * 2, CH * 2};
  cuuint32_t es[4] = {1, 1, 1, 1};
  for (int i = 0; i < 2; i++) {
    cuuint32_t box[4] = {i ? 16u : 32u, 19, 2, 1};
    encode(&tm.m[i], CU_TENSOR_MAP_DATA_TYPE_BFLOAT16, 4, (void*)x, dims, strides, box, es, CU_TENSOR_MAP_INTERLEAVE_NONE,
           i ? CU_TENSOR_MAP_SWIZZLE_NONE : CU_TENSOR_MAP_SWIZZLE_64B, PROMO, CU_TENSOR_MAP_FLOAT_OOB_FILL_NONE);
  }
  convnext_kernel<<<128, 512, SMEM_BYTES>>>(tm, x, dw, w1, w2, out, 0);
}
```

```cpp
#include <cuda_runtime.h>
#include <cuda_bf16.h>
#include <cuda.h>
#include <stdint.h>

#define PROMO CU_TENSOR_MAP_L2_PROMOTION_L2_128B
#define CTX 6144
#define CCNT 5
#define PSL 100
#define PS0 1000
namespace {

constexpr int IMG = 512, CH = 96;
constexpr int NSTEP = 67;
constexpr int SIGMA = 8;
constexpr int NROUND = 68;

constexpr uint32_t OFF_W1 = 0;
constexpr uint32_t OFF_W2 = 73728;
constexpr uint32_t OFF_RAW = 147456;
constexpr uint32_t RAW_PA = 2560, RAW_PB = 1280;
constexpr uint32_t RAW_BYTES = 2 * RAW_PA + 2 * RAW_PB;
constexpr uint32_t RAW_TX = 2 * 38 * 96;
constexpr uint32_t OFF_XRES = OFF_RAW + 4 * RAW_BYTES;
constexpr uint32_t OFF_C = OFF_XRES + 2 * 12288;
constexpr uint32_t C_BYTES = 12288;
constexpr uint32_t OFF_BAR = OFF_C + 2 * C_BYTES;
constexpr uint32_t BAR_RAW = OFF_BAR;
constexpr uint32_t BAR_CFULL = OFF_BAR + 32;
constexpr uint32_t BAR_CEMPTY = OFF_BAR + 48;
constexpr uint32_t BAR_XFULL = OFF_BAR + 80;
constexpr uint32_t BAR_W = OFF_BAR + 96;
constexpr uint32_t OFF_NRM = OFF_XRES + 9472;
constexpr uint32_t OFF_LT = OFF_BAR + 160;
constexpr uint32_t SMEM_BYTES = OFF_BAR + 160 + 600;

__device__ uint4 g_w[2 * 73728 / 16];
__device__ uint4 g_nrm[48];
__device__ unsigned g_done, g_seen;

constexpr float GELU_A = 0.32918364f;
constexpr uint32_t GELU_K2 = 0x40d940d9u;

constexpr int NB_CLOSE = 1, NB_SEC = 6  , NB_OPEN = 3, NB_PROD = 2, NB_PLAN = 4, NB_PREP = 5, NB_WG = 8  ;
#define REG_MLP 144
constexpr int REG_CONV = 488 - 2 * REG_MLP;

#define WG_FENCE() asm volatile("wgmma.fence.sync.aligned;" ::: "memory")
#define WG_COMMIT() asm volatile("wgmma.commit_group.sync.aligned;" ::: "memory")
#define WG_WAIT0() asm volatile("wgmma.wait_group.sync.aligned 0;" ::: "memory")
#define WG_WAIT1() asm volatile("wgmma.wait_group.sync.aligned 1;" ::: "memory")
#define PIN() asm volatile("pmevent 0;" ::: "memory")
#define NB_SYNC(id, n) asm volatile("bar.sync %0, %1;" ::"n"(id), "n"(n) : "memory")
#define NB_ARRIVE(id, n) asm volatile("bar.arrive %0, %1;" ::"n"(id), "n"(n) : "memory")

#define TS(idx)
#define TC(k)
#define TF(k)
#define TL(base, off)
#define TLDUMP(cond, base, n)

#define R24(c, d)                                                                                        \
  c(d[0]), c(d[1]), c(d[2]), c(d[3]), c(d[4]), c(d[5]), c(d[6]), c(d[7]), c(d[8]), c(d[9]), c(d[10]),    \
      c(d[11]), c(d[12]), c(d[13]), c(d[14]), c(d[15]), c(d[16]), c(d[17]), c(d[18]), c(d[19]), c(d[20]), \
      c(d[21]), c(d[22]), c(d[23])
#define WG_TXT(sd)                                                                             \
  "wgmma.mma_async.sync.aligned.m64n96k16.f16.f16.f16 "                                        \
  "{%0,%1,%2,%3,%4,%5,%6,%7,%8,%9,%10,%11,%12,%13,%14,%15,%16,%17,%18,%19,%20,%21,%22,%23}, " \
  "{%24,%25,%26,%27}, %28, " sd ", 1, 1, 1;\n"

__device__ __forceinline__ void wg_acc(uint32_t (&d)[24], const uint32_t* a, uint64_t db) {
  asm volatile(WG_TXT("1") : R24("+r", d) : "r"(a[0]), "r"(a[1]), "r"(a[2]), "r"(a[3]), "l"(db));
}
__device__ __forceinline__ void wg_init(uint32_t (&d)[24], const uint32_t* a, uint64_t db) {
  asm volatile(WG_TXT("0") : R24("=r", d) : "r"(a[0]), "r"(a[1]), "r"(a[2]), "r"(a[3]), "l"(db));
}
template <int N>
__device__ __forceinline__ void rfence(uint32_t (&d)[N]) {
#pragma unroll
  for (int i = 0; i < N; i++) asm volatile("" : "+r"(d[i])::"memory");
}
template <bool INIT, int KSTRIDE>
__device__ __forceinline__ void gemm6(uint32_t (&d)[24], const uint32_t (&a)[24], uint64_t db) {
#pragma unroll
  for (int k = 0; k < 6; k++) {
    if (INIT && k == 0) wg_init(d, &a[0], db);
    else wg_acc(d, &a[4 * k], db + k * KSTRIDE);
  }
  WG_COMMIT();
}

__device__ __forceinline__ void mbar_init(uint32_t bar, uint32_t cnt) {
  asm volatile("mbarrier.init.shared::cta.b64 [%0], %1;" ::"r"(bar), "r"(cnt) : "memory");
}
__device__ __forceinline__ void mbar_expect(uint32_t bar, uint32_t bytes) {
  asm volatile("mbarrier.arrive.expect_tx.shared::cta.b64 _, [%0], %1;" ::"r"(bar), "r"(bytes) : "memory");
}
__device__ __forceinline__ void mbar_arrive_cluster(uint32_t bar) {
  asm volatile("mbarrier.arrive.shared::cluster.b64 _, [%0];" ::"r"(bar) : "memory");
}
__device__ __forceinline__ bool mbar_try(uint32_t bar, uint32_t parity) {
  uint32_t ok;
  asm volatile(
      "{\n.reg .pred p;\nmbarrier.try_wait.parity.shared::cta.b64 p, [%1], %2;\nselp.u32 %0, 1, 0, p;\n}\n"
      : "=r"(ok)
      : "r"(bar), "r"(parity)
      : "memory");
  return ok;
}
__device__ __forceinline__ bool mbar_test(uint32_t bar, uint32_t parity) {
  uint32_t ok;
  asm volatile(
      "{\n.reg .pred p;\nmbarrier.test_wait.parity.shared::cta.b64 p, [%1], %2;\nselp.u32 %0, 1, 0, p;\n}\n"
      : "=r"(ok)
      : "r"(bar), "r"(parity)
      : "memory");
  return ok;
}
__device__ __forceinline__ void mbar_wait(uint32_t bar, uint32_t parity) {
  if (__builtin_expect(mbar_try(bar, parity), 1)) return;
#pragma unroll 1
  for (uint32_t n = 0; n < (1u << 16) && !mbar_try(bar, parity); n++) {}
}
__device__ __forceinline__ uint32_t mapa(uint32_t addr, uint32_t rank) {
  uint32_t r;
  asm("mapa.shared::cluster.u32 %0, %1, %2;" : "=r"(r) : "r"(addr), "r"(rank));
  return r;
}
__device__ __forceinline__ void tma_raw(uint32_t dst, const CUtensorMap* tm, int rank, int w2, int h, uint32_t bar) {
  mbar_expect(bar, RAW_TX);
#pragma unroll
  for (int k = 0; k < 4; k++) {
    const int e = k & 1;
    asm volatile(
        "cp.async.bulk.tensor.4d.shared::cluster.global.mbarrier::complete_tx::bytes [%0], [%1, {%2, %3, %4, %5}], [%6];"
        ::"r"(dst + (k < 2 ? e * RAW_PA : 2 * RAW_PA + e * RAW_PB)), "l"(tm + (k >> 1)), "r"(k < 2 ? 64 * rank : 32 + 16 * rank), "r"(w2 + e),
        "r"(h), "r"(1 - e), "r"(bar)
        : "memory");
  }
}
__device__ __forceinline__ void bulk_load(uint32_t dst, const void* src, uint32_t bytes, uint32_t bar) {
  asm volatile("cp.async.bulk.shared::cluster.global.mbarrier::complete_tx::bytes [%0], [%1], %2, [%3];" ::"r"(dst),
               "l"(src), "r"(bytes), "r"(bar)
               : "memory");
}
__device__ __forceinline__ void bulk_load_last(uint32_t dst, const void* src, uint32_t bytes, uint32_t bar) {
  asm volatile(
      "{\n.reg .b64 pol;\ncreatepolicy.fractional.L2::evict_first.b64 pol, 1.0;\n"
      "cp.async.bulk.shared::cluster.global.mbarrier::complete_tx::bytes.L2::cache_hint [%0], [%1], %2, [%3], pol;\n}\n" ::"r"(dst),
      "l"(src), "r"(bytes), "r"(bar)
      : "memory");
}
__device__ __forceinline__ uint32_t pack_bf16(float lo, float hi) {
  uint32_t r;
  asm("cvt.rn.bf16x2.f32 %0, %1, %2;" : "=r"(r) : "f"(hi), "f"(lo));
  return r;
}
__device__ __forceinline__ uint32_t pack_f16(float lo, float hi) {
  uint32_t r;
  asm("cvt.rn.f16x2.f32 %0, %1, %2;" : "=r"(r) : "f"(hi), "f"(lo));
  return r;
}
__device__ __forceinline__ float bf_lo(uint32_t v) { return __uint_as_float(v << 16); }
__device__ __forceinline__ float bf_hi(uint32_t v) { return __uint_as_float(v & 0xffff0000u); }
__device__ __forceinline__ uint32_t bf_add(uint32_t a, uint32_t b) {
  uint32_t r;
  asm("add.rn.bf16x2 %0, %1, %2;" : "=r"(r) : "r"(a), "r"(b));
  return r;
}
__device__ __forceinline__ uint32_t bf_mul(uint32_t a, uint32_t b) {
  uint32_t r;
  asm("mul.rn.bf16x2 %0, %1, %2;" : "=r"(r) : "r"(a), "r"(b));
  return r;
}
__device__ __forceinline__ uint32_t bf_fma(uint32_t a, uint32_t b, uint32_t c) {
  uint32_t r;
  asm("fma.rn.bf16x2 %0, %1, %2, %3;" : "=r"(r) : "r"(a), "r"(b), "r"(c));
  return r;
}

__device__ __forceinline__ uint32_t h_add(uint32_t a, uint32_t b) {
  uint32_t r;
  asm("add.rn.f16x2 %0, %1, %2;" : "=r"(r) : "r"(a), "r"(b));
  return r;
}
__device__ __forceinline__ uint32_t h_mul(uint32_t a, uint32_t b) {
  uint32_t r;
  asm("mul.rn.f16x2 %0, %1, %2;" : "=r"(r) : "r"(a), "r"(b));
  return r;
}
__device__ __forceinline__ uint32_t h_fma(uint32_t a, uint32_t b, uint32_t c) {
  uint32_t r;
  asm("fma.rn.f16x2 %0, %1, %2, %3;" : "=r"(r) : "r"(a), "r"(b), "r"(c));
  return r;
}
__device__ __forceinline__ float h_sum(uint32_t v) {
  float lo, hi;
  asm("{\n.reg .b16 l, h;\nmov.b32 {l, h}, %2;\ncvt.f32.f16 %0, l;\ncvt.f32.f16 %1, h;\n}\n" : "=f"(lo), "=f"(hi) : "r"(v));
  return lo + hi;
}
__device__ __forceinline__ void lds128(uint32_t (&v)[4], uint32_t a) {
  asm volatile("ld.shared.v4.b32 {%0,%1,%2,%3}, [%4];" : "=r"(v[0]), "=r"(v[1]), "=r"(v[2]), "=r"(v[3]) : "r"(a) : "memory");
}

template <int LO, int HI>
__device__ __forceinline__ void gelu(uint32_t (&o)[24], const uint32_t (&d)[24]) {
#pragma unroll
  for (int qq = LO; qq < HI; qq++) {
    const int q = (qq + 4) % 24;
    uint32_t t, u;
    asm("fma.rn.f16x2 %0, %1, %1, %2;" : "=r"(t) : "r"(d[q]), "r"(GELU_K2));
    asm("mul.rn.f16x2 %0, %1, %2;" : "=r"(u) : "r"(d[q]), "r"(t));
    asm("tanh.approx.f16x2 %0, %1;" : "=r"(t) : "r"(u));
    asm("fma.rn.f16x2 %0, %1, %2, %1;" : "=r"(o[q]) : "r"(d[q]), "r"(t));
  }
}

__device__ __forceinline__ uint32_t laneid() {
  uint32_t l;
  asm volatile("mov.u32 %0, %%laneid;" : "=r"(l));
  return l;
}

__device__ __forceinline__ bool elect_one() {
  uint32_t p;
  asm volatile("{\n.reg .pred p;\nelect.sync _|p, 0xffffffff;\nselp.u32 %0, 1, 0, p;\n}\n" : "=r"(p));
  return p;
}

__device__ __forceinline__ uint32_t clock_pin() {
  uint32_t t;
  asm volatile("mov.u32 %0, %%clock;" : "=r"(t)::"memory");
  return t;
}

struct MlpCtx {
  uint32_t sb;
  uint32_t caddr;
  uint32_t xaddr;
  uint32_t unscale;
  uint32_t peer_off;
  int wg, warp, rank, zero;
  uint8_t* optr;
};

__device__ __forceinline__ void ln_wait(const MlpCtx& m, int i) { mbar_wait(m.sb + BAR_CFULL + 8 * m.wg, i & 1); }
__device__ __forceinline__ void ln_load(const MlpCtx& m, uint32_t (&c)[24]) {
#pragma unroll
  for (int p = 0; p < 6; p++)
    asm volatile("ld.shared.v4.b32 {%0,%1,%2,%3}, [%4];"
                 : "=r"(c[4 * p]), "=r"(c[4 * p + 1]), "=r"(c[4 * p + 2]), "=r"(c[4 * p + 3])
                 : "r"(m.caddr + p * 2048)
                 : "memory");
}
__device__ __forceinline__ void ln_shfl(float (&st)[8], int mask) {
#pragma unroll
  for (int k = 0; k < 4; k++) st[4 + k] = __shfl_xor_sync(0xffffffffu, st[k], mask);
}
__device__ __forceinline__ void ln_fold(float (&st)[8]) {
#pragma unroll
  for (int k = 0; k < 4; k++) st[k] += st[4 + k];
}
__device__ __forceinline__ void ln_sums(const uint32_t (&c)[24], float (&st)[8]) {
#pragma unroll
  for (int r = 0; r < 2; r++) {
    uint32_t s0 = h_add(c[r], c[r + 2]), s1 = h_add(c[r + 4], c[r + 6]), s2 = h_add(c[r + 8], c[r + 10]);
    uint32_t s3 = h_add(c[r + 12], c[r + 14]), s4 = h_add(c[r + 16], c[r + 18]), s5 = h_add(c[r + 20], c[r + 22]);
    s0 = h_add(s0, s1); s2 = h_add(s2, s3); s4 = h_add(s4, s5);
    st[r] = h_sum(h_add(h_add(s0, s2), s4));
    uint32_t q0 = h_mul(c[r], c[r]), q1 = h_mul(c[r + 2], c[r + 2]);
#pragma unroll
    for (int p = 2; p < 12; p += 2) {
      q0 = h_fma(c[2 * p + r], c[2 * p + r], q0);
      q1 = h_fma(c[2 * p + 2 + r], c[2 * p + 2 + r], q1);
    }
    st[2 + r] = h_sum(h_add(q0, q1));
  }
}
__device__ __forceinline__ void ln_release(const MlpCtx& m) {
  const uint32_t e = m.sb + BAR_CEMPTY + 8 * (2 * m.rank + m.wg);
  asm volatile(
      "{\n.reg .pred p, q;\nelect.sync _|p, 0xffffffff;\nsetp.eq.and.s32 q, %3, 0, p;\n"
      "@q mbarrier.arrive.expect_tx.shared::cta.b64 _, [%0], %4;\n"
      "@p mbarrier.arrive.shared::cluster.b64 _, [%1];\n"
      "@p mbarrier.arrive.shared::cluster.b64 _, [%2];\n}\n" ::"r"(m.sb + BAR_CFULL + 8 * m.wg),
      "r"(e), "r"(e + m.peer_off), "r"(m.warp), "n"(CTX)
      : "memory");
}
__device__ __forceinline__ void ln_stats(float (&st)[8], uint32_t& bad, uint32_t bit) {
  bool ok = true;
#pragma unroll
  for (int r = 0; r < 2; r++) {
    const float nm = (st[r] + st[4 + r]) * (-1.0f / 96.0f);
    const float e2 = fmaf(st[2 + r] + st[6 + r], 1.0f / 96.0f, 1e-5f);
    float rs;
    asm("rsqrt.approx.ftz.f32 %0, %1;" : "=f"(rs) : "f"(fmaf(-nm, nm, e2)));
    ok = ok && (rs * rs * e2 <= 17.0f) && (e2 >= 1.001e-5f);
    const float rr = rs * GELU_A, dd = rr * nm;
    st[r] = __uint_as_float(pack_f16(rr, rr));
    st[2 + r] = __uint_as_float(pack_f16(dd, dd));
  }
  if (!ok) bad |= bit;
}
__device__ __forceinline__ void ln_apply(uint32_t (&a)[24], const uint32_t (&c)[24], const float (&st)[8]) {
#pragma unroll
  for (int p = 0; p < 24; p++) {
    a[p] = h_fma(c[p], __float_as_uint(st[p & 1]), __float_as_uint(st[2 + (p & 1)]));
  }
}

__device__ __noinline__ void slow_tile(const __nv_bfloat16* x, const __nv_bfloat16* dw, const __nv_bfloat16* w1,
                                       const __nv_bfloat16* w2, __nv_bfloat16* out, int row0, int col0, float* buf) {
  const int lane = threadIdx.x & 31;
  for (int px = 0; px < 16; px++) {
    const int row = row0 + (px >> 3), col = col0 + (px & 7);
    float c[3] = {0.f, 0.f, 0.f};
    for (int i = 0; i < 7; i++)
      for (int j = 0; j < 7; j++) {
        const int rr = row + i - 3, cc = col + j - 3;
        if (rr < 0 || rr >= IMG || cc < 0 || cc >= IMG) continue;
        for (int k = 0; k < 3; k++)
          c[k] = fmaf(__bfloat162float(x[((size_t)rr * IMG + cc) * CH + lane + 32 * k]), __bfloat162float(dw[(i * 7 + j) * CH + lane + 32 * k]), c[k]);
      }
    float mean = (c[0] + c[1] + c[2]) * (1.0f / 96.0f);
    for (int o = 16; o; o >>= 1) mean += __shfl_xor_sync(0xffffffffu, mean, o);
    float var = 0.f;
    for (int k = 0; k < 3; k++) { c[k] -= mean; var = fmaf(c[k] * (1.0f / 96.0f), c[k], var); }
    for (int o = 16; o; o >>= 1) var += __shfl_xor_sync(0xffffffffu, var, o);
    const float rs = 1.0f / sqrtf(var + 1e-5f);
    __syncwarp();
    for (int k = 0; k < 3; k++) buf[lane + 32 * k] = c[k] * rs;
    __syncwarp();
    for (int n = lane; n < 4 * CH; n += 32) {
      float y = 0.f;
      for (int k = 0; k < CH; k++) y = fmaf(buf[k], __bfloat162float(w1[k * 4 * CH + n]), y);
      buf[CH + n] = 0.5f * y * (1.0f + tanhf(0.7978845608f * (y + 0.044715f * y * y * y)));
    }
    __syncwarp();
    for (int n = lane; n < CH; n += 32) {
      float o = 0.f;
      for (int k = 0; k < 4 * CH; k++) o = fmaf(buf[CH + k], __bfloat162float(w2[k * CH + n]), o);
      const size_t idx = ((size_t)row * IMG + col) * CH + n;
      out[idx] = __float2bfloat16(__bfloat162float(x[idx]) + o);
    }
  }
}

__device__ __forceinline__ void x_load(const MlpCtx& m, uint32_t (&x)[24]) {
#pragma unroll
  for (int k = 0; k < 6; k++)
    asm volatile("ld.shared.v4.b32 {%0,%1,%2,%3}, [%4];"
                 : "=r"(x[4 * k]), "=r"(x[4 * k + 1]), "=r"(x[4 * k + 2]), "=r"(x[4 * k + 3])
                 : "r"(m.xaddr + (k / 3) * 384 + (k % 3) * 64)
                 : "memory");
}
template <int LO, int HI>
__device__ __forceinline__ void epilogue(const MlpCtx& m, const uint32_t (&d)[24], uint32_t (&x)[24]) {
#pragma unroll
  for (int k = LO; k < HI; k++) {
    const int r = k / 3, q = k % 3;
    uint32_t* y = &x[4 * k];
#pragma unroll
    for (int j = 0; j < 4; j++) {
      uint32_t v = d[2 * (4 * q + j) + r];
      float lo, hi;
      asm("{\n.reg .b16 l, h;\nmov.b32 {l, h}, %2;\ncvt.f32.f16 %0, l;\ncvt.f32.f16 %1, h;\n}\n" : "=f"(lo), "=f"(hi) : "r"(v));
      asm("fma.rn.bf16x2 %0, %1, %2, %0;" : "+r"(y[j]) : "r"(pack_bf16(lo, hi)), "r"(m.unscale));
    }
    asm volatile("st.shared.v4.b32 [%0], {%1,%2,%3,%4};" ::"r"(m.xaddr + r * 384 + q * 64), "r"(y[0]), "r"(y[1]), "r"(y[2]), "r"(y[3])
                 : "memory");
  }
}
__device__ __forceinline__ void out_store(const MlpCtx& m, int i) {
  asm volatile("fence.proxy.async.shared::cta;" ::: "memory");
  __syncwarp();
  if (elect_one()) {
    const uint32_t src = m.sb + OFF_XRES + m.wg * 12288 + m.warp * 1536;
    uint8_t* dst = m.optr + (size_t)i * (8 * IMG * CH * 2);
    asm volatile("cp.async.bulk.global.shared::cta.bulk_group [%0], [%1], 1536;" ::"l"(dst), "r"(src) : "memory");
    asm volatile("cp.async.bulk.global.shared::cta.bulk_group [%0], [%1], 1536;" ::"l"(dst + IMG * CH * 2), "r"(src + 6144) : "memory");
    asm volatile("cp.async.bulk.commit_group;" ::: "memory");
  }
}

#define FSET 3
template <int J> constexpr bool goes_first = J == FSET || J == ((FSET + 1) & 3);
template <int J> __device__ __forceinline__ void tok_wait() {
  if (goes_first<J>) NB_SYNC(NB_CLOSE, 256);
  else NB_SYNC(NB_SEC + (J & 1), 256);
}
template <int J> __device__ __forceinline__ void tok_next() {
  if (goes_first<J>) NB_ARRIVE(NB_SEC + (J & 1), 256);
  if (J == 0) NB_ARRIVE(NB_PROD, 160);
}
__device__ __forceinline__ void tok_pass() { NB_ARRIVE(NB_OPEN, 416); }
template <int J> __device__ __forceinline__ void tok_idle() { tok_wait<J>(); tok_next<J>(); tok_pass(); }

constexpr uint64_t CHK = 1152;

__device__ __forceinline__ float warp_sumsq(const uint32_t (&q)[4]) {
  const uint32_t t = bf_add(bf_add(q[0], q[1]), bf_add(q[2], q[3]));
  float f = bf_lo(t) + bf_hi(t);
#pragma unroll
  for (int o = 16; o; o >>= 1) f += __shfl_xor_sync(0xffffffffu, f, o);
  return f;
}
__device__ __forceinline__ int norm_exp(float f) { return (((int)(__float_as_uint(f * 1.5f) >> 23) - 127) >> 1) + 1; }
__device__ __forceinline__ int scale_exp(int e1, int e2) { return min(11 - e1 - e2, 14 - e2); }

__device__ __forceinline__ int sample_scale(const uint4* w1, const uint4* w2) {
  const int lane = threadIdx.x & 31;
  const uint4 a = __ldg(w1 + lane * 145), b = __ldg(w2 + lane * 145);
  const uint32_t qa[4] = {bf_mul(a.x, a.x), bf_mul(a.y, a.y), bf_mul(a.z, a.z), bf_mul(a.w, a.w)};
  const uint32_t qb[4] = {bf_mul(b.x, b.x), bf_mul(b.y, b.y), bf_mul(b.z, b.z), bf_mul(b.w, b.w)};
  return max(-64, min(64, scale_exp(norm_exp(144.f * warp_sumsq(qa)), norm_exp(144.f * warp_sumsq(qb))) - 1));
}

__device__ __forceinline__ void convert_tile(int t, const uint4* w1, const uint4* w2, uint32_t st) {
  const int lane = threadIdx.x & 31, k7 = lane & 7;
  uint32_t q[4] = {0, 0, 0, 0};
  uint4 v[6];
  const int j = t / 6, ks = t % 6, e = ks % 3, t4 = k7 >> 1;
  const uint4* src = t < 24 ? w1 + ((e < 2 ? 64 * (ks / 3) + 8 * t4 + 4 * e : 32 + 16 * (ks / 3) + 4 * t4) + (k7 & 1)) * 48 + j * 12 + (lane >> 3)
                            : w2 + (t - 24) * 192 + (lane >> 2) * 12 + (lane & 3);
#pragma unroll
  for (int k = 0; k < 6; k++) v[k] = __ldg(src + (k / 3) * 96 + (k % 3) * 4);
  const int s = sample_scale(w1, w2);
  const uint32_t dst = st + k7 * 16 + (lane >> 3) * 256;
  if (t < 24) {
#pragma unroll
    for (int k = 0; k < 6; k++) {
      const uint32_t w[4] = {v[k].x, v[k].y, v[k].z, v[k].w};
      uint32_t o[4];
#pragma unroll
      for (int i = 0; i < 4; i++) {
        q[i] = bf_fma(w[i], w[i], q[i]);
        o[i] = pack_f16(bf_lo(w[i]), bf_hi(w[i]));
      }
      asm volatile("st.shared.v4.b32 [%0], {%1,%2,%3,%4};" ::"r"(dst + (k / 3) * 128 + (k % 3) * 1024), "r"(o[0]), "r"(o[1]), "r"(o[2]), "r"(o[3])
                   : "memory");
    }
  } else {
    constexpr float F = 0.5f / GELU_A, FHI = 1.515625f;
    const float p2 = __uint_as_float((uint32_t)(127 + s - 56) << 23);
    const uint32_t hi = pack_bf16(FHI * 0x1p-56f, FHI * 0x1p-56f), lo = pack_bf16((F - FHI) * 0x1p-56f, (F - FHI) * 0x1p-56f);
    const uint32_t pw = pack_bf16(p2, p2);
#pragma unroll
    for (int k = 0; k < 6; k++) {
      const uint32_t w[4] = {v[k].x, v[k].y, v[k].z, v[k].w};
      uint32_t o[4];
#pragma unroll
      for (int i = 0; i < 4; i++) {
        q[i] = bf_fma(w[i], w[i], q[i]);
        const uint32_t ws = bf_mul(w[i], pw), u = bf_fma(ws, hi, bf_mul(ws, lo));
        o[i] = (u & 0x7fff7fffu) * 7u + u;
      }
      asm volatile("stmatrix.sync.aligned.m8n8.x4.shared.b16 [%0], {%1,%2,%3,%4};" ::"r"(dst + (k / 3) * 128 + (k % 3) * 1024), "r"(o[0]),
                   "r"(o[1]), "r"(o[2]), "r"(o[3])
                   : "memory");
    }
  }
  const float f = warp_sumsq(q);
  asm volatile("st.shared.v2.b32 [%0], {%1,%2};" ::"r"(st + 3072), "r"(__float_as_uint(f)), "r"(s) : "memory");
  asm volatile("fence.proxy.async.shared::cta;" ::: "memory");
  __syncwarp();
  TS(4);
  if (elect_one()) {
    asm volatile("cp.async.bulk.global.shared::cta.bulk_group [%0], [%1], 3072;" ::"l"(g_w + t * 192), "r"(st) : "memory");
    asm volatile("cp.async.bulk.global.shared::cta.bulk_group [%0], [%1], 16;" ::"l"(g_nrm + t), "r"(st + 3072) : "memory");
    asm volatile("cp.async.bulk.commit_group;" ::: "memory");
    asm volatile("cp.async.bulk.wait_group 0;" ::: "memory");
    asm volatile("red.relaxed.gpu.global.add.u32 [%0], 1;" ::"l"(&g_done) : "memory");
  }
  TS(5);
}

__device__ __forceinline__ uint32_t mlp_role(const MlpCtx& m0) {
  MlpCtx m = m0;
  uint32_t bad = 0;
  asm volatile("barrier.cluster.wait.aligned;" ::: "memory");
  if ((m.sb & 0x3FFFF) != 1024) bad = 0xffffu;
  constexpr uint64_t dW1 = (uint64_t)((1024 + OFF_W1) >> 4) | ((uint64_t)8 << 16) | ((uint64_t)16 << 32);
  constexpr uint64_t dW2 = dW1 + (OFF_W2 >> 4);
  TS(6);
  uint32_t A1[24], g[24], d[24], cn[24], D2[24];
  float st[8];
  ln_wait(m, 0);
  ln_load(m, cn);
  ln_sums(cn, st);
  ln_shfl(st, 1);
  ln_release(m);
  ln_fold(st);
  ln_shfl(st, 2);
  ln_stats(st, bad, 1);
  ln_apply(A1, cn, st);
  {
    const int lane = threadIdx.x & 31;
    TS(2);
    mbar_wait(m.sb + BAR_W, 0);
    TS(3);
    float n1, n2;
    int s;
    asm volatile("ld.shared.b32 %0, [%1];" : "=r"(s) : "r"(m.sb + OFF_NRM + 4) : "memory");
    asm volatile("ld.shared.f32 %0, [%1];" : "=f"(n1) : "r"(m.sb + OFF_NRM + 16 * min(lane, 23)) : "memory");
    asm volatile("ld.shared.f32 %0, [%1];" : "=f"(n2) : "r"(m.sb + OFF_NRM + 384 + 16 * min(lane, 23)) : "memory");
    if (lane >= 24) n1 = n2 = 0.f;
#pragma unroll
    for (int o = 16; o; o >>= 1) {
      n1 += __shfl_xor_sync(0xffffffffu, n1, o);
      n2 += __shfl_xor_sync(0xffffffffu, n2, o);
    }
    const int e1 = norm_exp(n1), e2 = norm_exp(n2), smax = scale_exp(e1, e2);
    if (e1 > 12 || e1 < -5 || e2 > 50 || e2 < -50 || s > smax || s < smax - 5) bad = 0xffffu;
    m.unscale = __shfl_sync(0xffffffffu, ((uint32_t)(127 - s) << 7) * 0x10001u, 0);
  }
  TS(7);
  if (m.wg & m.rank) tok_idle<3>();
  if (m.wg) tok_idle<0>();
  if (m.wg | m.rank) tok_idle<1>();
  {
    uint32_t d0[24];
    WG_FENCE();
    tok_wait<2>();
    tok_next<2>();
    gemm6<true, 192>(d0, A1, dW1);
    tok_pass(); PIN();
    WG_WAIT0(); rfence(d0);
    WG_FENCE();
    tok_wait<3>();
    tok_next<3>();
    gemm6<true, 192>(d, A1, dW1 + CHK);
    tok_pass(); PIN();
    gelu<0, 24>(g, d0);
    PIN();
    mbar_wait(m.sb + BAR_W + 8, 0);
    ln_wait(m, 1);
    WG_WAIT0(); rfence(d);
  }
#define G2(INIT, a, j)                      \
  WG_FENCE();                               \
  tok_wait<j>();                            \
  gemm6<INIT, 192>(D2, a, dW2 + (j) * CHK); \
  tok_next<j>(); PIN();                     \
  TL(ltb, (j) * 5 + 1);
#define G1(dst, j, P)                       \
  TL(ltb, ((j) ^ 2) * 5 + 2);               \
  P(); WG_WAIT0(); rfence(D2);              \
  WG_FENCE();                               \
  gemm6<true, 192>(dst, A1, dW1 + (j) * CHK); \
  tok_pass(); P();                          \
  TL(ltb, ((j) ^ 2) * 5 + 3);
#define ROUND_END(dst, j)                   \
  TL(ltb, (j) * 5 + 4);                     \
  PIN(); WG_WAIT0(); rfence(dst);
#define GA 9
#define GB 11
#define GC 13
#define GD 11
#pragma unroll 1
  for (int i = 0;; i++) {
    uint32_t g1[24], d2[24], g2[24], d3[24], g3[24], d0[24];
    ln_load(m, cn);
    PIN();
    G2(true, g, 0)
    gelu<0, GA>(g1, d);
    G1(d2, 2, PIN)
    ln_sums(cn, st);
    gelu<GA, 24>(g1, d);
    PIN();
    ln_shfl(st, 1);
    ROUND_END(d2, 0)

    G2(false, g1, 1)
    ln_fold(st);
    gelu<0, GB>(g2, d2);
    PIN();
    ln_shfl(st, 2);
    G1(d3, 3, PIN)
    ln_stats(st, bad, 2u << i);
    gelu<GB, 24>(g2, d2);
    ROUND_END(d3, 1)

    if (i == 15) {
      G2(false, g2, 2)
      tok_pass();
      gelu<0, 24>(g3, d3);
      PIN();
      x_load(m, cn);
      ROUND_END(D2, 2)
      G2(false, g3, 3)
      tok_pass();
      WG_WAIT0(); rfence(D2);
      epilogue<0, 6>(m, D2, cn);
      break;
    }
    G2(false, g2, 2)
    ln_apply(A1, cn, st);
    PIN();
    gelu<0, GC>(g3, d3);
    G1(d0, 0, PIN)
    gelu<GC, 24>(g3, d3);
    PIN();
    x_load(m, cn);
    ROUND_END(d0, 2)

    G2(false, g3, 3)
    gelu<0, GD>(g, d0);
    G1(d, 1, PIN)
    epilogue<0, 6>(m, D2, cn);
    gelu<GD, 24>(g, d0);
    PIN();
    asm volatile("fence.proxy.async.shared::cta;" ::: "memory");
    ROUND_END(d, 3)
    TLDUMP(m.warp == 0 && (i >> 1) == LTRACE, m.sb + OFF_LT + m.wg * 160 + (i & 1) * 80, 20)
  }
  out_store(m, 15);
  if (m.wg == 0) { tok_idle<0>(); tok_idle<1>(); }
  asm volatile("cp.async.bulk.wait_group 0;" ::: "memory");
  return __reduce_or_sync(0xffffffffu, bad & 0xffffu);
}

struct ConvCtx {
  uint32_t sb;
  uint32_t a0, a_c;
  uint32_t peer_off;
  int rank, v, c0, r0, zero;
  const CUtensorMap* tm;
  const uint8_t* xsrc;
  uint8_t* optr;
};

__device__ __forceinline__ void raw_refill(const ConvCtx& c, int s) {
  if (s + 4 < NSTEP && elect_one())
    tma_raw(c.sb + OFF_RAW + (s & 3) * RAW_BYTES, c.tm, c.rank, c.c0 / 2 - 2, c.r0 - 3 + 2 * (s + 4), c.sb + BAR_RAW + 8 * (s & 3));
}
__device__ __forceinline__ void step_ready(const ConvCtx& c, int s) {
  const int nx = (s + 1) & 3, par = ((s + 1) >> 2) & 1;
  if (s + 1 < NSTEP) mbar_wait(c.sb + BAR_RAW + 8 * nx, par);
  if (s >= 7 && s < NSTEP) mbar_wait(c.sb + BAR_CEMPTY + 8 * (2 * (nx & 1) + (nx >> 1)), par);
}

__device__ __forceinline__ void c_release(const ConvCtx& c, uint32_t w) {
  const uint32_t e = c.sb + BAR_CEMPTY + 8 * (2 * c.rank + w);
  asm volatile(
      "{\n.reg .pred p;\nelect.sync _|p, 0xffffffff;\n"
      "@p mbarrier.arrive.expect_tx.shared::cta.b64 _, [%0], %3;\n"
      "@p mbarrier.arrive.shared::cluster.b64 _, [%1], 4;\n"
      "@p mbarrier.arrive.shared::cluster.b64 _, [%2], 4;\n}\n" ::"r"(c.sb + BAR_CFULL + 8 * w),
      "r"(e), "r"(e + c.peer_off), "n"(CTX)
      : "memory");
}

__device__ __forceinline__ void prod_rows(const ConvCtx& c) {
  asm volatile("barrier.cluster.wait.aligned;" ::: "memory");
#pragma unroll 1
  for (int s = 0; s < NROUND + SIGMA + c.rank; s++) {
    const int r = s - SIGMA - c.rank;
    const int u = (r & 1) ? (r >> 1) - 1 : (r >> 1) + 2;
    step_ready(c, s);
    if (u >= ((r & 1) ? 0 : 4) && u < 32) mbar_wait(c.sb + ((r & 1) ? BAR_XFULL : BAR_CFULL) + 8 * (u & 1), (u >> 1) & 1);
    if (s < SIGMA) NB_SYNC(NB_PLAN, 160);
    else NB_SYNC(NB_OPEN, 416);
    if (r == 3) TC(1);
    if (r == 55) TC(2);
    if (r >= -1 && r < 7) TS(7 + r);
    raw_refill(c, s);
  }
}
__device__ __forceinline__ void prod_tiles(const ConvCtx& c) {
  asm volatile("barrier.cluster.wait.aligned;" ::: "memory");
#pragma unroll 1
  for (int n = 0; n < NROUND / 2; n++) {
    const uint32_t w = (n + 1) & 1;
    const uint32_t buf = c.sb + OFF_XRES + w * 12288;
    NB_SYNC(NB_PROD, 160);
    if (n >= 1 && n < 29) c_release(c, w);
    if (n >= 3 && n < 33) {
      uint8_t* dst = c.optr + (size_t)(n - 3) * (4 * IMG * CH * 2);
      if (elect_one()) {
        asm volatile("cp.async.bulk.global.shared::cta.bulk_group [%0], [%1], 6144;" ::"l"(dst), "r"(buf) : "memory");
        asm volatile("cp.async.bulk.global.shared::cta.bulk_group [%0], [%1], 6144;" ::"l"(dst + IMG * CH * 2), "r"(buf + 6144) : "memory");
        asm volatile("cp.async.bulk.commit_group;" ::: "memory");
        asm volatile("cp.async.bulk.wait_group.read 0;" ::: "memory");
      }
      __syncwarp();
    }
    if (n >= 1 && n < 33) {
      const uint8_t* src = c.xsrc + (size_t)(n - 1) * (4 * IMG * CH * 2);
      if (elect_one()) {
        mbar_expect(c.sb + BAR_XFULL + 8 * w, 12288);
        bulk_load_last(buf, src, 6144, c.sb + BAR_XFULL + 8 * w);
        bulk_load_last(buf + 6144, src + IMG * CH * 2, 6144, c.sb + BAR_XFULL + 8 * w);
      }
    }
  }
  asm volatile("cp.async.bulk.wait_group 0;" ::: "memory");
}

__device__ __forceinline__ void conv_ld8(uint32_t a0, uint32_t (&r)[6][6]) {
  const uint32_t a2 = a0 ^ (16 | ((a0 >> 2) & 32));
  const uint32_t a[3] = {a0, (a0 & 64) ? a2 : a0, a2};
#pragma unroll
  for (int j = 0; j < 6; j++)
    asm volatile("ld.shared.v4.b32 {%0,%1,%2,%3}, [%4];"
                 : "=r"(r[j][0]), "=r"(r[j][1]), "=r"(r[j][2]), "=r"(r[j][3])
                 : "r"(a[j >> 1] + (j >> 1) * 64 + (j & 1) * RAW_PA)
                 : "memory");
}
__device__ __forceinline__ void conv_ld4(uint32_t a0, uint32_t stage, int v, uint32_t (&r)[6][6]) {
  const uint32_t ab = ((a0 >> 1) & ~31u) + (stage / 2 + 2 * RAW_PA + 8 * v);
#pragma unroll
  for (int j = 0; j < 6; j++) {
    uint32_t a = ab + (j >> 1) * 32;
    asm volatile("ld.shared.v2.b32 {%0,%1}, [%2];" : "=r"(r[j][4]), "=r"(r[j][5]) : "r"(a + (j & 1) * RAW_PB) : "memory");
  }
}
template <int LO, int HI>
__device__ __forceinline__ void conv_frags(uint32_t zero, const uint32_t (&r)[6][6], uint32_t (&A)[12][4]) {
#pragma unroll
  for (int ch = LO; ch < HI; ch++) {
    const uint32_t sel = (ch & 1) ? 0x7632 : 0x5410;
    A[ch][0] = __byte_perm(r[0][ch >> 1], r[1][ch >> 1], sel);
    A[ch][1] = __byte_perm(r[2][ch >> 1], r[3][ch >> 1], sel);
    A[ch][2] = A[ch][1] ^ zero;
    A[ch][3] = __byte_perm(r[4][ch >> 1], r[5][ch >> 1], sel);
    rfence(A[ch]);
  }
}
__device__ __forceinline__ void hmma_acc(uint32_t (&v)[4], const uint32_t (&a)[4], const uint32_t* b) {
  asm volatile("mma.sync.aligned.m16n8k16.row.col.f32.bf16.bf16.f32 {%0,%1,%2,%3}, {%4,%5,%6,%7}, {%8,%9}, {%0,%1,%2,%3};"
               : "+r"(v[0]), "+r"(v[1]), "+r"(v[2]), "+r"(v[3])
               : "r"(a[0]), "r"(a[1]), "r"(a[2]), "r"(a[3]), "r"(b[0]), "r"(b[1]));
}
__device__ __forceinline__ void hmma_new(uint32_t (&a)[4], const uint32_t* b) {
  asm volatile("mma.sync.aligned.m16n8k16.row.col.f32.bf16.bf16.f32 {%0,%1,%2,%3}, {%0,%1,%2,%3}, {%4,%5}, {%6,%6,%6,%6};"
               : "+r"(a[0]), "+r"(a[1]), "+r"(a[2]), "+r"(a[3])
               : "r"(b[0]), "r"(b[1]), "f"(0.f));
}

#define EARLY 5
template <int S2, bool GATED>
__device__ __forceinline__ void conv_step(const ConvCtx& c, int s, uint32_t (&K)[12], uint32_t (&V)[12][4], const uint32_t (&B)[12][4],
                                          uint32_t (&A)[12][4]) {
  const int nx = ((s + 1) & 2) | (S2 ^ 1);
  uint32_t r[6][6];
  const uint32_t a0 = c.a0 + nx * RAW_BYTES;
  TL(ltb, 0);
  if (!GATED) TS(6 + s);
  if (GATED) NB_SYNC(NB_OPEN, 416);
  else NB_SYNC(NB_PLAN, 160);
  conv_ld4(a0, c.sb + OFF_RAW + nx * RAW_BYTES, c.v, r);
  PIN();
  TL(ltb, 1);
#pragma unroll
  for (int ch = 0; ch < 12; ch++) hmma_acc(V[11 - ch], A[11 - ch], &B[11 - ch][2]);
#pragma unroll
  for (int ch = 0; ch < 12 - EARLY; ch++) hmma_new(A[ch], &B[ch][0]);
  const uint32_t zero = c.zero & clock_pin();
  if (GATED) NB_ARRIVE(NB_CLOSE, 256);
#pragma unroll
  for (int ch = 12 - EARLY; ch < 12; ch++) hmma_new(A[ch], &B[ch][0]);
  PIN();
  TL(ltb, 2);
  const uint32_t off = ((S2 ^ 1) == c.rank) ? 0u : c.peer_off;
  const uint32_t dst = c.a_c + (GATED || s >= 3 ? off + (nx >> 1) * C_BYTES : OFF_XRES + 12288 - OFF_C);
  const uint32_t bar = c.sb + (GATED || s >= 3 ? off + BAR_CFULL + 8 * (nx >> 1) : BAR_W + 56);
#pragma unroll
  for (int q = 0; q < 12; q++) {
    const int ch = q & ~1, h = 2 * (q & 1);
    asm("add.rn.f16x2 %0, %0, %1;" : "+r"(K[q]) : "r"(pack_f16(__uint_as_float(V[ch][h + 1]), __uint_as_float(V[ch + 1][h]))));
  }
  if ((S2 ^ 1) == c.rank) {
#pragma unroll
    for (int q = 0; q < 3; q++)
      asm volatile("st.shared.v4.b32 [%0], {%1,%2,%3,%4};" ::"r"(dst + q * 2048), "r"(K[4 * q]), "r"(K[4 * q + 1]), "r"(K[4 * q + 2]), "r"(K[4 * q + 3])
                   : "memory");
    asm volatile("{\n.reg .pred p;\nelect.sync _|p, 0xffffffff;\n@p mbarrier.arrive.shared::cta.b64 _, [%0];\n}\n" ::"r"(bar) : "memory");
  } else {
#pragma unroll
  for (int q = 0; q < 3; q++)
    asm volatile("st.async.weak.shared::cluster.mbarrier::complete_tx::bytes.v4.b32 [%0], {%1,%2,%3,%4}, [%5];" ::"r"(dst + q * 2048),
                 "r"(K[4 * q]), "r"(K[4 * q + 1]), "r"(K[4 * q + 2]), "r"(K[4 * q + 3]), "r"(bar)
                 : "memory");
  }
  PIN();
#pragma unroll
  for (int q = 0; q < 12; q++) {
    const int ch = q & ~1, h = 2 * (q & 1);
    K[q] = pack_f16(__uint_as_float(V[ch][h]), __uint_as_float(V[ch + 1][h + 1]));
  }
  rfence(K);
  conv_frags<8, 12>(zero, r, V);
  PIN();
  conv_ld8(a0, r);
  conv_frags<0, 8>(zero, r, V);
  PIN();
  TL(ltb, 4);
  TLDUMP(c.v == 0 && lr >= 0 && lr < 10, c.sb + OFF_LT + 320 + lr * 20, 5)
}

__device__ __forceinline__ void conv_role(ConvCtx c) {
  const int lane = laneid(), g = lane >> 2, t = lane & 3;
  const int u = (t >> 1) * 19 + 2 * (g + (t & 1));
  c.a0 = c.sb + OFF_RAW + u * 64 + ((c.v ^ (u >> 1)) & 3) * 16;
  c.a_c = c.sb + OFF_C + 6144 * c.rank + 512 * c.v + ((lane + 2 * c.v) & 31) * 16;
  uint32_t B[12][4];
  {
    const int dc = (g >> 1) & 1, ro = g >> 2, rk = t >> 1;
    const int i0 = 4 * (g & 1) + rk - ro, j0 = 4 * (t & 1) - dc;
    const uint32_t base = c.sb + OFF_XRES + (i0 * 7 + j0) * 192;
    TS(2);
    mbar_wait(c.sb + BAR_W + 48, 0);
    TS(3);
#pragma unroll
    for (int b = 0; b < 2; b++) {
      uint32_t w[4][6];
#pragma unroll
      for (int k = 0; k < 4; k++) {
        const int ok = (unsigned)(i0 + 2 * b) < 7u && (unsigned)(j0 + k) < 7u;
#pragma unroll
        for (int q = 0; q < 6; q++) w[k][q] = 0;
        asm volatile(
            "{\n.reg .pred p;\nsetp.ne.s32 p, %8, 0;\n@p ld.shared.v4.b32 {%0,%1,%2,%3}, [%6];\n@p ld.shared.v2.b32 {%4,%5}, [%7];\n}\n"
            : "+r"(w[k][0]), "+r"(w[k][1]), "+r"(w[k][2]), "+r"(w[k][3]), "+r"(w[k][4]), "+r"(w[k][5])
            : "r"(base + (b * 14 + k) * 192 + 128 * c.rank + 16 * c.v), "r"(base + (b * 14 + k) * 192 + 64 + 32 * c.rank + 8 * c.v), "r"(ok)
            : "memory");
      }
#pragma unroll
      for (int q = 0; q < 6; q++) {
        B[2 * q][2 * b] = __byte_perm(w[0][q], w[1][q], 0x5410);
        B[2 * q][2 * b + 1] = __byte_perm(w[2][q], w[3][q], 0x5410);
        B[2 * q + 1][2 * b] = __shfl_xor_sync(0xffffffffu, __byte_perm(w[0][q], w[1][q], 0x7632), 4);
        B[2 * q + 1][2 * b + 1] = __shfl_xor_sync(0xffffffffu, __byte_perm(w[2][q], w[3][q], 0x7632), 4);
      }
    }
  }
  TS(4);
  asm volatile("barrier.cluster.wait.aligned;" ::: "memory");
  uint32_t K1[12], K2[12], V[12][4];
#pragma unroll
  for (int ch = 0; ch < 12; ch++) {
    K1[ch] = K2[ch] = 0;
#pragma unroll
    for (int k = 0; k < 4; k++) V[ch][k] = 0;
  }
  uint32_t A[12][4], r[6][6];
  mbar_wait(c.sb + BAR_RAW, 0);
  TS(5);
  conv_ld8(c.a0, r);
  conv_frags<0, 8>(c.zero, r, A);
  PIN();
  conv_ld4(c.a0, c.sb + OFF_RAW, c.v, r);
  conv_frags<8, 12>(c.zero, r, A);
  PIN();
  NB_ARRIVE(NB_CLOSE, 256);
#pragma unroll 1
  for (int s = 0; s < SIGMA; s += 2) {
    conv_step<0, false>(c, s, K1, V, B, A);
    conv_step<1, false>(c, s + 1, K2, A, B, V);
  }
#pragma unroll 1
  for (int s = SIGMA;; s += 2) {
    conv_step<0, true>(c, s, K1, V, B, A);
    if (s == NSTEP - 1) break;
    conv_step<1, true>(c, s + 1, K2, A, B, V);
  }
#pragma unroll 1
  for (int r = NSTEP - SIGMA - c.rank; r < NROUND - 1; r++) {
    NB_SYNC(NB_OPEN, 416);
    NB_ARRIVE(NB_CLOSE, 256);
  }
  NB_SYNC(NB_OPEN, 416);
}

struct TMaps { CUtensorMap m[2]; };

__global__ void __cluster_dims__(2, 1, 1) __launch_bounds__(512, 1)
convnext_kernel(const __grid_constant__ TMaps tms, const __nv_bfloat16* __restrict__ x, const __nv_bfloat16* __restrict__ dw,
                const __nv_bfloat16* __restrict__ w1, const __nv_bfloat16* __restrict__ w2, __nv_bfloat16* __restrict__ out,
                int zero) {
  extern __shared__ __align__(1024) uint8_t smem[];
  const uint32_t sb = (uint32_t)__cvta_generic_to_shared(smem);
  const int tid = threadIdx.x, lane = tid & 31;
  const int wid = __shfl_sync(0xffffffffu, tid >> 5, 0);
  const int rank = blockIdx.x & 1, cl = blockIdx.x >> 1;
  const int c0 = (cl & 15) * 32, r0 = (cl >> 4) * 128;
  const uint32_t peer_off = mapa(sb, rank ^ 1) - sb;

  TS(0);
  if (wid == 12 && elect_one()) {
    asm volatile("prefetch.tensormap [%0];" ::"l"(&tms.m[0]) : "memory");
    asm volatile("prefetch.tensormap [%0];" ::"l"(&tms.m[1]) : "memory");
#pragma unroll
    for (int i = 0; i < 8; i++) mbar_init(sb + BAR_W + 8 * i, i == 7 ? 100 : 1);
#pragma unroll
    for (int i = 0; i < 4; i++) mbar_init(sb + BAR_RAW + 8 * i, 1);
    asm volatile("fence.mbarrier_init.release.cluster;" ::: "memory");
  }
  if (wid == 14 && elect_one()) {
#pragma unroll
    for (int i = 0; i < 2; i++) mbar_init(sb + BAR_CFULL + 8 * i, CCNT);
#pragma unroll
    for (int i = 0; i < 4; i++) mbar_init(sb + BAR_CEMPTY + 8 * i, 4);
#pragma unroll
    for (int i = 0; i < 2; i++) mbar_init(sb + BAR_XFULL + 8 * i, 1);
#pragma unroll
    for (int i = 0; i < 2; i++) mbar_expect(sb + BAR_CFULL + 8 * i, CTX);
    asm volatile("fence.mbarrier_init.release.cluster;" ::: "memory");
  }
  if (wid == 0) {
    NB_ARRIVE(0, 512);
    asm volatile("barrier.cluster.arrive.relaxed.aligned;" ::: "memory");
    if (blockIdx.x < 48) convert_tile(blockIdx.x, reinterpret_cast<const uint4*>(w1), reinterpret_cast<const uint4*>(w2), sb);
  } else {
    NB_SYNC(0, 512);
    asm volatile("barrier.cluster.arrive.relaxed.aligned;" ::: "memory");
  }

  TS(1);
  if (wid < 8) {
    MlpCtx m;
    m.sb = sb; m.wg = wid >> 2; m.warp = wid & 3; m.rank = rank; m.peer_off = peer_off; m.zero = zero;
    m.optr = reinterpret_cast<uint8_t*>(out) + ((size_t)(r0 + 4 * m.wg + 2 * rank) * IMG + c0 + 8 * m.warp) * (CH * 2);
    m.caddr = sb + OFF_C + m.wg * C_BYTES + (lane & 3) * 512 + ((m.warp * 8 + (lane >> 2) + 2 * (lane & 3)) & 31) * 16;
    m.xaddr = sb + OFF_XRES + m.wg * 12288 + m.warp * 1536 + ((lane >> 3) & 1) * 6144 + ((lane >> 4) * 4 + ((lane >> 2) & 1)) * 192 + (lane & 3) * 16;
    m.unscale = 0;
    asm volatile("setmaxnreg.inc.sync.aligned.u32 %0;" ::"n"(REG_MLP));
    const uint32_t bad = mlp_role(m);
    asm volatile("barrier.cluster.arrive.relaxed.aligned;\nbarrier.cluster.wait.aligned;" ::: "memory");
    if (bad) {
      asm volatile("fence.proxy.async;" ::: "memory");
#pragma unroll 1
      for (int i = 0; i < 16; i++)
        if (bad >> i & 1)
          slow_tile(x, dw, w1, w2, out, r0 + 8 * i + 4 * m.wg + 2 * rank, c0 + 8 * m.warp,
                    reinterpret_cast<float*>(smem + OFF_XRES + wid * 3072));
    }
  } else {
    ConvCtx c;
    c.sb = sb; c.rank = rank; c.v = wid - 8; c.c0 = c0; c.r0 = r0; c.zero = zero; c.tm = tms.m;
    c.peer_off = peer_off;
    c.xsrc = reinterpret_cast<const uint8_t*>(x) + ((size_t)(r0 + 2 * rank) * IMG + c0) * (CH * 2);
    c.optr = reinterpret_cast<uint8_t*>(out) + ((size_t)(r0 + 2 * rank) * IMG + c0) * (CH * 2);
    if (wid < 12) {
      asm volatile("setmaxnreg.inc.sync.aligned.u32 %0;" ::"n"(REG_CONV));
      conv_role(c);
      __syncwarp();
      asm volatile("barrier.cluster.arrive.relaxed.aligned;\nbarrier.cluster.wait.aligned;\nexit;" ::: "memory");
    } else {
      asm volatile("setmaxnreg.dec.sync.aligned.u32 24;");
      if (wid == 14) TC(0);
      if (wid == 12) {
        if (elect_one()) {
          mbar_expect(sb + BAR_W + 48, 49 * CH * 2);
          bulk_load(sb + OFF_XRES, dw, 49 * CH * 2, sb + BAR_W + 48);
        }
        TS(2);
#pragma unroll 1
        for (int h = -4; h < 0; h++) raw_refill(c, h);
        TS(3);
        prod_rows(c);
        __syncwarp();
        asm volatile("barrier.cluster.arrive.relaxed.aligned;\nbarrier.cluster.wait.aligned;" ::: "memory");
      } else if (wid == 13) {
#pragma unroll 1
        for (int n = 0; n < (1 << 20); n++) {
          unsigned v;
          __nanosleep(n ? PSL : PS0);
          asm volatile("ld.acquire.gpu.global.u32 %0, [%1];" : "=r"(v) : "l"(&g_done) : "memory");
          if (__shfl_sync(0xffffffffu, v, 0) >= 48) break;
        }
        asm volatile("fence.proxy.async.global;" ::: "memory");
        if (elect_one()) {
          const uint8_t* w = reinterpret_cast<const uint8_t*>(g_w);
          mbar_expect(sb + BAR_W, 73728 + 768);
          mbar_expect(sb + BAR_W + 8, 73728);
          bulk_load(sb + OFF_NRM, g_nrm, 768, sb + BAR_W);
#pragma unroll
          for (int i = 0; i < 8; i++) bulk_load(sb + i * 18432, w + i * 18432, 18432, sb + BAR_W + 8 * (i >> 2));
          if (atomicAdd(&g_seen, 1u) == gridDim.x - 1) { g_done = 0; g_seen = 0; }
        }
        __syncwarp();
        prod_tiles(c);
        __syncwarp();
        asm volatile("barrier.cluster.arrive.relaxed.aligned;\nbarrier.cluster.wait.aligned;" ::: "memory");
        TC(3);
      }
    }
  }
}

typedef CUresult (*EncodeFn)(CUtensorMap*, CUtensorMapDataType, cuuint32_t, void*, const cuuint64_t*, const cuuint64_t*,
                             const cuuint32_t*, const cuuint32_t*, CUtensorMapInterleave, CUtensorMapSwizzle,
                             CUtensorMapL2promotion, CUtensorMapFloatOOBfill);

}

extern "C" void kernel_launch(void* const* d_in, const int* in_sizes, int n_in, void* d_out, int out_size) {
  const __nv_bfloat16* x = (const __nv_bfloat16*)d_in[0];
  const __nv_bfloat16* dw = (const __nv_bfloat16*)d_in[1];
  const __nv_bfloat16* w1 = (const __nv_bfloat16*)d_in[2];
  const __nv_bfloat16* w2 = (const __nv_bfloat16*)d_in[3];
  __nv_bfloat16* out = (__nv_bfloat16*)d_out;

  static EncodeFn encode = nullptr;
  if (!encode) {
    cudaDriverEntryPointQueryResult st;
    void* fn = nullptr;
    cudaGetDriverEntryPoint("cuTensorMapEncodeTiled", &fn, cudaEnableDefault, &st);
    encode = (EncodeFn)fn;
    cudaFuncSetAttribute(convnext_kernel, cudaFuncAttributeMaxDynamicSharedMemorySize, SMEM_BYTES);
  }
  TMaps tm;
  cuuint64_t dims[4] = {CH, IMG / 2, IMG, 2};
  cuuint64_t strides[3] = {CH * 4, (cuuint64_t)IMG * CH * 2, CH * 2};
  cuuint32_t es[4] = {1, 1, 1, 1};
  for (int i = 0; i < 2; i++) {
    cuuint32_t box[4] = {i ? 16u : 32u, 19, 2, 1};
    encode(&tm.m[i], CU_TENSOR_MAP_DATA_TYPE_BFLOAT16, 4, (void*)x, dims, strides, box, es, CU_TENSOR_MAP_INTERLEAVE_NONE,
           i ? CU_TENSOR_MAP_SWIZZLE_NONE : CU_TENSOR_MAP_SWIZZLE_64B, PROMO, CU_TENSOR_MAP_FLOAT_OOB_FILL_NONE);
  }
  convnext_kernel<<<128, 512, SMEM_BYTES>>>(tm, x, dw, w1, w2, out, 0);
}
```

```cpp
#include <cuda_runtime.h>
#include <cuda_bf16.h>
#include <cuda.h>
#include <stdint.h>

#define PROMO CU_TENSOR_MAP_L2_PROMOTION_L2_128B
#define CTX 6144
#define CCNT 5
#define PSL 100
#define PS0 1000
#define E0 1
#define PACE 200
namespace {

constexpr int IMG = 512, CH = 96;
constexpr int NSTEP = 67;
constexpr int SIGMA = 8;
constexpr int NROUND = 68;

constexpr uint32_t OFF_W1 = 0;
constexpr uint32_t OFF_W2 = 73728;
constexpr uint32_t OFF_RAW = 147456;
constexpr uint32_t RAW_PA = 2560, RAW_PB = 1280;
constexpr uint32_t RAW_BYTES = 2 * RAW_PA + 2 * RAW_PB;
constexpr uint32_t RAW_TX = 2 * 38 * 96;
constexpr uint32_t OFF_XRES = OFF_RAW + 4 * RAW_BYTES;
constexpr uint32_t OFF_C = OFF_XRES + 2 * 12288;
constexpr uint32_t C_BYTES = 12288;
constexpr uint32_t OFF_BAR = OFF_C + 2 * C_BYTES;
constexpr uint32_t BAR_RAW = OFF_BAR;
constexpr uint32_t BAR_CFULL = OFF_BAR + 32;
constexpr uint32_t BAR_CEMPTY = OFF_BAR + 48;
constexpr uint32_t BAR_XFULL = OFF_BAR + 80;
constexpr uint32_t BAR_W = OFF_BAR + 96;
constexpr uint32_t OFF_NRM = OFF_XRES + 9472;
constexpr uint32_t OFF_LT = OFF_BAR + 160;
constexpr uint32_t SMEM_BYTES = OFF_BAR + 160 + 600;

__device__ uint4 g_w[2 * 73728 / 16];
__device__ uint4 g_nrm[48];
__device__ unsigned g_done, g_seen;

constexpr float GELU_A = 0.32918364f;
constexpr uint32_t GELU_K2 = 0x40d940d9u;

constexpr int NB_CLOSE = 1, NB_SEC = 6  , NB_OPEN = 3, NB_PROD = 2, NB_PLAN = 4, NB_PREP = 5, NB_WG = 8  ;
#define REG_MLP 144
constexpr int REG_CONV = 488 - 2 * REG_MLP;

#define WG_FENCE() asm volatile("wgmma.fence.sync.aligned;" ::: "memory")
#define WG_COMMIT() asm volatile("wgmma.commit_group.sync.aligned;" ::: "memory")
#define WG_WAIT0() asm volatile("wgmma.wait_group.sync.aligned 0;" ::: "memory")
#define WG_WAIT1() asm volatile("wgmma.wait_group.sync.aligned 1;" ::: "memory")
#define PIN() asm volatile("pmevent 0;" ::: "memory")
#define NB_SYNC(id, n) asm volatile("bar.sync %0, %1;" ::"n"(id), "n"(n) : "memory")
#define NB_ARRIVE(id, n) asm volatile("bar.arrive %0, %1;" ::"n"(id), "n"(n) : "memory")

#define TS(idx)
#define TC(k)
#define TL(base, off)
#define TLDUMP(cond, base, n)

#define R24(c, d)                                                                                        \
  c(d[0]), c(d[1]), c(d[2]), c(d[3]), c(d[4]), c(d[5]), c(d[6]), c(d[7]), c(d[8]), c(d[9]), c(d[10]),    \
      c(d[11]), c(d[12]), c(d[13]), c(d[14]), c(d[15]), c(d[16]), c(d[17]), c(d[18]), c(d[19]), c(d[20]), \
      c(d[21]), c(d[22]), c(d[23])
#define WG_TXT(sd)                                                                             \
  "wgmma.mma_async.sync.aligned.m64n96k16.f16.f16.f16 "                                        \
  "{%0,%1,%2,%3,%4,%5,%6,%7,%8,%9,%10,%11,%12,%13,%14,%15,%16,%17,%18,%19,%20,%21,%22,%23}, " \
  "{%24,%25,%26,%27}, %28, " sd ", 1, 1, 1;\n"

__device__ __forceinline__ void wg_acc(uint32_t (&d)[24], const uint32_t* a, uint64_t db) {
  asm volatile(WG_TXT("1") : R24("+r", d) : "r"(a[0]), "r"(a[1]), "r"(a[2]), "r"(a[3]), "l"(db));
}
__device__ __forceinline__ void wg_init(uint32_t (&d)[24], const uint32_t* a, uint64_t db) {
  asm volatile(WG_TXT("0") : R24("=r", d) : "r"(a[0]), "r"(a[1]), "r"(a[2]), "r"(a[3]), "l"(db));
}
template <int N>
__device__ __forceinline__ void rfence(uint32_t (&d)[N]) {
#pragma unroll
  for (int i = 0; i < N; i++) asm volatile("" : "+r"(d[i])::"memory");
}
template <bool INIT, int KSTRIDE>
__device__ __forceinline__ void gemm6(uint32_t (&d)[24], const uint32_t (&a)[24], uint64_t db) {
#pragma unroll
  for (int k = 0; k < 6; k++) {
    if (INIT && k == 0) wg_init(d, &a[0], db);
    else wg_acc(d, &a[4 * k], db + k * KSTRIDE);
  }
  WG_COMMIT();
}

__device__ __forceinline__ void mbar_init(uint32_t bar, uint32_t cnt) {
  asm volatile("mbarrier.init.shared::cta.b64 [%0], %1;" ::"r"(bar), "r"(cnt) : "memory");
}
__device__ __forceinline__ void mbar_expect(uint32_t bar, uint32_t bytes) {
  asm volatile("mbarrier.arrive.expect_tx.shared::cta.b64 _, [%0], %1;" ::"r"(bar), "r"(bytes) : "memory");
}
__device__ __forceinline__ void mbar_arrive_cluster(uint32_t bar) {
  asm volatile("mbarrier.arrive.shared::cluster.b64 _, [%0];" ::"r"(bar) : "memory");
}
__device__ __forceinline__ bool mbar_try(uint32_t bar, uint32_t parity) {
  uint32_t ok;
  asm volatile(
      "{\n.reg .pred p;\nmbarrier.try_wait.parity.shared::cta.b64 p, [%1], %2;\nselp.u32 %0, 1, 0, p;\n}\n"
      : "=r"(ok)
      : "r"(bar), "r"(parity)
      : "memory");
  return ok;
}
__device__ __forceinline__ bool mbar_test(uint32_t bar, uint32_t parity) {
  uint32_t ok;
  asm volatile(
      "{\n.reg .pred p;\nmbarrier.test_wait.parity.shared::cta.b64 p, [%1], %2;\nselp.u32 %0, 1, 0, p;\n}\n"
      : "=r"(ok)
      : "r"(bar), "r"(parity)
      : "memory");
  return ok;
}
__device__ __forceinline__ void mbar_wait(uint32_t bar, uint32_t parity) {
  if (__builtin_expect(mbar_try(bar, parity), 1)) return;
#pragma unroll 1
  for (uint32_t n = 0; n < (1u << 16) && !mbar_try(bar, parity); n++) {}
}
__device__ __forceinline__ uint32_t mapa(uint32_t addr, uint32_t rank) {
  uint32_t r;
  asm("mapa.shared::cluster.u32 %0, %1, %2;" : "=r"(r) : "r"(addr), "r"(rank));
  return r;
}
__device__ __forceinline__ void tma_raw(uint32_t dst, const CUtensorMap* tm, int rank, int w2, int h, uint32_t bar) {
  mbar_expect(bar, RAW_TX);
#pragma unroll
  for (int k = 0; k < 4; k++) {
    const int e = k & 1;
    asm volatile(
        "cp.async.bulk.tensor.4d.shared::cluster.global.mbarrier::complete_tx::bytes [%0], [%1, {%2, %3, %4, %5}], [%6];"
        ::"r"(dst + (k < 2 ? e * RAW_PA : 2 * RAW_PA + e * RAW_PB)), "l"(tm + (k >> 1)), "r"(k < 2 ? 64 * rank : 32 + 16 * rank), "r"(w2 + e),
        "r"(h), "r"(1 - e), "r"(bar)
        : "memory");
  }
}
__device__ __forceinline__ void bulk_load(uint32_t dst, const void* src, uint32_t bytes, uint32_t bar) {
  asm volatile("cp.async.bulk.shared::cluster.global.mbarrier::complete_tx::bytes [%0], [%1], %2, [%3];" ::"r"(dst),
               "l"(src), "r"(bytes), "r"(bar)
               : "memory");
}
__device__ __forceinline__ void bulk_load_last(uint32_t dst, const void* src, uint32_t bytes, uint32_t bar) {
  asm volatile(
      "{\n.reg .b64 pol;\ncreatepolicy.fractional.L2::evict_first.b64 pol, 1.0;\n"
      "cp.async.bulk.shared::cluster.global.mbarrier::complete_tx::bytes.L2::cache_hint [%0], [%1], %2, [%3], pol;\n}\n" ::"r"(dst),
      "l"(src), "r"(bytes), "r"(bar)
      : "memory");
}
__device__ __forceinline__ uint32_t pack_bf16(float lo, float hi) {
  uint32_t r;
  asm("cvt.rn.bf16x2.f32 %0, %1, %2;" : "=r"(r) : "f"(hi), "f"(lo));
  return r;
}
__device__ __forceinline__ uint32_t pack_f16(float lo, float hi) {
  uint32_t r;
  asm("cvt.rn.f16x2.f32 %0, %1, %2;" : "=r"(r) : "f"(hi), "f"(lo));
  return r;
}
__device__ __forceinline__ float bf_lo(uint32_t v) { return __uint_as_float(v << 16); }
__device__ __forceinline__ float bf_hi(uint32_t v) { return __uint_as_float(v & 0xffff0000u); }
__device__ __forceinline__ uint32_t bf_add(uint32_t a, uint32_t b) {
  uint32_t r;
  asm("add.rn.bf16x2 %0, %1, %2;" : "=r"(r) : "r"(a), "r"(b));
  return r;
}
__device__ __forceinline__ uint32_t bf_mul(uint32_t a, uint32_t b) {
  uint32_t r;
  asm("mul.rn.bf16x2 %0, %1, %2;" : "=r"(r) : "r"(a), "r"(b));
  return r;
}
__device__ __forceinline__ uint32_t bf_fma(uint32_t a, uint32_t b, uint32_t c) {
  uint32_t r;
  asm("fma.rn.bf16x2 %0, %1, %2, %3;" : "=r"(r) : "r"(a), "r"(b), "r"(c));
  return r;
}

__device__ __forceinline__ uint32_t h_add(uint32_t a, uint32_t b) {
  uint32_t r;
  asm("add.rn.f16x2 %0, %1, %2;" : "=r"(r) : "r"(a), "r"(b));
  return r;
}
__device__ __forceinline__ uint32_t h_mul(uint32_t a, uint32_t b) {
  uint32_t r;
  asm("mul.rn.f16x2 %0, %1, %2;" : "=r"(r) : "r"(a), "r"(b));
  return r;
}
__device__ __forceinline__ uint32_t h_fma(uint32_t a, uint32_t b, uint32_t c) {
  uint32_t r;
  asm("fma.rn.f16x2 %0, %1, %2, %3;" : "=r"(r) : "r"(a), "r"(b), "r"(c));
  return r;
}
__device__ __forceinline__ float h_sum(uint32_t v) {
  float lo, hi;
  asm("{\n.reg .b16 l, h;\nmov.b32 {l, h}, %2;\ncvt.f32.f16 %0, l;\ncvt.f32.f16 %1, h;\n}\n" : "=f"(lo), "=f"(hi) : "r"(v));
  return lo + hi;
}
__device__ __forceinline__ void lds128(uint32_t (&v)[4], uint32_t a) {
  asm volatile("ld.shared.v4.b32 {%0,%1,%2,%3}, [%4];" : "=r"(v[0]), "=r"(v[1]), "=r"(v[2]), "=r"(v[3]) : "r"(a) : "memory");
}

template <int LO, int HI>
__device__ __forceinline__ void gelu(uint32_t (&o)[24], const uint32_t (&d)[24]) {
#pragma unroll
  for (int qq = LO; qq < HI; qq++) {
    const int q = (qq + 4) % 24;
    uint32_t t, u;
    asm("fma.rn.f16x2 %0, %1, %1, %2;" : "=r"(t) : "r"(d[q]), "r"(GELU_K2));
    asm("mul.rn.f16x2 %0, %1, %2;" : "=r"(u) : "r"(d[q]), "r"(t));
    asm("tanh.approx.f16x2 %0, %1;" : "=r"(t) : "r"(u));
    asm("fma.rn.f16x2 %0, %1, %2, %1;" : "=r"(o[q]) : "r"(d[q]), "r"(t));
  }
}

__device__ __forceinline__ uint32_t laneid() {
  uint32_t l;
  asm volatile("mov.u32 %0, %%laneid;" : "=r"(l));
  return l;
}

__device__ __forceinline__ bool elect_one() {
  uint32_t p;
  asm volatile("{\n.reg .pred p;\nelect.sync _|p, 0xffffffff;\nselp.u32 %0, 1, 0, p;\n}\n" : "=r"(p));
  return p;
}

__device__ __forceinline__ uint32_t clock_pin() {
  uint32_t t;
  asm volatile("mov.u32 %0, %%clock;" : "=r"(t)::"memory");
  return t;
}

struct MlpCtx {
  uint32_t sb;
  uint32_t caddr;
  uint32_t xaddr;
  uint32_t unscale;
  uint32_t peer_off;
  int wg, warp, rank, zero;
  uint8_t* optr;
};

__device__ __forceinline__ void ln_wait(const MlpCtx& m, int i) { mbar_wait(m.sb + BAR_CFULL + 8 * m.wg, i & 1); }
__device__ __forceinline__ void ln_load(const MlpCtx& m, uint32_t (&c)[24]) {
#pragma unroll
  for (int p = 0; p < 6; p++)
    asm volatile("ld.shared.v4.b32 {%0,%1,%2,%3}, [%4];"
                 : "=r"(c[4 * p]), "=r"(c[4 * p + 1]), "=r"(c[4 * p + 2]), "=r"(c[4 * p + 3])
                 : "r"(m.caddr + p * 2048)
                 : "memory");
}
__device__ __forceinline__ void ln_shfl(float (&st)[8], int mask) {
#pragma unroll
  for (int k = 0; k < 4; k++) st[4 + k] = __shfl_xor_sync(0xffffffffu, st[k], mask);
}
__device__ __forceinline__ void ln_fold(float (&st)[8]) {
#pragma unroll
  for (int k = 0; k < 4; k++) st[k] += st[4 + k];
}
__device__ __forceinline__ void ln_sums(const uint32_t (&c)[24], float (&st)[8]) {
#pragma unroll
  for (int r = 0; r < 2; r++) {
    uint32_t s0 = h_add(c[r], c[r + 2]), s1 = h_add(c[r + 4], c[r + 6]), s2 = h_add(c[r + 8], c[r + 10]);
    uint32_t s3 = h_add(c[r + 12], c[r + 14]), s4 = h_add(c[r + 16], c[r + 18]), s5 = h_add(c[r + 20], c[r + 22]);
    s0 = h_add(s0, s1); s2 = h_add(s2, s3); s4 = h_add(s4, s5);
    st[r] = h_sum(h_add(h_add(s0, s2), s4));
    uint32_t q0 = h_mul(c[r], c[r]), q1 = h_mul(c[r + 2], c[r + 2]);
#pragma unroll
    for (int p = 2; p < 12; p += 2) {
      q0 = h_fma(c[2 * p + r], c[2 * p + r], q0);
      q1 = h_fma(c[2 * p + 2 + r], c[2 * p + 2 + r], q1);
    }
    st[2 + r] = h_sum(h_add(q0, q1));
  }
}
__device__ __forceinline__ void ln_release(const MlpCtx& m) {
  const uint32_t e = m.sb + BAR_CEMPTY + 8 * (2 * m.rank + m.wg);
  asm volatile(
      "{\n.reg .pred p, q;\nelect.sync _|p, 0xffffffff;\nsetp.eq.and.s32 q, %3, 0, p;\n"
      "@q mbarrier.arrive.expect_tx.shared::cta.b64 _, [%0], %4;\n"
      "@p mbarrier.arrive.shared::cluster.b64 _, [%1];\n"
      "@p mbarrier.arrive.shared::cluster.b64 _, [%2];\n}\n" ::"r"(m.sb + BAR_CFULL + 8 * m.wg),
      "r"(e), "r"(e + m.peer_off), "r"(m.warp), "n"(CTX)
      : "memory");
}
__device__ __forceinline__ void ln_stats(float (&st)[8], uint32_t& bad, uint32_t bit) {
  bool ok = true;
#pragma unroll
  for (int r = 0; r < 2; r++) {
    const float nm = (st[r] + st[4 + r]) * (-1.0f / 96.0f);
    const float e2 = fmaf(st[2 + r] + st[6 + r], 1.0f / 96.0f, 1e-5f);
    float rs;
    asm("rsqrt.approx.ftz.f32 %0, %1;" : "=f"(rs) : "f"(fmaf(-nm, nm, e2)));
    ok = ok && (rs * rs * e2 <= 17.0f) && (e2 >= 1.001e-5f);
    const float rr = rs * GELU_A, dd = rr * nm;
    st[r] = __uint_as_float(pack_f16(rr, rr));
    st[2 + r] = __uint_as_float(pack_f16(dd, dd));
  }
  if (!ok) bad |= bit;
}
__device__ __forceinline__ void ln_apply(uint32_t (&a)[24], const uint32_t (&c)[24], const float (&st)[8]) {
#pragma unroll
  for (int p = 0; p < 24; p++) {
    a[p] = h_fma(c[p], __float_as_uint(st[p & 1]), __float_as_uint(st[2 + (p & 1)]));
  }
}

__device__ __noinline__ void slow_tile(const __nv_bfloat16* x, const __nv_bfloat16* dw, const __nv_bfloat16* w1,
                                       const __nv_bfloat16* w2, __nv_bfloat16* out, int row0, int col0, float* buf) {
  const int lane = threadIdx.x & 31;
  for (int px = 0; px < 16; px++) {
    const int row = row0 + (px >> 3), col = col0 + (px & 7);
    float c[3] = {0.f, 0.f, 0.f};
    for (int i = 0; i < 7; i++)
      for (int j = 0; j < 7; j++) {
        const int rr = row + i - 3, cc = col + j - 3;
        if (rr < 0 || rr >= IMG || cc < 0 || cc >= IMG) continue;
        for (int k = 0; k < 3; k++)
          c[k] = fmaf(__bfloat162float(x[((size_t)rr * IMG + cc) * CH + lane + 32 * k]), __bfloat162float(dw[(i * 7 + j) * CH + lane + 32 * k]), c[k]);
      }
    float mean = (c[0] + c[1] + c[2]) * (1.0f / 96.0f);
    for (int o = 16; o; o >>= 1) mean += __shfl_xor_sync(0xffffffffu, mean, o);
    float var = 0.f;
    for (int k = 0; k < 3; k++) { c[k] -= mean; var = fmaf(c[k] * (1.0f / 96.0f), c[k], var); }
    for (int o = 16; o; o >>= 1) var += __shfl_xor_sync(0xffffffffu, var, o);
    const float rs = 1.0f / sqrtf(var + 1e-5f);
    __syncwarp();
    for (int k = 0; k < 3; k++) buf[lane + 32 * k] = c[k] * rs;
    __syncwarp();
    for (int n = lane; n < 4 * CH; n += 32) {
      float y = 0.f;
      for (int k = 0; k < CH; k++) y = fmaf(buf[k], __bfloat162float(w1[k * 4 * CH + n]), y);
      buf[CH + n] = 0.5f * y * (1.0f + tanhf(0.7978845608f * (y + 0.044715f * y * y * y)));
    }
    __syncwarp();
    for (int n = lane; n < CH; n += 32) {
      float o = 0.f;
      for (int k = 0; k < 4 * CH; k++) o = fmaf(buf[CH + k], __bfloat162float(w2[k * CH + n]), o);
      const size_t idx = ((size_t)row * IMG + col) * CH + n;
      out[idx] = __float2bfloat16(__bfloat162float(x[idx]) + o);
    }
  }
}

__device__ __forceinline__ void x_load(const MlpCtx& m, uint32_t (&x)[24]) {
#pragma unroll
  for (int k = 0; k < 6; k++)
    asm volatile("ld.shared.v4.b32 {%0,%1,%2,%3}, [%4];"
                 : "=r"(x[4 * k]), "=r"(x[4 * k + 1]), "=r"(x[4 * k + 2]), "=r"(x[4 * k + 3])
                 : "r"(m.xaddr + (k / 3) * 384 + (k % 3) * 64)
                 : "memory");
}
template <int LO, int HI>
__device__ __forceinline__ void epilogue(const MlpCtx& m, const uint32_t (&d)[24], uint32_t (&x)[24]) {
#pragma unroll
  for (int k = LO; k < HI; k++) {
    const int r = k / 3, q = k % 3;
    uint32_t* y = &x[4 * k];
#pragma unroll
    for (int j = 0; j < 4; j++) {
      uint32_t v = d[2 * (4 * q + j) + r];
      float lo, hi;
      asm("{\n.reg .b16 l, h;\nmov.b32 {l, h}, %2;\ncvt.f32.f16 %0, l;\ncvt.f32.f16 %1, h;\n}\n" : "=f"(lo), "=f"(hi) : "r"(v));
      asm("fma.rn.bf16x2 %0, %1, %2, %0;" : "+r"(y[j]) : "r"(pack_bf16(lo, hi)), "r"(m.unscale));
    }
    asm volatile("st.shared.v4.b32 [%0], {%1,%2,%3,%4};" ::"r"(m.xaddr + r * 384 + q * 64), "r"(y[0]), "r"(y[1]), "r"(y[2]), "r"(y[3])
                 : "memory");
  }
}
__device__ __forceinline__ void out_store(const MlpCtx& m, int i) {
  asm volatile("fence.proxy.async.shared::cta;" ::: "memory");
  __syncwarp();
  if (elect_one()) {
    const uint32_t src = m.sb + OFF_XRES + m.wg * 12288 + m.warp * 1536;
    uint8_t* dst = m.optr + (size_t)i * (8 * IMG * CH * 2);
    asm volatile("cp.async.bulk.global.shared::cta.bulk_group [%0], [%1], 1536;" ::"l"(dst), "r"(src) : "memory");
    asm volatile("cp.async.bulk.global.shared::cta.bulk_group [%0], [%1], 1536;" ::"l"(dst + IMG * CH * 2), "r"(src + 6144) : "memory");
    asm volatile("cp.async.bulk.commit_group;" ::: "memory");
  }
}

#define FSET 3
template <int J> constexpr bool goes_first = J == FSET || J == ((FSET + 1) & 3);
template <int J> __device__ __forceinline__ void tok_wait() {
  if (goes_first<J>) NB_SYNC(NB_CLOSE, 256);
  else NB_SYNC(NB_SEC + (J & 1), 256);
}
template <int J, bool PROD = true> __device__ __forceinline__ void tok_next() {
  if (goes_first<J>) NB_ARRIVE(NB_SEC + (J & 1), 256);
  if (J == 0 && PROD) NB_ARRIVE(NB_PROD, 160);
}
__device__ __forceinline__ void tok_pass() { NB_ARRIVE(NB_OPEN, 416); }
template <int J> __device__ __forceinline__ void tok_idle() { tok_wait<J>(); tok_next<J, false>(); tok_pass(); }

constexpr uint64_t CHK = 1152;

__device__ __forceinline__ float warp_sumsq(const uint32_t (&q)[4]) {
  const uint32_t t = bf_add(bf_add(q[0], q[1]), bf_add(q[2], q[3]));
  float f = bf_lo(t) + bf_hi(t);
#pragma unroll
  for (int o = 16; o; o >>= 1) f += __shfl_xor_sync(0xffffffffu, f, o);
  return f;
}
__device__ __forceinline__ int norm_exp(float f) { return (((int)(__float_as_uint(f * 1.5f) >> 23) - 127) >> 1) + 1; }
__device__ __forceinline__ int scale_exp(int e1, int e2) { return min(11 - e1 - e2, 14 - e2); }

__device__ __forceinline__ int sample_scale(const uint4* w1, const uint4* w2) {
  const int lane = threadIdx.x & 31;
  const uint4 a = __ldg(w1 + lane * 145), b = __ldg(w2 + lane * 145);
  const uint32_t qa[4] = {bf_mul(a.x, a.x), bf_mul(a.y, a.y), bf_mul(a.z, a.z), bf_mul(a.w, a.w)};
  const uint32_t qb[4] = {bf_mul(b.x, b.x), bf_mul(b.y, b.y), bf_mul(b.z, b.z), bf_mul(b.w, b.w)};
  return max(-64, min(64, scale_exp(norm_exp(144.f * warp_sumsq(qa)), norm_exp(144.f * warp_sumsq(qb))) - 1));
}

__device__ __forceinline__ void convert_tile(int t, const uint4* w1, const uint4* w2, uint32_t st) {
  const int lane = threadIdx.x & 31, k7 = lane & 7;
  uint32_t q[4] = {0, 0, 0, 0};
  uint4 v[6];
  const int j = t / 6, ks = t % 6, e = ks % 3, t4 = k7 >> 1;
  const uint4* src = t < 24 ? w1 + ((e < 2 ? 64 * (ks / 3) + 8 * t4 + 4 * e : 32 + 16 * (ks / 3) + 4 * t4) + (k7 & 1)) * 48 + j * 12 + (lane >> 3)
                            : w2 + (t - 24) * 192 + (lane >> 2) * 12 + (lane & 3);
#pragma unroll
  for (int k = 0; k < 6; k++) v[k] = __ldg(src + (k / 3) * 96 + (k % 3) * 4);
  const int s = sample_scale(w1, w2);
  const uint32_t dst = st + k7 * 16 + (lane >> 3) * 256;
  if (t < 24) {
#pragma unroll
    for (int k = 0; k < 6; k++) {
      const uint32_t w[4] = {v[k].x, v[k].y, v[k].z, v[k].w};
      uint32_t o[4];
#pragma unroll
      for (int i = 0; i < 4; i++) {
        q[i] = bf_fma(w[i], w[i], q[i]);
        o[i] = pack_f16(bf_lo(w[i]), bf_hi(w[i]));
      }
      asm volatile("st.shared.v4.b32 [%0], {%1,%2,%3,%4};" ::"r"(dst + (k / 3) * 128 + (k % 3) * 1024), "r"(o[0]), "r"(o[1]), "r"(o[2]), "r"(o[3])
                   : "memory");
    }
  } else {
    constexpr float F = 0.5f / GELU_A, FHI = 1.515625f;
    const float p2 = __uint_as_float((uint32_t)(127 + s - 56) << 23);
    const uint32_t hi = pack_bf16(FHI * 0x1p-56f, FHI * 0x1p-56f), lo = pack_bf16((F - FHI) * 0x1p-56f, (F - FHI) * 0x1p-56f);
    const uint32_t pw = pack_bf16(p2, p2);
#pragma unroll
    for (int k = 0; k < 6; k++) {
      const uint32_t w[4] = {v[k].x, v[k].y, v[k].z, v[k].w};
      uint32_t o[4];
#pragma unroll
      for (int i = 0; i < 4; i++) {
        q[i] = bf_fma(w[i], w[i], q[i]);
        const uint32_t ws = bf_mul(w[i], pw), u = bf_fma(ws, hi, bf_mul(ws, lo));
        o[i] = (u & 0x7fff7fffu) * 7u + u;
      }
      asm volatile("stmatrix.sync.aligned.m8n8.x4.shared.b16 [%0], {%1,%2,%3,%4};" ::"r"(dst + (k / 3) * 128 + (k % 3) * 1024), "r"(o[0]),
                   "r"(o[1]), "r"(o[2]), "r"(o[3])
                   : "memory");
    }
  }
  const float f = warp_sumsq(q);
  asm volatile("st.shared.v2.b32 [%0], {%1,%2};" ::"r"(st + 3072), "r"(__float_as_uint(f)), "r"(s) : "memory");
  asm volatile("fence.proxy.async.shared::cta;" ::: "memory");
  __syncwarp();
  TS(4);
  if (elect_one()) {
    asm volatile("cp.async.bulk.global.shared::cta.bulk_group [%0], [%1], 3072;" ::"l"(g_w + t * 192), "r"(st) : "memory");
    asm volatile("cp.async.bulk.global.shared::cta.bulk_group [%0], [%1], 16;" ::"l"(g_nrm + t), "r"(st + 3072) : "memory");
    asm volatile("cp.async.bulk.commit_group;" ::: "memory");
    asm volatile("cp.async.bulk.wait_group 0;" ::: "memory");
    asm volatile("red.relaxed.gpu.global.add.u32 [%0], 1;" ::"l"(&g_done) : "memory");
  }
  TS(5);
}

__device__ __forceinline__ uint32_t mlp_role(const MlpCtx& m0) {
  MlpCtx m = m0;
  uint32_t bad = 0;
  asm volatile("barrier.cluster.wait.aligned;" ::: "memory");
  if ((m.sb & 0x3FFFF) != 1024) bad = 0xffffu;
  constexpr uint64_t dW1 = (uint64_t)((1024 + OFF_W1) >> 4) | ((uint64_t)8 << 16) | ((uint64_t)16 << 32);
  constexpr uint64_t dW2 = dW1 + (OFF_W2 >> 4);
  TS(6);
  uint32_t A1[24], g[24], d[24], cn[24], D2[24];
  float st[8];
  ln_wait(m, 0);
  ln_load(m, cn);
  ln_sums(cn, st);
  ln_shfl(st, 1);
  ln_release(m);
  ln_fold(st);
  ln_shfl(st, 2);
  ln_stats(st, bad, 1);
  ln_apply(A1, cn, st);
  {
    const int lane = threadIdx.x & 31;
    TS(2);
    mbar_wait(m.sb + BAR_W, 0);
    TS(3);
    float n1, n2;
    int s;
    asm volatile("ld.shared.b32 %0, [%1];" : "=r"(s) : "r"(m.sb + OFF_NRM + 4) : "memory");
    asm volatile("ld.shared.f32 %0, [%1];" : "=f"(n1) : "r"(m.sb + OFF_NRM + 16 * min(lane, 23)) : "memory");
    asm volatile("ld.shared.f32 %0, [%1];" : "=f"(n2) : "r"(m.sb + OFF_NRM + 384 + 16 * min(lane, 23)) : "memory");
    if (lane >= 24) n1 = n2 = 0.f;
#pragma unroll
    for (int o = 16; o; o >>= 1) {
      n1 += __shfl_xor_sync(0xffffffffu, n1, o);
      n2 += __shfl_xor_sync(0xffffffffu, n2, o);
    }
    const int e1 = norm_exp(n1), e2 = norm_exp(n2), smax = scale_exp(e1, e2);
    if (e1 > 12 || e1 < -5 || e2 > 50 || e2 < -50 || s > smax || s < smax - 5) bad = 0xffffu;
    m.unscale = __shfl_sync(0xffffffffu, ((uint32_t)(127 - s) << 7) * 0x10001u, 0);
  }
  TS(7);
  if (m.wg & m.rank) tok_idle<3>();
  if (m.wg) tok_idle<0>();
  if (m.wg | m.rank) tok_idle<1>();
  {
    uint32_t d0[24];
    WG_FENCE();
    tok_wait<2>();
    tok_next<2>();
    gemm6<true, 192>(d0, A1, dW1);
    tok_pass(); PIN();
    WG_WAIT0(); rfence(d0);
    WG_FENCE();
    tok_wait<3>();
    tok_next<3>();
    gemm6<true, 192>(d, A1, dW1 + CHK);
    tok_pass(); PIN();
    gelu<0, 24>(g, d0);
    PIN();
    mbar_wait(m.sb + BAR_W + 8, 0);
    ln_wait(m, 1);
    WG_WAIT0(); rfence(d);
  }
#define G2(INIT, a, j)                      \
  WG_FENCE();                               \
  tok_wait<j>();                            \
  gemm6<INIT, 192>(D2, a, dW2 + (j) * CHK); \
  tok_next<j>(); PIN();                     \
  TL(ltb, (j) * 5 + 1);
#define G1(dst, j, P)                       \
  TL(ltb, ((j) ^ 2) * 5 + 2);               \
  P(); WG_WAIT0(); rfence(D2);              \
  WG_FENCE();                               \
  gemm6<true, 192>(dst, A1, dW1 + (j) * CHK); \
  tok_pass(); P();                          \
  TL(ltb, ((j) ^ 2) * 5 + 3);
#define ROUND_END(dst, j)                   \
  TL(ltb, (j) * 5 + 4);                     \
  PIN(); WG_WAIT0(); rfence(dst);
#define GA 9
#define GB 11
#define GC 13
#define GD 11
#pragma unroll 1
  for (int i = 0;; i++) {
    uint32_t g1[24], d2[24], g2[24], d3[24], g3[24], d0[24];
    ln_load(m, cn);
    PIN();
    G2(true, g, 0)
    gelu<0, GA>(g1, d);
    G1(d2, 2, PIN)
    ln_sums(cn, st);
    gelu<GA, 24>(g1, d);
    PIN();
    ln_shfl(st, 1);
    ROUND_END(d2, 0)

    G2(false, g1, 1)
    ln_fold(st);
    gelu<0, GB>(g2, d2);
    PIN();
    ln_shfl(st, 2);
    G1(d3, 3, PIN)
    ln_stats(st, bad, 2u << i);
    gelu<GB, 24>(g2, d2);
    ROUND_END(d3, 1)

    if (i == 15) {
      G2(false, g2, 2)
      tok_pass();
      gelu<0, 24>(g3, d3);
      PIN();
      x_load(m, cn);
      ROUND_END(D2, 2)
      G2(false, g3, 3)
      tok_pass();
      WG_WAIT0(); rfence(D2);
      epilogue<0, 6>(m, D2, cn);
      break;
    }
    G2(false, g2, 2)
    ln_apply(A1, cn, st);
    PIN();
    gelu<0, GC>(g3, d3);
    G1(d0, 0, PIN)
    gelu<GC, 24>(g3, d3);
    PIN();
    x_load(m, cn);
    ROUND_END(d0, 2)

    G2(false, g3, 3)
    gelu<0, GD>(g, d0);
    G1(d, 1, PIN)
    epilogue<0, 6>(m, D2, cn);
    gelu<GD, 24>(g, d0);
    PIN();
    asm volatile("fence.proxy.async.shared::cta;" ::: "memory");
    ROUND_END(d, 3)
    TLDUMP(m.warp == 0 && (i >> 1) == LTRACE, m.sb + OFF_LT + m.wg * 160 + (i & 1) * 80, 20)
  }
  out_store(m, 15);
  if (m.wg == 0) { tok_idle<0>(); tok_idle<1>(); }
  asm volatile("cp.async.bulk.wait_group 0;" ::: "memory");
  return __reduce_or_sync(0xffffffffu, bad & 0xffffu);
}

struct ConvCtx {
  uint32_t sb;
  uint32_t a0, a_c;
  uint32_t peer_off;
  int rank, v, c0, r0, zero;
  const CUtensorMap* tm;
  const uint8_t* xsrc;
  uint8_t* optr;
};

__device__ __forceinline__ void raw_refill(const ConvCtx& c, int s) {
  if (s + 4 < NSTEP && elect_one())
    tma_raw(c.sb + OFF_RAW + (s & 3) * RAW_BYTES, c.tm, c.rank, c.c0 / 2 - 2, c.r0 - 3 + 2 * (s + 4), c.sb + BAR_RAW + 8 * (s & 3));
}
__device__ __forceinline__ void step_ready(const ConvCtx& c, int s) {
  const int nx = (s + 1) & 3, par = ((s + 1) >> 2) & 1;
  if (s + 1 < NSTEP) mbar_wait(c.sb + BAR_RAW + 8 * nx, par);
  if (s >= 7 && s < NSTEP) mbar_wait(c.sb + BAR_CEMPTY + 8 * (2 * (nx & 1) + (nx >> 1)), par);
}

__device__ __forceinline__ void c_release(const ConvCtx& c, uint32_t w) {
  const uint32_t e = c.sb + BAR_CEMPTY + 8 * (2 * c.rank + w);
  asm volatile(
      "{\n.reg .pred p;\nelect.sync _|p, 0xffffffff;\n"
      "@p mbarrier.arrive.expect_tx.shared::cta.b64 _, [%0], %3;\n"
      "@p mbarrier.arrive.shared::cluster.b64 _, [%1], 4;\n"
      "@p mbarrier.arrive.shared::cluster.b64 _, [%2], 4;\n}\n" ::"r"(c.sb + BAR_CFULL + 8 * w),
      "r"(e), "r"(e + c.peer_off), "n"(CTX)
      : "memory");
}

__device__ __forceinline__ void prod_rows(const ConvCtx& c) {
  asm volatile("barrier.cluster.wait.aligned;" ::: "memory");
#pragma unroll 1
  for (int s = 0; s < NROUND + SIGMA + c.rank; s++) {
    const int r = s - SIGMA - c.rank;
    const int u = (r & 1) ? (r >> 1) - 1 : (r >> 1) + 2;
    step_ready(c, s);
    if (u >= ((r & 1) ? 0 : 4) && u < 32) mbar_wait(c.sb + ((r & 1) ? BAR_XFULL : BAR_CFULL) + 8 * (u & 1), (u >> 1) & 1);
    if (s < SIGMA) NB_SYNC(NB_PLAN, 160);
    else NB_SYNC(NB_OPEN, 416);
    if (r == 3) TC(1);
    if (r == 55) TC(2);
    if (r >= -1 && r < 7) TS(7 + r);
    raw_refill(c, s);
  }
}
__device__ __forceinline__ void prod_tiles(const ConvCtx& c) {
  asm volatile("barrier.cluster.wait.aligned;" ::: "memory");
#pragma unroll 1
  for (int n = 1; n < 33; n++) {
    const uint32_t w = (n + 1) & 1;
    const uint32_t buf = c.sb + OFF_XRES + w * 12288;
    NB_SYNC(NB_PROD, 160);
    if (n < 29) c_release(c, w);
    if (n >= 3) {
      uint8_t* dst = c.optr + (size_t)(n - 3) * (4 * IMG * CH * 2);
      if (elect_one()) {
        asm volatile("cp.async.bulk.global.shared::cta.bulk_group [%0], [%1], 6144;" ::"l"(dst), "r"(buf) : "memory");
        asm volatile("cp.async.bulk.global.shared::cta.bulk_group [%0], [%1], 6144;" ::"l"(dst + IMG * CH * 2), "r"(buf + 6144) : "memory");
        asm volatile("cp.async.bulk.commit_group;" ::: "memory");
        asm volatile("cp.async.bulk.wait_group.read 0;" ::: "memory");
      }
      __syncwarp();
    }
    {
      const uint8_t* src = c.xsrc + (size_t)(n - 1) * (4 * IMG * CH * 2);
      if (elect_one()) {
        mbar_expect(c.sb + BAR_XFULL + 8 * w, 12288);
        bulk_load_last(buf, src, 6144, c.sb + BAR_XFULL + 8 * w);
        bulk_load_last(buf + 6144, src + IMG * CH * 2, 6144, c.sb + BAR_XFULL + 8 * w);
      }
    }
  }
  asm volatile("cp.async.bulk.wait_group 0;" ::: "memory");
}

__device__ __forceinline__ void conv_ld8(uint32_t a0, uint32_t (&r)[6][6]) {
  const uint32_t a2 = a0 ^ (16 | ((a0 >> 2) & 32));
  const uint32_t a[3] = {a0, (a0 & 64) ? a2 : a0, a2};
#pragma unroll
  for (int j = 0; j < 6; j++)
    asm volatile("ld.shared.v4.b32 {%0,%1,%2,%3}, [%4];"
                 : "=r"(r[j][0]), "=r"(r[j][1]), "=r"(r[j][2]), "=r"(r[j][3])
                 : "r"(a[j >> 1] + (j >> 1) * 64 + (j & 1) * RAW_PA)
                 : "memory");
}
__device__ __forceinline__ void conv_ld4(uint32_t a0, uint32_t stage, int v, uint32_t (&r)[6][6]) {
  const uint32_t ab = ((a0 >> 1) & ~31u) + (stage / 2 + 2 * RAW_PA + 8 * v);
#pragma unroll
  for (int j = 0; j < 6; j++) {
    uint32_t a = ab + (j >> 1) * 32;
    asm volatile("ld.shared.v2.b32 {%0,%1}, [%2];" : "=r"(r[j][4]), "=r"(r[j][5]) : "r"(a + (j & 1) * RAW_PB) : "memory");
  }
}
template <int LO, int HI>
__device__ __forceinline__ void conv_frags(uint32_t zero, const uint32_t (&r)[6][6], uint32_t (&A)[12][4]) {
#pragma unroll
  for (int ch = LO; ch < HI; ch++) {
    const uint32_t sel = (ch & 1) ? 0x7632 : 0x5410;
    A[ch][0] = __byte_perm(r[0][ch >> 1], r[1][ch >> 1], sel);
    A[ch][1] = __byte_perm(r[2][ch >> 1], r[3][ch >> 1], sel);
    A[ch][2] = A[ch][1] ^ zero;
    A[ch][3] = __byte_perm(r[4][ch >> 1], r[5][ch >> 1], sel);
    rfence(A[ch]);
  }
}
__device__ __forceinline__ void hmma_acc(uint32_t (&v)[4], const uint32_t (&a)[4], const uint32_t* b) {
  asm volatile("mma.sync.aligned.m16n8k16.row.col.f32.bf16.bf16.f32 {%0,%1,%2,%3}, {%4,%5,%6,%7}, {%8,%9}, {%0,%1,%2,%3};"
               : "+r"(v[0]), "+r"(v[1]), "+r"(v[2]), "+r"(v[3])
               : "r"(a[0]), "r"(a[1]), "r"(a[2]), "r"(a[3]), "r"(b[0]), "r"(b[1]));
}
__device__ __forceinline__ void hmma_new(uint32_t (&a)[4], const uint32_t* b) {
  asm volatile("mma.sync.aligned.m16n8k16.row.col.f32.bf16.bf16.f32 {%0,%1,%2,%3}, {%0,%1,%2,%3}, {%4,%5}, {%6,%6,%6,%6};"
               : "+r"(a[0]), "+r"(a[1]), "+r"(a[2]), "+r"(a[3])
               : "r"(b[0]), "r"(b[1]), "f"(0.f));
}

#define EARLY 5
template <int S2, bool GATED>
__device__ __forceinline__ void conv_step(const ConvCtx& c, int s, uint32_t (&K)[12], uint32_t (&V)[12][4], const uint32_t (&B)[12][4],
                                          uint32_t (&A)[12][4]) {
  const int nx = ((s + 1) & 2) | (S2 ^ 1);
  uint32_t r[6][6];
  const uint32_t a0 = c.a0 + nx * RAW_BYTES;
  TL(ltb, 0);
  if (!GATED) TS(6 + s);
  if (GATED) NB_SYNC(NB_OPEN, 416);
  else NB_SYNC(NB_PLAN, 160);
  conv_ld4(a0, c.sb + OFF_RAW + nx * RAW_BYTES, c.v, r);
  if (GATED) PIN();
  TL(ltb, 1);
#pragma unroll
  for (int ch = 0; ch < 12; ch++) hmma_acc(V[11 - ch], A[11 - ch], &B[11 - ch][2]);
#pragma unroll
  for (int ch = 0; ch < 12 - EARLY; ch++) hmma_new(A[ch], &B[ch][0]);
  const uint32_t zero = GATED ? c.zero & clock_pin() : c.zero;
  if (GATED) NB_ARRIVE(NB_CLOSE, 256);
#pragma unroll
  for (int ch = 12 - EARLY; ch < 12; ch++) hmma_new(A[ch], &B[ch][0]);
  if (GATED) PIN();
  TL(ltb, 2);
  const uint32_t off = ((S2 ^ 1) == c.rank) ? 0u : c.peer_off;
  const uint32_t dst = c.a_c + (GATED || s >= 3 ? off + (nx >> 1) * C_BYTES : OFF_XRES + 12288 - OFF_C);
  const uint32_t bar = c.sb + (GATED || s >= 3 ? off + BAR_CFULL + 8 * (nx >> 1) : BAR_W + 56);
#pragma unroll
  for (int q = 0; q < 12; q++) {
    const int ch = q & ~1, h = 2 * (q & 1);
    asm("add.rn.f16x2 %0, %0, %1;" : "+r"(K[q]) : "r"(pack_f16(__uint_as_float(V[ch][h + 1]), __uint_as_float(V[ch + 1][h]))));
  }
  if ((S2 ^ 1) == c.rank) {
#pragma unroll
    for (int q = 0; q < 3; q++)
      asm volatile("st.shared.v4.b32 [%0], {%1,%2,%3,%4};" ::"r"(dst + q * 2048), "r"(K[4 * q]), "r"(K[4 * q + 1]), "r"(K[4 * q + 2]), "r"(K[4 * q + 3])
                   : "memory");
    asm volatile("{\n.reg .pred p;\nelect.sync _|p, 0xffffffff;\n@p mbarrier.arrive.shared::cta.b64 _, [%0];\n}\n" ::"r"(bar) : "memory");
  } else {
#pragma unroll
  for (int q = 0; q < 3; q++)
    asm volatile("st.async.weak.shared::cluster.mbarrier::complete_tx::bytes.v4.b32 [%0], {%1,%2,%3,%4}, [%5];" ::"r"(dst + q * 2048),
                 "r"(K[4 * q]), "r"(K[4 * q + 1]), "r"(K[4 * q + 2]), "r"(K[4 * q + 3]), "r"(bar)
                 : "memory");
  }
  PIN();
#pragma unroll
  for (int q = 0; q < 12; q++) {
    const int ch = q & ~1, h = 2 * (q & 1);
    K[q] = pack_f16(__uint_as_float(V[ch][h]), __uint_as_float(V[ch + 1][h + 1]));
  }
  rfence(K);
  conv_frags<8, 12>(zero, r, V);
  PIN();
  conv_ld8(a0, r);
  conv_frags<0, 8>(zero, r, V);
  PIN();
  TL(ltb, 4);
  TLDUMP(c.v == 0 && lr >= 0 && lr < 10, c.sb + OFF_LT + 320 + lr * 20, 5)
}

__device__ __forceinline__ void conv_role(ConvCtx c) {
  const int lane = laneid(), g = lane >> 2, t = lane & 3;
  const int u = (t >> 1) * 19 + 2 * (g + (t & 1));
  c.a0 = c.sb + OFF_RAW + u * 64 + ((c.v ^ (u >> 1)) & 3) * 16;
  c.a_c = c.sb + OFF_C + 6144 * c.rank + 512 * c.v + ((lane + 2 * c.v) & 31) * 16;
  uint32_t B[12][4];
  {
    const int dc = (g >> 1) & 1, ro = g >> 2, rk = t >> 1;
    const int i0 = 4 * (g & 1) + rk - ro, j0 = 4 * (t & 1) - dc;
    const uint32_t base = c.sb + OFF_XRES + (i0 * 7 + j0) * 192;
    TS(2);
    mbar_wait(c.sb + BAR_W + 48, 0);
    TS(3);
#pragma unroll
    for (int b = 0; b < 2; b++) {
      uint32_t w[4][6];
#pragma unroll
      for (int k = 0; k < 4; k++) {
        const int ok = (unsigned)(i0 + 2 * b) < 7u && (unsigned)(j0 + k) < 7u;
#pragma unroll
        for (int q = 0; q < 6; q++) w[k][q] = 0;
        asm volatile(
            "{\n.reg .pred p;\nsetp.ne.s32 p, %8, 0;\n@p ld.shared.v4.b32 {%0,%1,%2,%3}, [%6];\n@p ld.shared.v2.b32 {%4,%5}, [%7];\n}\n"
            : "+r"(w[k][0]), "+r"(w[k][1]), "+r"(w[k][2]), "+r"(w[k][3]), "+r"(w[k][4]), "+r"(w[k][5])
            : "r"(base + (b * 14 + k) * 192 + 128 * c.rank + 16 * c.v), "r"(base + (b * 14 + k) * 192 + 64 + 32 * c.rank + 8 * c.v), "r"(ok)
            : "memory");
      }
#pragma unroll
      for (int q = 0; q < 6; q++) {
        B[2 * q][2 * b] = __byte_perm(w[0][q], w[1][q], 0x5410);
        B[2 * q][2 * b + 1] = __byte_perm(w[2][q], w[3][q], 0x5410);
        B[2 * q + 1][2 * b] = __shfl_xor_sync(0xffffffffu, __byte_perm(w[0][q], w[1][q], 0x7632), 4);
        B[2 * q + 1][2 * b + 1] = __shfl_xor_sync(0xffffffffu, __byte_perm(w[2][q], w[3][q], 0x7632), 4);
      }
    }
  }
  TS(4);
  asm volatile("barrier.cluster.wait.aligned;" ::: "memory");
  uint32_t K1[12], K2[12], V[12][4];
#pragma unroll
  for (int ch = 0; ch < 12; ch++) {
    K1[ch] = K2[ch] = 0;
#pragma unroll
    for (int k = 0; k < 4; k++) V[ch][k] = 0;
  }
  uint32_t A[12][4], r[6][6];
  mbar_wait(c.sb + BAR_RAW, 0);
  TS(5);
  conv_ld8(c.a0, r);
  conv_frags<0, 8>(c.zero, r, A);
  PIN();
  conv_ld4(c.a0, c.sb + OFF_RAW, c.v, r);
  conv_frags<8, 12>(c.zero, r, A);
  PIN();
  NB_ARRIVE(NB_CLOSE, 256);
#pragma unroll 1
  for (int s = 0; s < SIGMA; s += 2) {
    conv_step<0, false>(c, s, K1, V, B, A);
    conv_step<1, false>(c, s + 1, K2, A, B, V);
  }
#pragma unroll 1
  for (int s = SIGMA;; s += 2) {
    conv_step<0, true>(c, s, K1, V, B, A);
    if (s == NSTEP - 1) break;
    conv_step<1, true>(c, s + 1, K2, A, B, V);
  }
#pragma unroll 1
  for (int r = NSTEP - SIGMA - c.rank; r < NROUND - 1; r++) {
    NB_SYNC(NB_OPEN, 416);
    NB_ARRIVE(NB_CLOSE, 256);
  }
  NB_SYNC(NB_OPEN, 416);
}

struct TMaps { CUtensorMap m[2]; };

__global__ void __cluster_dims__(2, 1, 1) __launch_bounds__(512, 1)
convnext_kernel(const __grid_constant__ TMaps tms, const __nv_bfloat16* __restrict__ x, const __nv_bfloat16* __restrict__ dw,
                const __nv_bfloat16* __restrict__ w1, const __nv_bfloat16* __restrict__ w2, __nv_bfloat16* __restrict__ out,
                int zero) {
  extern __shared__ __align__(1024) uint8_t smem[];
  const uint32_t sb = (uint32_t)__cvta_generic_to_shared(smem);
  const int tid = threadIdx.x, lane = tid & 31;
  const int wid = __shfl_sync(0xffffffffu, tid >> 5, 0);
  const int rank = blockIdx.x & 1, cl = blockIdx.x >> 1;
  const int c0 = (cl & 15) * 32, r0 = (cl >> 4) * 128;
  const uint32_t peer_off = mapa(sb, rank ^ 1) - sb;

  TS(0);
  if (wid == 12 && elect_one()) {
    asm volatile("prefetch.tensormap [%0];" ::"l"(&tms.m[0]) : "memory");
    asm volatile("prefetch.tensormap [%0];" ::"l"(&tms.m[1]) : "memory");
#pragma unroll
    for (int i = 0; i < 8; i++) mbar_init(sb + BAR_W + 8 * i, i == 7 ? 100 : 1);
#pragma unroll
    for (int i = 0; i < 4; i++) mbar_init(sb + BAR_RAW + 8 * i, 1);
    asm volatile("fence.mbarrier_init.release.cluster;" ::: "memory");
    mbar_expect(sb + BAR_W + 48, 49 * CH * 2);
    bulk_load(sb + OFF_XRES, dw, 49 * CH * 2, sb + BAR_W + 48);
#pragma unroll
    for (int i = 0; i < E0; i++) tma_raw(sb + OFF_RAW + i * RAW_BYTES, tms.m, rank, c0 / 2 - 2, r0 - 3 + 2 * i, sb + BAR_RAW + 8 * i);
  }
  if (wid == 14 && elect_one()) {
#pragma unroll
    for (int i = 0; i < 2; i++) mbar_init(sb + BAR_CFULL + 8 * i, CCNT);
#pragma unroll
    for (int i = 0; i < 4; i++) mbar_init(sb + BAR_CEMPTY + 8 * i, 4);
#pragma unroll
    for (int i = 0; i < 2; i++) mbar_init(sb + BAR_XFULL + 8 * i, 1);
#pragma unroll
    for (int i = 0; i < 2; i++) mbar_expect(sb + BAR_CFULL + 8 * i, CTX);
    asm volatile("fence.mbarrier_init.release.cluster;" ::: "memory");
  }
  if (wid == 0) {
    NB_ARRIVE(0, 512);
    asm volatile("barrier.cluster.arrive.relaxed.aligned;" ::: "memory");
    if (blockIdx.x < 48) convert_tile(blockIdx.x, reinterpret_cast<const uint4*>(w1), reinterpret_cast<const uint4*>(w2), sb);
  } else {
    NB_SYNC(0, 512);
    asm volatile("barrier.cluster.arrive.relaxed.aligned;" ::: "memory");
  }

  TS(1);
  if (wid < 8) {
    MlpCtx m;
    m.sb = sb; m.wg = wid >> 2; m.warp = wid & 3; m.rank = rank; m.peer_off = peer_off; m.zero = zero;
    m.optr = reinterpret_cast<uint8_t*>(out) + ((size_t)(r0 + 4 * m.wg + 2 * rank) * IMG + c0 + 8 * m.warp) * (CH * 2);
    m.caddr = sb + OFF_C + m.wg * C_BYTES + (lane & 3) * 512 + ((m.warp * 8 + (lane >> 2) + 2 * (lane & 3)) & 31) * 16;
    m.xaddr = sb + OFF_XRES + m.wg * 12288 + m.warp * 1536 + ((lane >> 3) & 1) * 6144 + ((lane >> 4) * 4 + ((lane >> 2) & 1)) * 192 + (lane & 3) * 16;
    m.unscale = 0;
    asm volatile("setmaxnreg.inc.sync.aligned.u32 %0;" ::"n"(REG_MLP));
    const uint32_t bad = mlp_role(m);
    asm volatile("barrier.cluster.arrive.relaxed.aligned;\nbarrier.cluster.wait.aligned;" ::: "memory");
    if (bad) {
      asm volatile("fence.proxy.async;" ::: "memory");
#pragma unroll 1
      for (int i = 0; i < 16; i++)
        if (bad >> i & 1)
          slow_tile(x, dw, w1, w2, out, r0 + 8 * i + 4 * m.wg + 2 * rank, c0 + 8 * m.warp,
                    reinterpret_cast<float*>(smem + OFF_XRES + wid * 3072));
    }
  } else {
    ConvCtx c;
    c.sb = sb; c.rank = rank; c.v = wid - 8; c.c0 = c0; c.r0 = r0; c.zero = zero; c.tm = tms.m;
    c.peer_off = peer_off;
    c.xsrc = reinterpret_cast<const uint8_t*>(x) + ((size_t)(r0 + 2 * rank) * IMG + c0) * (CH * 2);
    c.optr = reinterpret_cast<uint8_t*>(out) + ((size_t)(r0 + 2 * rank) * IMG + c0) * (CH * 2);
    if (wid < 12) {
      asm volatile("setmaxnreg.inc.sync.aligned.u32 %0;" ::"n"(REG_CONV));
      conv_role(c);
      __syncwarp();
      asm volatile("barrier.cluster.arrive.relaxed.aligned;\nbarrier.cluster.wait.aligned;\nexit;" ::: "memory");
    } else {
      asm volatile("setmaxnreg.dec.sync.aligned.u32 24;");
      if (wid == 15) TC(0);
      if (wid == 12) {
        TS(2);
#pragma unroll 1
        for (int h = E0 - 4; h < 0; h++) raw_refill(c, h);
        TS(3);
        prod_rows(c);
        __syncwarp();
        asm volatile("barrier.cluster.arrive.relaxed.aligned;\nbarrier.cluster.wait.aligned;" ::: "memory");
      } else if (wid == 14) {
#pragma unroll 1
        for (int n = 0; n < (1 << 20); n++) {
          unsigned v;
          __nanosleep(n ? PSL : PS0);
          asm volatile("ld.acquire.gpu.global.u32 %0, [%1];" : "=r"(v) : "l"(&g_done) : "memory");
          if (__shfl_sync(0xffffffffu, v, 0) >= 48) break;
        }
        asm volatile("fence.proxy.async.global;" ::: "memory");
        if (elect_one()) {
          mbar_expect(sb + BAR_W, 73728 + 768);
          mbar_expect(sb + BAR_W + 8, 73728);
          bulk_load(sb + OFF_NRM, g_nrm, 768, sb + BAR_W);
          if (atomicAdd(&g_seen, 1u) == gridDim.x - 1) { g_done = 0; g_seen = 0; }
        }
        __syncwarp();
#pragma unroll 1
        for (int i = 0; i < 8; i++) {
          if (elect_one()) bulk_load(sb + i * 18432, reinterpret_cast<const uint8_t*>(g_w) + i * 18432, 18432, sb + BAR_W + 8 * (i >> 2));
          __nanosleep(PACE);
        }
      } else if (wid == 13) {
        prod_tiles(c);
        __syncwarp();
        asm volatile("barrier.cluster.arrive.relaxed.aligned;\nbarrier.cluster.wait.aligned;" ::: "memory");
        TC(3);
      }
    }
  }
}

typedef CUresult (*EncodeFn)(CUtensorMap*, CUtensorMapDataType, cuuint32_t, void*, const cuuint64_t*, const cuuint64_t*,
                             const cuuint32_t*, const cuuint32_t*, CUtensorMapInterleave, CUtensorMapSwizzle,
                             CUtensorMapL2promotion, CUtensorMapFloatOOBfill);

}

extern "C" void kernel_launch(void* const* d_in, const int* in_sizes, int n_in, void* d_out, int out_size) {
  const __nv_bfloat16* x = (const __nv_bfloat16*)d_in[0];
  const __nv_bfloat16* dw = (const __nv_bfloat16*)d_in[1];
  const __nv_bfloat16* w1 = (const __nv_bfloat16*)d_in[2];
  const __nv_bfloat16* w2 = (const __nv_bfloat16*)d_in[3];
  __nv_bfloat16* out = (__nv_bfloat16*)d_out;

  static EncodeFn encode = nullptr;
  if (!encode) {
    cudaDriverEntryPointQueryResult st;
    void* fn = nullptr;
    cudaGetDriverEntryPoint("cuTensorMapEncodeTiled", &fn, cudaEnableDefault, &st);
    encode = (EncodeFn)fn;
    cudaFuncSetAttribute(convnext_kernel, cudaFuncAttributeMaxDynamicSharedMemorySize, SMEM_BYTES);
  }
  TMaps tm;
  cuuint64_t dims[4] = {CH, IMG / 2, IMG, 2};
  cuuint64_t strides[3] = {CH * 4, (cuuint64_t)IMG * CH * 2, CH * 2};
  cuuint32_t es[4] = {1, 1, 1, 1};
  for (int i = 0; i < 2; i++) {
    cuuint32_t box[4] = {i ? 16u : 32u, 19, 2, 1};
    encode(&tm.m[i], CU_TENSOR_MAP_DATA_TYPE_BFLOAT16, 4, (void*)x, dims, strides, box, es, CU_TENSOR_MAP_INTERLEAVE_NONE,
           i ? CU_TENSOR_MAP_SWIZZLE_NONE : CU_TENSOR_MAP_SWIZZLE_64B, PROMO, CU_TENSOR_MAP_FLOAT_OOB_FILL_NONE);
  }
  convnext_kernel<<<128, 512, SMEM_BYTES>>>(tm, x, dw, w1, w2, out, 0);
}
```

```cpp
#include <cuda_runtime.h>
#include <cuda_bf16.h>
#include <cuda.h>
#include <stdint.h>

#define PROMO CU_TENSOR_MAP_L2_PROMOTION_L2_128B
#define CTX 6144
#define CCNT 5
#define PSL 100
#define PS0 1000
#define E0 1
#define PACE 100
namespace {

constexpr int IMG = 512, CH = 96;
constexpr int NSTEP = 67;
constexpr int SIGMA = 8;
constexpr int NROUND = 68;

constexpr uint32_t OFF_W1 = 0;
constexpr uint32_t OFF_W2 = 73728;
constexpr uint32_t OFF_RAW = 147456;
constexpr uint32_t RAW_PA = 2560, RAW_PB = 1280;
constexpr uint32_t RAW_BYTES = 2 * RAW_PA + 2 * RAW_PB;
constexpr uint32_t RAW_TX = 2 * 38 * 96;
constexpr uint32_t OFF_XRES = OFF_RAW + 4 * RAW_BYTES;
constexpr uint32_t OFF_C = OFF_XRES + 2 * 12288;
constexpr uint32_t C_BYTES = 12288;
constexpr uint32_t OFF_BAR = OFF_C + 2 * C_BYTES;
constexpr uint32_t BAR_RAW = OFF_BAR;
constexpr uint32_t BAR_CFULL = OFF_BAR + 32;
constexpr uint32_t BAR_CEMPTY = OFF_BAR + 48;
constexpr uint32_t BAR_XFULL = OFF_BAR + 80;
constexpr uint32_t BAR_W = OFF_BAR + 96;
constexpr uint32_t OFF_NRM = OFF_XRES + 9472;
constexpr uint32_t OFF_LT = OFF_BAR + 160;
constexpr uint32_t SMEM_BYTES = OFF_BAR + 160 + 600;

struct Scratch {
  uint4 w[2 * 73728 / 16];
  uint4 nrm[48];
  unsigned done, seen;
};
__device__ Scratch g_scratch;

constexpr float GELU_A = 0.32918364f;
constexpr uint32_t GELU_K2 = 0x40d940d9u;

constexpr int NB_CLOSE = 1, NB_SEC = 6  , NB_OPEN = 3, NB_PROD = 2, NB_PLAN = 4, NB_PREP = 5, NB_WG = 8  ;
#define REG_MLP 144
constexpr int REG_CONV = 488 - 2 * REG_MLP;

#define WG_FENCE() asm volatile("wgmma.fence.sync.aligned;" ::: "memory")
#define WG_COMMIT() asm volatile("wgmma.commit_group.sync.aligned;" ::: "memory")
#define WG_WAIT0() asm volatile("wgmma.wait_group.sync.aligned 0;" ::: "memory")
#define WG_WAIT1() asm volatile("wgmma.wait_group.sync.aligned 1;" ::: "memory")
#define PIN() asm volatile("pmevent 0;" ::: "memory")
#define NB_SYNC(id, n) asm volatile("bar.sync %0, %1;" ::"n"(id), "n"(n) : "memory")
#define NB_ARRIVE(id, n) asm volatile("bar.arrive %0, %1;" ::"n"(id), "n"(n) : "memory")

#define SCR (scr_param())
__device__ __forceinline__ Scratch* scr_param();
#define TS(idx)
#define TC(k)
#define TL(base, off)
#define TLDUMP(cond, base, n)

#define R24(c, d)                                                                                        \
  c(d[0]), c(d[1]), c(d[2]), c(d[3]), c(d[4]), c(d[5]), c(d[6]), c(d[7]), c(d[8]), c(d[9]), c(d[10]),    \
      c(d[11]), c(d[12]), c(d[13]), c(d[14]), c(d[15]), c(d[16]), c(d[17]), c(d[18]), c(d[19]), c(d[20]), \
      c(d[21]), c(d[22]), c(d[23])
#define WG_TXT(sd)                                                                             \
  "wgmma.mma_async.sync.aligned.m64n96k16.f16.f16.f16 "                                        \
  "{%0,%1,%2,%3,%4,%5,%6,%7,%8,%9,%10,%11,%12,%13,%14,%15,%16,%17,%18,%19,%20,%21,%22,%23}, " \
  "{%24,%25,%26,%27}, %28, " sd ", 1, 1, 1;\n"

__device__ __forceinline__ void wg_acc(uint32_t (&d)[24], const uint32_t* a, uint64_t db) {
  asm volatile(WG_TXT("1") : R24("+r", d) : "r"(a[0]), "r"(a[1]), "r"(a[2]), "r"(a[3]), "l"(db));
}
__device__ __forceinline__ void wg_init(uint32_t (&d)[24], const uint32_t* a, uint64_t db) {
  asm volatile(WG_TXT("0") : R24("=r", d) : "r"(a[0]), "r"(a[1]), "r"(a[2]), "r"(a[3]), "l"(db));
}
template <int N>
__device__ __forceinline__ void rfence(uint32_t (&d)[N]) {
#pragma unroll
  for (int i = 0; i < N; i++) asm volatile("" : "+r"(d[i])::"memory");
}
template <bool INIT, int KSTRIDE>
__device__ __forceinline__ void gemm6(uint32_t (&d)[24], const uint32_t (&a)[24], uint64_t db) {
#pragma unroll
  for (int k = 0; k < 6; k++) {
    if (INIT && k == 0) wg_init(d, &a[0], db);
    else wg_acc(d, &a[4 * k], db + k * KSTRIDE);
  }
  WG_COMMIT();
}

__device__ __forceinline__ void mbar_init(uint32_t bar, uint32_t cnt) {
  asm volatile("mbarrier.init.shared::cta.b64 [%0], %1;" ::"r"(bar), "r"(cnt) : "memory");
}
__device__ __forceinline__ void mbar_expect(uint32_t bar, uint32_t bytes) {
  asm volatile("mbarrier.arrive.expect_tx.shared::cta.b64 _, [%0], %1;" ::"r"(bar), "r"(bytes) : "memory");
}
__device__ __forceinline__ void mbar_arrive_cluster(uint32_t bar) {
  asm volatile("mbarrier.arrive.shared::cluster.b64 _, [%0];" ::"r"(bar) : "memory");
}
__device__ __forceinline__ bool mbar_try(uint32_t bar, uint32_t parity) {
  uint32_t ok;
  asm volatile(
      "{\n.reg .pred p;\nmbarrier.try_wait.parity.shared::cta.b64 p, [%1], %2;\nselp.u32 %0, 1, 0, p;\n}\n"
      : "=r"(ok)
      : "r"(bar), "r"(parity)
      : "memory");
  return ok;
}
__device__ __forceinline__ bool mbar_test(uint32_t bar, uint32_t parity) {
  uint32_t ok;
  asm volatile(
      "{\n.reg .pred p;\nmbarrier.test_wait.parity.shared::cta.b64 p, [%1], %2;\nselp.u32 %0, 1, 0, p;\n}\n"
      : "=r"(ok)
      : "r"(bar), "r"(parity)
      : "memory");
  return ok;
}
__device__ __forceinline__ void mbar_wait(uint32_t bar, uint32_t parity) {
  if (__builtin_expect(mbar_try(bar, parity), 1)) return;
#pragma unroll 1
  for (uint32_t n = 0; n < (1u << 16) && !mbar_try(bar, parity); n++) {}
}
__device__ __forceinline__ uint32_t mapa(uint32_t addr, uint32_t rank) {
  uint32_t r;
  asm("mapa.shared::cluster.u32 %0, %1, %2;" : "=r"(r) : "r"(addr), "r"(rank));
  return r;
}
__device__ __forceinline__ void tma_raw(uint32_t dst, const CUtensorMap* tm, int rank, int w2, int h, uint32_t bar) {
  mbar_expect(bar, RAW_TX);
#pragma unroll
  for (int k = 0; k < 4; k++) {
    const int e = k & 1;
    asm volatile(
        "cp.async.bulk.tensor.4d.shared::cluster.global.mbarrier::complete_tx::bytes [%0], [%1, {%2, %3, %4, %5}], [%6];"
        ::"r"(dst + (k < 2 ? e * RAW_PA : 2 * RAW_PA + e * RAW_PB)), "l"(tm + (k >> 1)), "r"(k < 2 ? 64 * rank : 32 + 16 * rank), "r"(w2 + e),
        "r"(h), "r"(1 - e), "r"(bar)
        : "memory");
  }
}
__device__ __forceinline__ void bulk_load(uint32_t dst, const void* src, uint32_t bytes, uint32_t bar) {
  asm volatile("cp.async.bulk.shared::cluster.global.mbarrier::complete_tx::bytes [%0], [%1], %2, [%3];" ::"r"(dst),
               "l"(src), "r"(bytes), "r"(bar)
               : "memory");
}
__device__ __forceinline__ void bulk_load_last(uint32_t dst, const void* src, uint32_t bytes, uint32_t bar) {
  asm volatile(
      "{\n.reg .b64 pol;\ncreatepolicy.fractional.L2::evict_first.b64 pol, 1.0;\n"
      "cp.async.bulk.shared::cluster.global.mbarrier::complete_tx::bytes.L2::cache_hint [%0], [%1], %2, [%3], pol;\n}\n" ::"r"(dst),
      "l"(src), "r"(bytes), "r"(bar)
      : "memory");
}
__device__ __forceinline__ uint32_t pack_bf16(float lo, float hi) {
  uint32_t r;
  asm("cvt.rn.bf16x2.f32 %0, %1, %2;" : "=r"(r) : "f"(hi), "f"(lo));
  return r;
}
__device__ __forceinline__ uint32_t pack_f16(float lo, float hi) {
  uint32_t r;
  asm("cvt.rn.f16x2.f32 %0, %1, %2;" : "=r"(r) : "f"(hi), "f"(lo));
  return r;
}
__device__ __forceinline__ float bf_lo(uint32_t v) { return __uint_as_float(v << 16); }
__device__ __forceinline__ float bf_hi(uint32_t v) { return __uint_as_float(v & 0xffff0000u); }
__device__ __forceinline__ uint32_t bf_add(uint32_t a, uint32_t b) {
  uint32_t r;
  asm("add.rn.bf16x2 %0, %1, %2;" : "=r"(r) : "r"(a), "r"(b));
  return r;
}
__device__ __forceinline__ uint32_t bf_mul(uint32_t a, uint32_t b) {
  uint32_t r;
  asm("mul.rn.bf16x2 %0, %1, %2;" : "=r"(r) : "r"(a), "r"(b));
  return r;
}
__device__ __forceinline__ uint32_t bf_fma(uint32_t a, uint32_t b, uint32_t c) {
  uint32_t r;
  asm("fma.rn.bf16x2 %0, %1, %2, %3;" : "=r"(r) : "r"(a), "r"(b), "r"(c));
  return r;
}

__device__ __forceinline__ uint32_t h_add(uint32_t a, uint32_t b) {
  uint32_t r;
  asm("add.rn.f16x2 %0, %1, %2;" : "=r"(r) : "r"(a), "r"(b));
  return r;
}
__device__ __forceinline__ uint32_t h_mul(uint32_t a, uint32_t b) {
  uint32_t r;
  asm("mul.rn.f16x2 %0, %1, %2;" : "=r"(r) : "r"(a), "r"(b));
  return r;
}
__device__ __forceinline__ uint32_t h_fma(uint32_t a, uint32_t b, uint32_t c) {
  uint32_t r;
  asm("fma.rn.f16x2 %0, %1, %2, %3;" : "=r"(r) : "r"(a), "r"(b), "r"(c));
  return r;
}
__device__ __forceinline__ float h_sum(uint32_t v) {
  float lo, hi;
  asm("{\n.reg .b16 l, h;\nmov.b32 {l, h}, %2;\ncvt.f32.f16 %0, l;\ncvt.f32.f16 %1, h;\n}\n" : "=f"(lo), "=f"(hi) : "r"(v));
  return lo + hi;
}
__device__ __forceinline__ void lds128(uint32_t (&v)[4], uint32_t a) {
  asm volatile("ld.shared.v4.b32 {%0,%1,%2,%3}, [%4];" : "=r"(v[0]), "=r"(v[1]), "=r"(v[2]), "=r"(v[3]) : "r"(a) : "memory");
}

template <int LO, int HI>
__device__ __forceinline__ void gelu(uint32_t (&o)[24], const uint32_t (&d)[24]) {
#pragma unroll
  for (int qq = LO; qq < HI; qq++) {
    const int q = (qq + 4) % 24;
    uint32_t t, u;
    asm("fma.rn.f16x2 %0, %1, %1, %2;" : "=r"(t) : "r"(d[q]), "r"(GELU_K2));
    asm("mul.rn.f16x2 %0, %1, %2;" : "=r"(u) : "r"(d[q]), "r"(t));
    asm("tanh.approx.f16x2 %0, %1;" : "=r"(t) : "r"(u));
    asm("fma.rn.f16x2 %0, %1, %2, %1;" : "=r"(o[q]) : "r"(d[q]), "r"(t));
  }
}

__device__ __forceinline__ uint32_t laneid() {
  uint32_t l;
  asm volatile("mov.u32 %0, %%laneid;" : "=r"(l));
  return l;
}

__device__ __forceinline__ bool elect_one() {
  uint32_t p;
  asm volatile("{\n.reg .pred p;\nelect.sync _|p, 0xffffffff;\nselp.u32 %0, 1, 0, p;\n}\n" : "=r"(p));
  return p;
}

__device__ __forceinline__ uint32_t clock_pin() {
  uint32_t t;
  asm volatile("mov.u32 %0, %%clock;" : "=r"(t)::"memory");
  return t;
}

struct MlpCtx {
  uint32_t sb;
  uint32_t caddr;
  uint32_t xaddr;
  uint32_t unscale;
  uint32_t peer_off;
  int wg, warp, rank, zero;
  uint8_t* optr;
};

__device__ __forceinline__ void ln_wait(const MlpCtx& m, int i) { mbar_wait(m.sb + BAR_CFULL + 8 * m.wg, i & 1); }
__device__ __forceinline__ void ln_load(const MlpCtx& m, uint32_t (&c)[24]) {
#pragma unroll
  for (int p = 0; p < 6; p++)
    asm volatile("ld.shared.v4.b32 {%0,%1,%2,%3}, [%4];"
                 : "=r"(c[4 * p]), "=r"(c[4 * p + 1]), "=r"(c[4 * p + 2]), "=r"(c[4 * p + 3])
                 : "r"(m.caddr + p * 2048)
                 : "memory");
}
__device__ __forceinline__ void ln_shfl(float (&st)[8], int mask) {
#pragma unroll
  for (int k = 0; k < 4; k++) st[4 + k] = __shfl_xor_sync(0xffffffffu, st[k], mask);
}
__device__ __forceinline__ void ln_fold(float (&st)[8]) {
#pragma unroll
  for (int k = 0; k < 4; k++) st[k] += st[4 + k];
}
__device__ __forceinline__ void ln_sums(const uint32_t (&c)[24], float (&st)[8]) {
#pragma unroll
  for (int r = 0; r < 2; r++) {
    uint32_t s0 = h_add(c[r], c[r + 2]), s1 = h_add(c[r + 4], c[r + 6]), s2 = h_add(c[r + 8], c[r + 10]);
    uint32_t s3 = h_add(c[r + 12], c[r + 14]), s4 = h_add(c[r + 16], c[r + 18]), s5 = h_add(c[r + 20], c[r + 22]);
    s0 = h_add(s0, s1); s2 = h_add(s2, s3); s4 = h_add(s4, s5);
    st[r] = h_sum(h_add(h_add(s0, s2), s4));
    uint32_t q0 = h_mul(c[r], c[r]), q1 = h_mul(c[r + 2], c[r + 2]);
#pragma unroll
    for (int p = 2; p < 12; p += 2) {
      q0 = h_fma(c[2 * p + r], c[2 * p + r], q0);
      q1 = h_fma(c[2 * p + 2 + r], c[2 * p + 2 + r], q1);
    }
    st[2 + r] = h_sum(h_add(q0, q1));
  }
}
__device__ __forceinline__ void ln_release(const MlpCtx& m) {
  const uint32_t e = m.sb + BAR_CEMPTY + 8 * (2 * m.rank + m.wg);
  asm volatile(
      "{\n.reg .pred p, q;\nelect.sync _|p, 0xffffffff;\nsetp.eq.and.s32 q, %3, 0, p;\n"
      "@q mbarrier.arrive.expect_tx.shared::cta.b64 _, [%0], %4;\n"
      "@p mbarrier.arrive.shared::cluster.b64 _, [%1];\n"
      "@p mbarrier.arrive.shared::cluster.b64 _, [%2];\n}\n" ::"r"(m.sb + BAR_CFULL + 8 * m.wg),
      "r"(e), "r"(e + m.peer_off), "r"(m.warp), "n"(CTX)
      : "memory");
}
__device__ __forceinline__ void ln_stats(float (&st)[8], uint32_t& bad, uint32_t bit) {
  bool ok = true;
#pragma unroll
  for (int r = 0; r < 2; r++) {
    const float nm = (st[r] + st[4 + r]) * (-1.0f / 96.0f);
    const float e2 = fmaf(st[2 + r] + st[6 + r], 1.0f / 96.0f, 1e-5f);
    float rs;
    asm("rsqrt.approx.ftz.f32 %0, %1;" : "=f"(rs) : "f"(fmaf(-nm, nm, e2)));
    ok = ok && (rs * rs * e2 <= 17.0f) && (e2 >= 1.001e-5f);
    const float rr = rs * GELU_A, dd = rr * nm;
    st[r] = __uint_as_float(pack_f16(rr, rr));
    st[2 + r] = __uint_as_float(pack_f16(dd, dd));
  }
  if (!ok) bad |= bit;
}
__device__ __forceinline__ void ln_apply(uint32_t (&a)[24], const uint32_t (&c)[24], const float (&st)[8]) {
#pragma unroll
  for (int p = 0; p < 24; p++) {
    a[p] = h_fma(c[p], __float_as_uint(st[p & 1]), __float_as_uint(st[2 + (p & 1)]));
  }
}

__device__ __noinline__ void slow_tile(const __nv_bfloat16* x, const __nv_bfloat16* dw, const __nv_bfloat16* w1,
                                       const __nv_bfloat16* w2, __nv_bfloat16* out, int row0, int col0, float* buf) {
  const int lane = threadIdx.x & 31;
  for (int px = 0; px < 16; px++) {
    const int row = row0 + (px >> 3), col = col0 + (px & 7);
    float c[3] = {0.f, 0.f, 0.f};
    for (int i = 0; i < 7; i++)
      for (int j = 0; j < 7; j++) {
        const int rr = row + i - 3, cc = col + j - 3;
        if (rr < 0 || rr >= IMG || cc < 0 || cc >= IMG) continue;
        for (int k = 0; k < 3; k++)
          c[k] = fmaf(__bfloat162float(x[((size_t)rr * IMG + cc) * CH + lane + 32 * k]), __bfloat162float(dw[(i * 7 + j) * CH + lane + 32 * k]), c[k]);
      }
    float mean = (c[0] + c[1] + c[2]) * (1.0f / 96.0f);
    for (int o = 16; o; o >>= 1) mean += __shfl_xor_sync(0xffffffffu, mean, o);
    float var = 0.f;
    for (int k = 0; k < 3; k++) { c[k] -= mean; var = fmaf(c[k] * (1.0f / 96.0f), c[k], var); }
    for (int o = 16; o; o >>= 1) var += __shfl_xor_sync(0xffffffffu, var, o);
    const float rs = 1.0f / sqrtf(var + 1e-5f);
    __syncwarp();
    for (int k = 0; k < 3; k++) buf[lane + 32 * k] = c[k] * rs;
    __syncwarp();
    for (int n = lane; n < 4 * CH; n += 32) {
      float y = 0.f;
      for (int k = 0; k < CH; k++) y = fmaf(buf[k], __bfloat162float(w1[k * 4 * CH + n]), y);
      buf[CH + n] = 0.5f * y * (1.0f + tanhf(0.7978845608f * (y + 0.044715f * y * y * y)));
    }
    __syncwarp();
    for (int n = lane; n < CH; n += 32) {
      float o = 0.f;
      for (int k = 0; k < 4 * CH; k++) o = fmaf(buf[CH + k], __bfloat162float(w2[k * CH + n]), o);
      const size_t idx = ((size_t)row * IMG + col) * CH + n;
      out[idx] = __float2bfloat16(__bfloat162float(x[idx]) + o);
    }
  }
}

__device__ __forceinline__ void x_load(const MlpCtx& m, uint32_t (&x)[24]) {
#pragma unroll
  for (int k = 0; k < 6; k++)
    asm volatile("ld.shared.v4.b32 {%0,%1,%2,%3}, [%4];"
                 : "=r"(x[4 * k]), "=r"(x[4 * k + 1]), "=r"(x[4 * k + 2]), "=r"(x[4 * k + 3])
                 : "r"(m.xaddr + (k / 3) * 384 + (k % 3) * 64)
                 : "memory");
}
template <int LO, int HI>
__device__ __forceinline__ void epilogue(const MlpCtx& m, const uint32_t (&d)[24], uint32_t (&x)[24]) {
#pragma unroll
  for (int k = LO; k < HI; k++) {
    const int r = k / 3, q = k % 3;
    uint32_t* y = &x[4 * k];
#pragma unroll
    for (int j = 0; j < 4; j++) {
      uint32_t v = d[2 * (4 * q + j) + r];
      float lo, hi;
      asm("{\n.reg .b16 l, h;\nmov.b32 {l, h}, %2;\ncvt.f32.f16 %0, l;\ncvt.f32.f16 %1, h;\n}\n" : "=f"(lo), "=f"(hi) : "r"(v));
      asm("fma.rn.bf16x2 %0, %1, %2, %0;" : "+r"(y[j]) : "r"(pack_bf16(lo, hi)), "r"(m.unscale));
    }
    asm volatile("st.shared.v4.b32 [%0], {%1,%2,%3,%4};" ::"r"(m.xaddr + r * 384 + q * 64), "r"(y[0]), "r"(y[1]), "r"(y[2]), "r"(y[3])
                 : "memory");
  }
}
__device__ __forceinline__ void out_store(const MlpCtx& m, int i) {
  asm volatile("fence.proxy.async.shared::cta;" ::: "memory");
  __syncwarp();
  if (elect_one()) {
    const uint32_t src = m.sb + OFF_XRES + m.wg * 12288 + m.warp * 1536;
    uint8_t* dst = m.optr + (size_t)i * (8 * IMG * CH * 2);
    asm volatile("cp.async.bulk.global.shared::cta.bulk_group [%0], [%1], 1536;" ::"l"(dst), "r"(src) : "memory");
    asm volatile("cp.async.bulk.global.shared::cta.bulk_group [%0], [%1], 1536;" ::"l"(dst + IMG * CH * 2), "r"(src + 6144) : "memory");
    asm volatile("cp.async.bulk.commit_group;" ::: "memory");
  }
}

#define FSET 3
template <int J> constexpr bool goes_first = J == FSET || J == ((FSET + 1) & 3);
template <int J> __device__ __forceinline__ void tok_wait() {
  if (goes_first<J>) NB_SYNC(NB_CLOSE, 256);
  else NB_SYNC(NB_SEC + (J & 1), 256);
}
template <int J, bool PROD = true> __device__ __forceinline__ void tok_next() {
  if (goes_first<J>) NB_ARRIVE(NB_SEC + (J & 1), 256);
  if (J == 0 && PROD) NB_ARRIVE(NB_PROD, 160);
}
__device__ __forceinline__ void tok_pass() { NB_ARRIVE(NB_OPEN, 416); }
template <int J> __device__ __forceinline__ void tok_idle() { tok_wait<J>(); tok_next<J, false>(); tok_pass(); }

constexpr uint64_t CHK = 1152;

__device__ __forceinline__ float warp_sumsq(const uint32_t (&q)[4]) {
  const uint32_t t = bf_add(bf_add(q[0], q[1]), bf_add(q[2], q[3]));
  float f = bf_lo(t) + bf_hi(t);
#pragma unroll
  for (int o = 16; o; o >>= 1) f += __shfl_xor_sync(0xffffffffu, f, o);
  return f;
}
__device__ __forceinline__ int norm_exp(float f) { return (((int)(__float_as_uint(f * 1.5f) >> 23) - 127) >> 1) + 1; }
__device__ __forceinline__ int scale_exp(int e1, int e2) { return min(11 - e1 - e2, 14 - e2); }

__device__ __forceinline__ void convert_tile(int t, int k, const uint4* w1, const uint4* w2, uint32_t st, Scratch* scr) {
  const int lane = threadIdx.x & 31, k7 = lane & 7;
  const int j = t / 6, ks = t % 6, e = ks % 3, t4 = k7 >> 1;
  const uint4* src = t < 24 ? w1 + ((e < 2 ? 64 * (ks / 3) + 8 * t4 + 4 * e : 32 + 16 * (ks / 3) + 4 * t4) + (k7 & 1)) * 48 + j * 12 + (lane >> 3)
                            : w2 + (t - 24) * 192 + (lane >> 2) * 12 + (lane & 3);
  src += (k / 3) * 96 + (k % 3) * 4;
  if (k >= 6) src = (k == 6 ? w1 : w2) + lane * 145;
  const uint4 v = __ldg(src);
  const uint32_t w[4] = {v.x, v.y, v.z, v.w};
  const uint32_t q[4] = {bf_mul(v.x, v.x), bf_mul(v.y, v.y), bf_mul(v.z, v.z), bf_mul(v.w, v.w)};
  asm volatile("st.shared.f32 [%0], %1;" ::"r"(st + 3088 + 4 * k), "f"(warp_sumsq(q)) : "memory");
  NB_SYNC(NB_PREP, 256);
  uint32_t a[4], b[4], o[4];
  lds128(a, st + 3088);
  lds128(b, st + 3104);
  const int s = max(-64, min(64, scale_exp(norm_exp(144.f * __uint_as_float(b[2])), norm_exp(144.f * __uint_as_float(b[3]))) - 1));
  const uint32_t dst = st + k7 * 16 + (lane >> 3) * 256 + (k / 3) * 128 + (k % 3) * 1024;
  if (k >= 6) {
    const float f = ((__uint_as_float(a[0]) + __uint_as_float(a[1])) + (__uint_as_float(a[2]) + __uint_as_float(a[3]))) +
                    (__uint_as_float(b[0]) + __uint_as_float(b[1]));
    asm volatile("st.shared.v2.b32 [%0], {%1,%2};" ::"r"(st + 3072), "r"(__float_as_uint(f)), "r"(s) : "memory");
  } else if (t < 24) {
#pragma unroll
    for (int i = 0; i < 4; i++) o[i] = pack_f16(bf_lo(w[i]), bf_hi(w[i]));
    asm volatile("st.shared.v4.b32 [%0], {%1,%2,%3,%4};" ::"r"(dst), "r"(o[0]), "r"(o[1]), "r"(o[2]), "r"(o[3]) : "memory");
  } else {
    constexpr float F = 0.5f / GELU_A, FHI = 1.515625f;
    const float p2 = __uint_as_float((uint32_t)(127 + s - 56) << 23);
    const uint32_t hi = pack_bf16(FHI * 0x1p-56f, FHI * 0x1p-56f), lo = pack_bf16((F - FHI) * 0x1p-56f, (F - FHI) * 0x1p-56f);
    const uint32_t pw = pack_bf16(p2, p2);
#pragma unroll
    for (int i = 0; i < 4; i++) {
      const uint32_t ws = bf_mul(w[i], pw), u = bf_fma(ws, hi, bf_mul(ws, lo));
      o[i] = (u & 0x7fff7fffu) * 7u + u;
    }
    asm volatile("stmatrix.sync.aligned.m8n8.x4.shared.b16 [%0], {%1,%2,%3,%4};" ::"r"(dst), "r"(o[0]), "r"(o[1]), "r"(o[2]), "r"(o[3])
                 : "memory");
  }
  asm volatile("fence.proxy.async.shared::cta;" ::: "memory");
  NB_SYNC(NB_PREP, 256);
  TS(4);
  if (k == 0 && elect_one()) {
    asm volatile("cp.async.bulk.global.shared::cta.bulk_group [%0], [%1], 3072;" ::"l"(scr->w + t * 192), "r"(st) : "memory");
    asm volatile("cp.async.bulk.global.shared::cta.bulk_group [%0], [%1], 16;" ::"l"(scr->nrm + t), "r"(st + 3072) : "memory");
    asm volatile("cp.async.bulk.commit_group;" ::: "memory");
    asm volatile("cp.async.bulk.wait_group 0;" ::: "memory");
    asm volatile("red.relaxed.gpu.global.add.u32 [%0], 1;" ::"l"(&scr->done) : "memory");
  }
  TS(5);
}

__device__ __forceinline__ uint32_t mlp_role(const MlpCtx& m0) {
  MlpCtx m = m0;
  uint32_t bad = 0;
  asm volatile("barrier.cluster.wait.aligned;" ::: "memory");
  if ((m.sb & 0x3FFFF) != 1024) bad = 0xffffu;
  constexpr uint64_t dW1 = (uint64_t)((1024 + OFF_W1) >> 4) | ((uint64_t)8 << 16) | ((uint64_t)16 << 32);
  constexpr uint64_t dW2 = dW1 + (OFF_W2 >> 4);
  TS(6);
  uint32_t A1[24], g[24], d[24], cn[24], D2[24];
  float st[8];
  if (m.wg & m.rank) tok_idle<3>();
  else if (m.wg) tok_idle<0>();
  else if (m.rank) tok_idle<1>();
  ln_wait(m, 0);
  ln_load(m, cn);
  ln_sums(cn, st);
  ln_shfl(st, 1);
  ln_release(m);
  ln_fold(st);
  ln_shfl(st, 2);
  ln_stats(st, bad, 1);
  ln_apply(A1, cn, st);
  {
    const int lane = threadIdx.x & 31;
    TS(2);
    mbar_wait(m.sb + BAR_W, 0);
    TS(3);
    float n1, n2;
    int s;
    asm volatile("ld.shared.b32 %0, [%1];" : "=r"(s) : "r"(m.sb + OFF_NRM + 4) : "memory");
    asm volatile("ld.shared.f32 %0, [%1];" : "=f"(n1) : "r"(m.sb + OFF_NRM + 16 * min(lane, 23)) : "memory");
    asm volatile("ld.shared.f32 %0, [%1];" : "=f"(n2) : "r"(m.sb + OFF_NRM + 384 + 16 * min(lane, 23)) : "memory");
    if (lane >= 24) n1 = n2 = 0.f;
#pragma unroll
    for (int o = 16; o; o >>= 1) {
      n1 += __shfl_xor_sync(0xffffffffu, n1, o);
      n2 += __shfl_xor_sync(0xffffffffu, n2, o);
    }
    const int e1 = norm_exp(n1), e2 = norm_exp(n2), smax = scale_exp(e1, e2);
    if (e1 > 12 || e1 < -5 || e2 > 50 || e2 < -50 || s > smax || s < smax - 5) bad = 0xffffu;
    m.unscale = __shfl_sync(0xffffffffu, ((uint32_t)(127 - s) << 7) * 0x10001u, 0);
  }
  TS(7);
  if (m.wg & m.rank) tok_idle<0>();
  if (m.wg) tok_idle<1>();
  {
    uint32_t d0[24];
    WG_FENCE();
    tok_wait<2>();
    tok_next<2>();
    gemm6<true, 192>(d0, A1, dW1);
    tok_pass(); PIN();
    WG_WAIT0(); rfence(d0);
    WG_FENCE();
    tok_wait<3>();
    tok_next<3>();
    gemm6<true, 192>(d, A1, dW1 + CHK);
    tok_pass(); PIN();
    gelu<0, 24>(g, d0);
    PIN();
    mbar_wait(m.sb + BAR_W + 8, 0);
    ln_wait(m, 1);
    WG_WAIT0(); rfence(d);
  }
#define G2(INIT, a, j)                      \
  WG_FENCE();                               \
  tok_wait<j>();                            \
  gemm6<INIT, 192>(D2, a, dW2 + (j) * CHK); \
  tok_next<j>(); PIN();                     \
  TL(ltb, (j) * 5 + 1);
#define G1(dst, j, P)                       \
  TL(ltb, ((j) ^ 2) * 5 + 2);               \
  P(); WG_WAIT0(); rfence(D2);              \
  WG_FENCE();                               \
  gemm6<true, 192>(dst, A1, dW1 + (j) * CHK); \
  tok_pass(); P();                          \
  TL(ltb, ((j) ^ 2) * 5 + 3);
#define ROUND_END(dst, j)                   \
  TL(ltb, (j) * 5 + 4);                     \
  PIN(); WG_WAIT0(); rfence(dst);
#define GA 9
#define GB 11
#define GC 13
#define GD 11
#pragma unroll 1
  for (int i = 0;; i++) {
    uint32_t g1[24], d2[24], g2[24], d3[24], g3[24], d0[24];
    ln_load(m, cn);
    PIN();
    G2(true, g, 0)
    gelu<0, GA>(g1, d);
    G1(d2, 2, PIN)
    ln_sums(cn, st);
    gelu<GA, 24>(g1, d);
    PIN();
    ln_shfl(st, 1);
    ROUND_END(d2, 0)

    G2(false, g1, 1)
    ln_fold(st);
    gelu<0, GB>(g2, d2);
    PIN();
    ln_shfl(st, 2);
    G1(d3, 3, PIN)
    ln_stats(st, bad, 2u << i);
    gelu<GB, 24>(g2, d2);
    ROUND_END(d3, 1)

    if (i == 15) {
      G2(false, g2, 2)
      tok_pass();
      gelu<0, 24>(g3, d3);
      PIN();
      x_load(m, cn);
      ROUND_END(D2, 2)
      G2(false, g3, 3)
      tok_pass();
      WG_WAIT0(); rfence(D2);
      epilogue<0, 6>(m, D2, cn);
      break;
    }
    G2(false, g2, 2)
    ln_apply(A1, cn, st);
    PIN();
    gelu<0, GC>(g3, d3);
    G1(d0, 0, PIN)
    gelu<GC, 24>(g3, d3);
    PIN();
    x_load(m, cn);
    ROUND_END(d0, 2)

    G2(false, g3, 3)
    gelu<0, GD>(g, d0);
    G1(d, 1, PIN)
    epilogue<0, 6>(m, D2, cn);
    gelu<GD, 24>(g, d0);
    PIN();
    asm volatile("fence.proxy.async.shared::cta;" ::: "memory");
    ROUND_END(d, 3)
    TLDUMP(m.warp == 0 && (i >> 1) == LTRACE, m.sb + OFF_LT + m.wg * 160 + (i & 1) * 80, 20)
  }
  out_store(m, 15);
  if (m.wg == 0) { tok_idle<0>(); tok_idle<1>(); }
  asm volatile("cp.async.bulk.wait_group.read 0;" ::: "memory");
  return __reduce_or_sync(0xffffffffu, bad & 0xffffu);
}

struct ConvCtx {
  uint32_t sb;
  uint32_t a0, a_c;
  uint32_t peer_off;
  int rank, v, c0, r0, zero;
  const CUtensorMap* tm;
  const uint8_t* xsrc;
  uint8_t* optr;
};

__device__ __forceinline__ void raw_refill(const ConvCtx& c, int s) {
  if (s + 4 < NSTEP && elect_one())
    tma_raw(c.sb + OFF_RAW + (s & 3) * RAW_BYTES, c.tm, c.rank, c.c0 / 2 - 2, c.r0 - 3 + 2 * (s + 4), c.sb + BAR_RAW + 8 * (s & 3));
}
__device__ __forceinline__ void step_ready(const ConvCtx& c, int s) {
  const int nx = (s + 1) & 3, par = ((s + 1) >> 2) & 1;
  if (s + 1 < NSTEP) mbar_wait(c.sb + BAR_RAW + 8 * nx, par);
  if (s >= 7 && s < NSTEP) mbar_wait(c.sb + BAR_CEMPTY + 8 * (2 * (nx & 1) + (nx >> 1)), par);
}

__device__ __forceinline__ void c_release(const ConvCtx& c, uint32_t w) {
  const uint32_t e = c.sb + BAR_CEMPTY + 8 * (2 * c.rank + w);
  asm volatile(
      "{\n.reg .pred p;\nelect.sync _|p, 0xffffffff;\n"
      "@p mbarrier.arrive.expect_tx.shared::cta.b64 _, [%0], %3;\n"
      "@p mbarrier.arrive.shared::cluster.b64 _, [%1], 4;\n"
      "@p mbarrier.arrive.shared::cluster.b64 _, [%2], 4;\n}\n" ::"r"(c.sb + BAR_CFULL + 8 * w),
      "r"(e), "r"(e + c.peer_off), "n"(CTX)
      : "memory");
}

__device__ __forceinline__ void prod_rows(const ConvCtx& c) {
#pragma unroll 1
  for (int s = 0; s < NROUND + SIGMA + c.rank; s++) {
    const int r = s - SIGMA - c.rank;
    const int u = (r & 1) ? (r >> 1) - 1 : (r >> 1) + 2;
    step_ready(c, s);
    if (u >= ((r & 1) ? 0 : 4) && u < 32) mbar_wait(c.sb + ((r & 1) ? BAR_XFULL : BAR_CFULL) + 8 * (u & 1), (u >> 1) & 1);
    if (s < SIGMA) NB_SYNC(NB_PLAN, 160);
    else NB_SYNC(NB_OPEN, 416);
    if (r == 3) TC(1);
    if (r == 55) TC(2);
    if (r >= -1 && r < 7) TS(7 + r);
    raw_refill(c, s);
  }
}
__device__ __forceinline__ void prod_tiles(const ConvCtx& c) {
  asm volatile("barrier.cluster.wait.aligned;" ::: "memory");
#pragma unroll 1
  for (int n = 1; n < 33; n++) {
    const uint32_t w = (n + 1) & 1;
    const uint32_t buf = c.sb + OFF_XRES + w * 12288;
    NB_SYNC(NB_PROD, 160);
    if (n < 29) c_release(c, w);
    if (n >= 3) {
      uint8_t* dst = c.optr + (size_t)(n - 3) * (4 * IMG * CH * 2);
      if (elect_one()) {
        asm volatile("cp.async.bulk.global.shared::cta.bulk_group [%0], [%1], 6144;" ::"l"(dst), "r"(buf) : "memory");
        asm volatile("cp.async.bulk.global.shared::cta.bulk_group [%0], [%1], 6144;" ::"l"(dst + IMG * CH * 2), "r"(buf + 6144) : "memory");
        asm volatile("cp.async.bulk.commit_group;" ::: "memory");
        asm volatile("cp.async.bulk.wait_group.read 0;" ::: "memory");
      }
      __syncwarp();
    }
    {
      const uint8_t* src = c.xsrc + (size_t)(n - 1) * (4 * IMG * CH * 2);
      if (elect_one()) {
        mbar_expect(c.sb + BAR_XFULL + 8 * w, 12288);
        bulk_load_last(buf, src, 6144, c.sb + BAR_XFULL + 8 * w);
        bulk_load_last(buf + 6144, src + IMG * CH * 2, 6144, c.sb + BAR_XFULL + 8 * w);
      }
    }
  }
  asm volatile("cp.async.bulk.wait_group 0;" ::: "memory");
}

__device__ __forceinline__ void conv_ld8(uint32_t a0, uint32_t (&r)[6][6]) {
  const uint32_t a2 = a0 ^ (16 | ((a0 >> 2) & 32));
  const uint32_t a[3] = {a0, (a0 & 64) ? a2 : a0, a2};
#pragma unroll
  for (int j = 0; j < 6; j++)
    asm volatile("ld.shared.v4.b32 {%0,%1,%2,%3}, [%4];"
                 : "=r"(r[j][0]), "=r"(r[j][1]), "=r"(r[j][2]), "=r"(r[j][3])
                 : "r"(a[j >> 1] + (j >> 1) * 64 + (j & 1) * RAW_PA)
                 : "memory");
}
__device__ __forceinline__ void conv_ld4(uint32_t a0, uint32_t stage, int v, uint32_t (&r)[6][6]) {
  const uint32_t ab = ((a0 >> 1) & ~31u) + (stage / 2 + 2 * RAW_PA + 8 * v);
#pragma unroll
  for (int j = 0; j < 6; j++) {
    uint32_t a = ab + (j >> 1) * 32;
    asm volatile("ld.shared.v2.b32 {%0,%1}, [%2];" : "=r"(r[j][4]), "=r"(r[j][5]) : "r"(a + (j & 1) * RAW_PB) : "memory");
  }
}
template <int LO, int HI>
__device__ __forceinline__ void conv_frags(uint32_t zero, const uint32_t (&r)[6][6], uint32_t (&A)[12][4]) {
#pragma unroll
  for (int ch = LO; ch < HI; ch++) {
    const uint32_t sel = (ch & 1) ? 0x7632 : 0x5410;
    A[ch][0] = __byte_perm(r[0][ch >> 1], r[1][ch >> 1], sel);
    A[ch][1] = __byte_perm(r[2][ch >> 1], r[3][ch >> 1], sel);
    A[ch][2] = A[ch][1] ^ zero;
    A[ch][3] = __byte_perm(r[4][ch >> 1], r[5][ch >> 1], sel);
    rfence(A[ch]);
  }
}
__device__ __forceinline__ void hmma_acc(uint32_t (&v)[4], const uint32_t (&a)[4], const uint32_t* b) {
  asm volatile("mma.sync.aligned.m16n8k16.row.col.f32.bf16.bf16.f32 {%0,%1,%2,%3}, {%4,%5,%6,%7}, {%8,%9}, {%0,%1,%2,%3};"
               : "+r"(v[0]), "+r"(v[1]), "+r"(v[2]), "+r"(v[3])
               : "r"(a[0]), "r"(a[1]), "r"(a[2]), "r"(a[3]), "r"(b[0]), "r"(b[1]));
}
__device__ __forceinline__ void hmma_new(uint32_t (&a)[4], const uint32_t* b) {
  asm volatile("mma.sync.aligned.m16n8k16.row.col.f32.bf16.bf16.f32 {%0,%1,%2,%3}, {%0,%1,%2,%3}, {%4,%5}, {%6,%6,%6,%6};"
               : "+r"(a[0]), "+r"(a[1]), "+r"(a[2]), "+r"(a[3])
               : "r"(b[0]), "r"(b[1]), "f"(0.f));
}

#define EARLY 5
template <int S2, bool GATED>
__device__ __forceinline__ void conv_step(const ConvCtx& c, int s, uint32_t (&K)[12], uint32_t (&V)[12][4], const uint32_t (&B)[12][4],
                                          uint32_t (&A)[12][4]) {
  const int nx = ((s + 1) & 2) | (S2 ^ 1);
  uint32_t r[6][6];
  const uint32_t a0 = c.a0 + nx * RAW_BYTES;
  TL(ltb, 0);
  if (!GATED) TS(6 + s);
  if (GATED) NB_SYNC(NB_OPEN, 416);
  else NB_SYNC(NB_PLAN, 160);
  conv_ld4(a0, c.sb + OFF_RAW + nx * RAW_BYTES, c.v, r);
  if (GATED) PIN();
  TL(ltb, 1);
#pragma unroll
  for (int ch = 0; ch < 12; ch++) hmma_acc(V[11 - ch], A[11 - ch], &B[11 - ch][2]);
#pragma unroll
  for (int ch = 0; ch < 12 - EARLY; ch++) hmma_new(A[ch], &B[ch][0]);
  const uint32_t zero = GATED ? c.zero & clock_pin() : c.zero;
  if (GATED) NB_ARRIVE(NB_CLOSE, 256);
#pragma unroll
  for (int ch = 12 - EARLY; ch < 12; ch++) hmma_new(A[ch], &B[ch][0]);
  if (GATED) PIN();
  TL(ltb, 2);
  const uint32_t off = ((S2 ^ 1) == c.rank) ? 0u : c.peer_off;
  const uint32_t dst = c.a_c + (GATED || s >= 3 ? off + (nx >> 1) * C_BYTES : OFF_XRES + 12288 - OFF_C);
  const uint32_t bar = c.sb + (GATED || s >= 3 ? off + BAR_CFULL + 8 * (nx >> 1) : BAR_W + 56);
#pragma unroll
  for (int q = 0; q < 12; q++) {
    const int ch = q & ~1, h = 2 * (q & 1);
    asm("add.rn.f16x2 %0, %0, %1;" : "+r"(K[q]) : "r"(pack_f16(__uint_as_float(V[ch][h + 1]), __uint_as_float(V[ch + 1][h]))));
  }
  if ((S2 ^ 1) == c.rank) {
#pragma unroll
    for (int q = 0; q < 3; q++)
      asm volatile("st.shared.v4.b32 [%0], {%1,%2,%3,%4};" ::"r"(dst + q * 2048), "r"(K[4 * q]), "r"(K[4 * q + 1]), "r"(K[4 * q + 2]), "r"(K[4 * q + 3])
                   : "memory");
    asm volatile("{\n.reg .pred p;\nelect.sync _|p, 0xffffffff;\n@p mbarrier.arrive.shared::cta.b64 _, [%0];\n}\n" ::"r"(bar) : "memory");
  } else {
#pragma unroll
  for (int q = 0; q < 3; q++)
    asm volatile("st.async.weak.shared::cluster.mbarrier::complete_tx::bytes.v4.b32 [%0], {%1,%2,%3,%4}, [%5];" ::"r"(dst + q * 2048),
                 "r"(K[4 * q]), "r"(K[4 * q + 1]), "r"(K[4 * q + 2]), "r"(K[4 * q + 3]), "r"(bar)
                 : "memory");
  }
  PIN();
#pragma unroll
  for (int q = 0; q < 12; q++) {
    const int ch = q & ~1, h = 2 * (q & 1);
    K[q] = pack_f16(__uint_as_float(V[ch][h]), __uint_as_float(V[ch + 1][h + 1]));
  }
  rfence(K);
  conv_frags<8, 12>(zero, r, V);
  PIN();
  conv_ld8(a0, r);
  conv_frags<0, 8>(zero, r, V);
  PIN();
  TL(ltb, 4);
  TLDUMP(c.v == 0 && lr >= 0 && lr < 10, c.sb + OFF_LT + 320 + lr * 20, 5)
}

__device__ __forceinline__ void conv_role(ConvCtx c) {
  const int lane = laneid(), g = lane >> 2, t = lane & 3;
  const int u = (t >> 1) * 19 + 2 * (g + (t & 1));
  c.a0 = c.sb + OFF_RAW + u * 64 + ((c.v ^ (u >> 1)) & 3) * 16;
  c.a_c = c.sb + OFF_C + 6144 * c.rank + 512 * c.v + ((lane + 2 * c.v) & 31) * 16;
  uint32_t B[12][4];
  {
    const int dc = (g >> 1) & 1, ro = g >> 2, rk = t >> 1;
    const int i0 = 4 * (g & 1) + rk - ro, j0 = 4 * (t & 1) - dc;
    const uint32_t base = c.sb + OFF_XRES + (i0 * 7 + j0) * 192;
    TS(2);
    asm volatile("barrier.cluster.wait.aligned;" ::: "memory");
    mbar_wait(c.sb + BAR_W + 48, 0);
    TS(3);
#pragma unroll
    for (int b = 0; b < 2; b++) {
      uint32_t w[4][6];
#pragma unroll
      for (int k = 0; k < 4; k++) {
        const int ok = (unsigned)(i0 + 2 * b) < 7u && (unsigned)(j0 + k) < 7u;
#pragma unroll
        for (int q = 0; q < 6; q++) w[k][q] = 0;
        asm volatile(
            "{\n.reg .pred p;\nsetp.ne.s32 p, %8, 0;\n@p ld.shared.v4.b32 {%0,%1,%2,%3}, [%6];\n@p ld.shared.v2.b32 {%4,%5}, [%7];\n}\n"
            : "+r"(w[k][0]), "+r"(w[k][1]), "+r"(w[k][2]), "+r"(w[k][3]), "+r"(w[k][4]), "+r"(w[k][5])
            : "r"(base + (b * 14 + k) * 192 + 128 * c.rank + 16 * c.v), "r"(base + (b * 14 + k) * 192 + 64 + 32 * c.rank + 8 * c.v), "r"(ok)
            : "memory");
      }
#pragma unroll
      for (int q = 0; q < 6; q++) {
        B[2 * q][2 * b] = __byte_perm(w[0][q], w[1][q], 0x5410);
        B[2 * q][2 * b + 1] = __byte_perm(w[2][q], w[3][q], 0x5410);
        B[2 * q + 1][2 * b] = __shfl_xor_sync(0xffffffffu, __byte_perm(w[0][q], w[1][q], 0x7632), 4);
        B[2 * q + 1][2 * b + 1] = __shfl_xor_sync(0xffffffffu, __byte_perm(w[2][q], w[3][q], 0x7632), 4);
      }
    }
  }
  TS(4);
  uint32_t K1[12], K2[12], V[12][4];
#pragma unroll
  for (int ch = 0; ch < 12; ch++) {
    K1[ch] = K2[ch] = 0;
#pragma unroll
    for (int k = 0; k < 4; k++) V[ch][k] = 0;
  }
  uint32_t A[12][4], r[6][6];
  mbar_wait(c.sb + BAR_RAW, 0);
  TS(5);
  conv_ld8(c.a0, r);
  conv_ld4(c.a0, c.sb + OFF_RAW, c.v, r);
  conv_frags<0, 12>(c.zero, r, A);
  PIN();
  NB_ARRIVE(NB_CLOSE, 256);
#pragma unroll 1
  for (int s = 0; s < SIGMA; s += 2) {
    conv_step<0, false>(c, s, K1, V, B, A);
    conv_step<1, false>(c, s + 1, K2, A, B, V);
  }
#pragma unroll 1
  for (int s = SIGMA;; s += 2) {
    conv_step<0, true>(c, s, K1, V, B, A);
    if (s == NSTEP - 1) break;
    conv_step<1, true>(c, s + 1, K2, A, B, V);
  }
#pragma unroll 1
  for (int r = NSTEP - SIGMA - c.rank; r < NROUND - 1; r++) {
    NB_SYNC(NB_OPEN, 416);
    NB_ARRIVE(NB_CLOSE, 256);
  }
  NB_SYNC(NB_OPEN, 416);
}

struct TMaps { CUtensorMap m[2]; };
__device__ __forceinline__ Scratch* scr_param() {
  extern __shared__ __align__(1024) uint8_t smem[];
  return *reinterpret_cast<Scratch* volatile*>(smem + OFF_LT + 592);
}

__global__ void __cluster_dims__(2, 1, 1) __launch_bounds__(512, 1)
convnext_kernel(const __grid_constant__ TMaps tms, const __nv_bfloat16* __restrict__ x, const __nv_bfloat16* __restrict__ dw,
                const __nv_bfloat16* __restrict__ w1, const __nv_bfloat16* __restrict__ w2, __nv_bfloat16* __restrict__ out,
                Scratch* scr, int zero) {
  extern __shared__ __align__(1024) uint8_t smem[];
  const uint32_t sb = (uint32_t)__cvta_generic_to_shared(smem);
  const int tid = threadIdx.x, lane = tid & 31;
  const int wid = __shfl_sync(0xffffffffu, tid >> 5, 0);
  const int rank = blockIdx.x & 1, cl = blockIdx.x >> 1;
  const int c0 = (cl & 15) * 32, r0 = (cl >> 4) * 128;
  const uint32_t peer_off = mapa(sb, rank ^ 1) - sb;

  TS(0);
  if (wid == 12 && elect_one()) {
    mbar_init(sb + BAR_W + 48, 1);
#pragma unroll
    for (int i = 0; i < 4; i++) mbar_init(sb + BAR_RAW + 8 * i, 1);
    asm volatile("fence.mbarrier_init.release.cluster;" ::: "memory");
    mbar_expect(sb + BAR_W + 48, 49 * CH * 2);
    bulk_load(sb + OFF_XRES, dw, 49 * CH * 2, sb + BAR_W + 48);
#pragma unroll
    for (int i = 0; i < E0; i++) tma_raw(sb + OFF_RAW + i * RAW_BYTES, tms.m, rank, c0 / 2 - 2, r0 - 3 + 2 * i, sb + BAR_RAW + 8 * i);
  }
  if (wid == 14 && elect_one()) {
    asm volatile("prefetch.tensormap [%0];" ::"l"(&tms.m[1]) : "memory");
#pragma unroll
    for (int i = 0; i < 3; i++) mbar_init(sb + BAR_W + 8 * i, 1);
    mbar_init(sb + BAR_W + 56, 100);
#pragma unroll
    for (int i = 0; i < 2; i++) mbar_init(sb + BAR_CFULL + 8 * i, CCNT);
#pragma unroll
    for (int i = 0; i < 4; i++) mbar_init(sb + BAR_CEMPTY + 8 * i, 4);
#pragma unroll
    for (int i = 0; i < 2; i++) mbar_init(sb + BAR_XFULL + 8 * i, 1);
#pragma unroll
    for (int i = 0; i < 2; i++) mbar_expect(sb + BAR_CFULL + 8 * i, CTX);
    asm volatile("fence.mbarrier_init.release.cluster;" ::: "memory");
  }
  __syncwarp();
  asm volatile("barrier.cluster.arrive.relaxed.aligned;" ::: "memory");

  TS(1);
  if (wid < 8) {
    if (blockIdx.x < 48) convert_tile(blockIdx.x, wid, reinterpret_cast<const uint4*>(w1), reinterpret_cast<const uint4*>(w2), sb, scr);
    MlpCtx m;
    m.sb = sb; m.wg = wid >> 2; m.warp = wid & 3; m.rank = rank; m.peer_off = peer_off; m.zero = zero;
    m.optr = reinterpret_cast<uint8_t*>(out) + ((size_t)(r0 + 4 * m.wg + 2 * rank) * IMG + c0 + 8 * m.warp) * (CH * 2);
    m.caddr = sb + OFF_C + m.wg * C_BYTES + (lane & 3) * 512 + ((m.warp * 8 + (lane >> 2) + 2 * (lane & 3)) & 31) * 16;
    m.xaddr = sb + OFF_XRES + m.wg * 12288 + m.warp * 1536 + ((lane >> 3) & 1) * 6144 + ((lane >> 4) * 4 + ((lane >> 2) & 1)) * 192 + (lane & 3) * 16;
    m.unscale = 0;
    asm volatile("setmaxnreg.inc.sync.aligned.u32 %0;" ::"n"(REG_MLP));
    const uint32_t bad = mlp_role(m);
    TC(3);
    if (bad) {
      asm volatile("cp.async.bulk.wait_group 0;" ::: "memory");
      mbar_wait(sb + BAR_W + 16, 0);
      __syncwarp();
      asm volatile("fence.proxy.async;" ::: "memory");
#pragma unroll 1
      for (int i = 0; i < 16; i++)
        if (bad >> i & 1)
          slow_tile(x, dw, w1, w2, out, r0 + 8 * i + 4 * m.wg + 2 * rank, c0 + 8 * m.warp,
                    reinterpret_cast<float*>(smem + OFF_RAW + wid * 2048));
    }
  } else {
    ConvCtx c;
    c.sb = sb; c.rank = rank; c.v = wid - 8; c.c0 = c0; c.r0 = r0; c.zero = zero; c.tm = tms.m;
    c.peer_off = peer_off;
    c.xsrc = reinterpret_cast<const uint8_t*>(x) + ((size_t)(r0 + 2 * rank) * IMG + c0) * (CH * 2);
    c.optr = reinterpret_cast<uint8_t*>(out) + ((size_t)(r0 + 2 * rank) * IMG + c0) * (CH * 2);
    if (wid < 12) {
      asm volatile("setmaxnreg.inc.sync.aligned.u32 %0;" ::"n"(REG_CONV));
      conv_role(c);
    } else {
      asm volatile("setmaxnreg.dec.sync.aligned.u32 24;");
      if (wid == 15) TC(0);
      if (wid == 12) {
        TS(2);
#pragma unroll 1
        for (int h = E0 - 4; h < 0; h++) raw_refill(c, h);
        TS(3);
        asm volatile("barrier.cluster.wait.aligned;" ::: "memory");
        prod_rows(c);
      } else if (wid == 14) {
#pragma unroll 1
        for (int n = 0; n < (1 << 20); n++) {
          unsigned v;
          __nanosleep(n ? PSL : PS0);
          asm volatile("ld.acquire.gpu.global.u32 %0, [%1];" : "=r"(v) : "l"(&scr->done) : "memory");
          if (__shfl_sync(0xffffffffu, v, 0) >= 48) break;
        }
        asm volatile("barrier.cluster.wait.aligned;" ::: "memory");
        asm volatile("fence.proxy.async.global;" ::: "memory");
        if (elect_one()) {
          mbar_expect(sb + BAR_W, 36864 + 768);
          mbar_expect(sb + BAR_W + 8, 110592);
          bulk_load(sb + OFF_NRM, scr->nrm, 768, sb + BAR_W);
          if (atomicAdd(&scr->seen, 1u) == gridDim.x - 1) { scr->done = 0; scr->seen = 0; }
        }
        __syncwarp();
#pragma unroll 1
        for (int i = 0; i < 8; i++) {
          if (elect_one()) bulk_load(sb + i * 18432, reinterpret_cast<const uint8_t*>(scr->w) + i * 18432, 18432, sb + BAR_W + (i < 2 ? 0 : 8));
          __nanosleep(PACE);
        }
      } else if (wid == 13) {
        prod_tiles(c);
        __syncwarp();
        if (elect_one()) asm volatile("mbarrier.arrive.shared::cta.b64 _, [%0];" ::"r"(sb + BAR_W + 16) : "memory");
      }
    }
  }
}

typedef CUresult (*EncodeFn)(CUtensorMap*, CUtensorMapDataType, cuuint32_t, void*, const cuuint64_t*, const cuuint64_t*,
                             const cuuint32_t*, const cuuint32_t*, CUtensorMapInterleave, CUtensorMapSwizzle,
                             CUtensorMapL2promotion, CUtensorMapFloatOOBfill);

}

extern "C" void kernel_launch(void* const* d_in, const int* in_sizes, int n_in, void* d_out, int out_size) {
  const __nv_bfloat16* x = (const __nv_bfloat16*)d_in[0];
  const __nv_bfloat16* dw = (const __nv_bfloat16*)d_in[1];
  const __nv_bfloat16* w1 = (const __nv_bfloat16*)d_in[2];
  const __nv_bfloat16* w2 = (const __nv_bfloat16*)d_in[3];
  __nv_bfloat16* out = (__nv_bfloat16*)d_out;

  static EncodeFn encode = nullptr;
  static Scratch* scr = nullptr;
  if (!encode) {
    cudaDriverEntryPointQueryResult st;
    void* fn = nullptr;
    cudaGetDriverEntryPoint("cuTensorMapEncodeTiled", &fn, cudaEnableDefault, &st);
    encode = (EncodeFn)fn;
    cudaGetSymbolAddress((void**)&scr, g_scratch);
    cudaFuncSetAttribute(convnext_kernel, cudaFuncAttributeMaxDynamicSharedMemorySize, SMEM_BYTES);
  }
  TMaps tm;
  cuuint64_t dims[4] = {CH, IMG / 2, IMG, 2};
  cuuint64_t strides[3] = {CH * 4, (cuuint64_t)IMG * CH * 2, CH * 2};
  cuuint32_t es[4] = {1, 1, 1, 1};
  for (int i = 0; i < 2; i++) {
    cuuint32_t box[4] = {i ? 16u : 32u, 19, 2, 1};
    encode(&tm.m[i], CU_TENSOR_MAP_DATA_TYPE_BFLOAT16, 4, (void*)x, dims, strides, box, es, CU_TENSOR_MAP_INTERLEAVE_NONE,
           i ? CU_TENSOR_MAP_SWIZZLE_NONE : CU_TENSOR_MAP_SWIZZLE_64B, PROMO, CU_TENSOR_MAP_FLOAT_OOB_FILL_NONE);
  }
  convnext_kernel<<<128, 512, SMEM_BYTES>>>(tm, x, dw, w1, w2, out, scr, 0);
}
```

```cpp
#include <cuda_runtime.h>
#include <cuda_bf16.h>
#include <cuda.h>
#include <stdint.h>

#define PROMO CU_TENSOR_MAP_L2_PROMOTION_L2_128B
#define CTX 6144
#define CCNT 5
#define PSL 100
#define PS0 1000
#define E0 1
#define PACE 100
namespace {

constexpr int IMG = 512, CH = 96;
constexpr int NSTEP = 67;
constexpr int SIGMA = 8;
constexpr int NROUND = 68;

constexpr uint32_t OFF_W1 = 0;
constexpr uint32_t OFF_W2 = 73728;
constexpr uint32_t OFF_RAW = 147456;
constexpr uint32_t RAW_PA = 2560, RAW_PB = 1280;
constexpr uint32_t RAW_BYTES = 2 * RAW_PA + 2 * RAW_PB;
constexpr uint32_t RAW_TX = 2 * 38 * 96;
constexpr uint32_t OFF_XRES = OFF_RAW + 4 * RAW_BYTES;
constexpr uint32_t OFF_C = OFF_XRES + 2 * 12288;
constexpr uint32_t C_BYTES = 12288;
constexpr uint32_t OFF_BAR = OFF_C + 2 * C_BYTES;
constexpr uint32_t BAR_RAW = OFF_BAR;
constexpr uint32_t BAR_CFULL = OFF_BAR + 32;
constexpr uint32_t BAR_CEMPTY = OFF_BAR + 48;
constexpr uint32_t BAR_XFULL = OFF_BAR + 80;
constexpr uint32_t BAR_W = OFF_BAR + 96;
constexpr uint32_t OFF_NRM = OFF_XRES + 9472;
constexpr uint32_t OFF_LT = OFF_BAR + 160;
constexpr uint32_t SMEM_BYTES = OFF_BAR + 160 + 600;

struct Scratch {
  uint4 w[2 * 73728 / 16];
  uint4 nrm[48];
  unsigned done, seen;
};
__device__ Scratch g_scratch;

constexpr float GELU_A = 0.32918364f;
constexpr uint32_t GELU_K2 = 0x40d940d9u;

constexpr int NB_CLOSE = 1, NB_SEC = 6  , NB_OPEN = 3, NB_PROD = 2, NB_PLAN = 4, NB_PREP = 5, NB_WG = 8  ;
#define REG_MLP 144
constexpr int REG_CONV = 488 - 2 * REG_MLP;

#define WG_FENCE() asm volatile("wgmma.fence.sync.aligned;" ::: "memory")
#define WG_COMMIT() asm volatile("wgmma.commit_group.sync.aligned;" ::: "memory")
#define WG_WAIT0() asm volatile("wgmma.wait_group.sync.aligned 0;" ::: "memory")
#define WG_WAIT1() asm volatile("wgmma.wait_group.sync.aligned 1;" ::: "memory")
#define PIN() asm volatile("pmevent 0;" ::: "memory")
#define NB_SYNC(id, n) asm volatile("bar.sync %0, %1;" ::"n"(id), "n"(n) : "memory")
#define NB_ARRIVE(id, n) asm volatile("bar.arrive %0, %1;" ::"n"(id), "n"(n) : "memory")

#define SCR (scr_param())
__device__ __forceinline__ Scratch* scr_param();
#define TS(idx)
#define TC(k)
#define TL(base, off)
#define TLDUMP(cond, base, n)

#define R24(c, d)                                                                                        \
  c(d[0]), c(d[1]), c(d[2]), c(d[3]), c(d[4]), c(d[5]), c(d[6]), c(d[7]), c(d[8]), c(d[9]), c(d[10]),    \
      c(d[11]), c(d[12]), c(d[13]), c(d[14]), c(d[15]), c(d[16]), c(d[17]), c(d[18]), c(d[19]), c(d[20]), \
      c(d[21]), c(d[22]), c(d[23])
#define WG_TXT(sd)                                                                             \
  "wgmma.mma_async.sync.aligned.m64n96k16.f16.f16.f16 "                                        \
  "{%0,%1,%2,%3,%4,%5,%6,%7,%8,%9,%10,%11,%12,%13,%14,%15,%16,%17,%18,%19,%20,%21,%22,%23}, " \
  "{%24,%25,%26,%27}, %28, " sd ", 1, 1, 1;\n"

__device__ __forceinline__ void wg_acc(uint32_t (&d)[24], const uint32_t* a, uint64_t db) {
  asm volatile(WG_TXT("1") : R24("+r", d) : "r"(a[0]), "r"(a[1]), "r"(a[2]), "r"(a[3]), "l"(db));
}
__device__ __forceinline__ void wg_init(uint32_t (&d)[24], const uint32_t* a, uint64_t db) {
  asm volatile(WG_TXT("0") : R24("=r", d) : "r"(a[0]), "r"(a[1]), "r"(a[2]), "r"(a[3]), "l"(db));
}
template <int N>
__device__ __forceinline__ void rfence(uint32_t (&d)[N]) {
#pragma unroll
  for (int i = 0; i < N; i++) asm volatile("" : "+r"(d[i])::"memory");
}
template <bool INIT, int KSTRIDE>
__device__ __forceinline__ void gemm6(uint32_t (&d)[24], const uint32_t (&a)[24], uint64_t db) {
#pragma unroll
  for (int k = 0; k < 6; k++) {
    if (INIT && k == 0) wg_init(d, &a[0], db);
    else wg_acc(d, &a[4 * k], db + k * KSTRIDE);
  }
  WG_COMMIT();
}

__device__ __forceinline__ void mbar_init(uint32_t bar, uint32_t cnt) {
  asm volatile("mbarrier.init.shared::cta.b64 [%0], %1;" ::"r"(bar), "r"(cnt) : "memory");
}
__device__ __forceinline__ void mbar_expect(uint32_t bar, uint32_t bytes) {
  asm volatile("mbarrier.arrive.expect_tx.shared::cta.b64 _, [%0], %1;" ::"r"(bar), "r"(bytes) : "memory");
}
__device__ __forceinline__ void mbar_arrive_cluster(uint32_t bar) {
  asm volatile("mbarrier.arrive.shared::cluster.b64 _, [%0];" ::"r"(bar) : "memory");
}
__device__ __forceinline__ bool mbar_try(uint32_t bar, uint32_t parity) {
  uint32_t ok;
  asm volatile(
      "{\n.reg .pred p;\nmbarrier.try_wait.parity.shared::cta.b64 p, [%1], %2;\nselp.u32 %0, 1, 0, p;\n}\n"
      : "=r"(ok)
      : "r"(bar), "r"(parity)
      : "memory");
  return ok;
}
__device__ __forceinline__ bool mbar_test(uint32_t bar, uint32_t parity) {
  uint32_t ok;
  asm volatile(
      "{\n.reg .pred p;\nmbarrier.test_wait.parity.shared::cta.b64 p, [%1], %2;\nselp.u32 %0, 1, 0, p;\n}\n"
      : "=r"(ok)
      : "r"(bar), "r"(parity)
      : "memory");
  return ok;
}
__device__ __forceinline__ void mbar_wait(uint32_t bar, uint32_t parity) {
  if (__builtin_expect(mbar_try(bar, parity), 1)) return;
#pragma unroll 1
  for (uint32_t n = 0; n < (1u << 16) && !mbar_try(bar, parity); n++) {}
}
__device__ __forceinline__ uint32_t mapa(uint32_t addr, uint32_t rank) {
  uint32_t r;
  asm("mapa.shared::cluster.u32 %0, %1, %2;" : "=r"(r) : "r"(addr), "r"(rank));
  return r;
}
__device__ __forceinline__ void tma_raw(uint32_t dst, const CUtensorMap* tm, int rank, int w2, int h, uint32_t bar) {
  mbar_expect(bar, RAW_TX);
#pragma unroll
  for (int k = 0; k < 4; k++) {
    const int e = k & 1;
    asm volatile(
        "cp.async.bulk.tensor.4d.shared::cluster.global.mbarrier::complete_tx::bytes [%0], [%1, {%2, %3, %4, %5}], [%6];"
        ::"r"(dst + (k < 2 ? e * RAW_PA : 2 * RAW_PA + e * RAW_PB)), "l"(tm + (k >> 1)), "r"(k < 2 ? 64 * rank : 32 + 16 * rank), "r"(w2 + e),
        "r"(h), "r"(1 - e), "r"(bar)
        : "memory");
  }
}
__device__ __forceinline__ void bulk_load(uint32_t dst, const void* src, uint32_t bytes, uint32_t bar) {
  asm volatile("cp.async.bulk.shared::cluster.global.mbarrier::complete_tx::bytes [%0], [%1], %2, [%3];" ::"r"(dst),
               "l"(src), "r"(bytes), "r"(bar)
               : "memory");
}
__device__ __forceinline__ void bulk_load_last(uint32_t dst, const void* src, uint32_t bytes, uint32_t bar) {
  asm volatile(
      "{\n.reg .b64 pol;\ncreatepolicy.fractional.L2::evict_first.b64 pol, 1.0;\n"
      "cp.async.bulk.shared::cluster.global.mbarrier::complete_tx::bytes.L2::cache_hint [%0], [%1], %2, [%3], pol;\n}\n" ::"r"(dst),
      "l"(src), "r"(bytes), "r"(bar)
      : "memory");
}
__device__ __forceinline__ uint32_t pack_bf16(float lo, float hi) {
  uint32_t r;
  asm("cvt.rn.bf16x2.f32 %0, %1, %2;" : "=r"(r) : "f"(hi), "f"(lo));
  return r;
}
__device__ __forceinline__ uint32_t pack_f16(float lo, float hi) {
  uint32_t r;
  asm("cvt.rn.f16x2.f32 %0, %1, %2;" : "=r"(r) : "f"(hi), "f"(lo));
  return r;
}
__device__ __forceinline__ float bf_lo(uint32_t v) { return __uint_as_float(v << 16); }
__device__ __forceinline__ float bf_hi(uint32_t v) { return __uint_as_float(v & 0xffff0000u); }
__device__ __forceinline__ uint32_t bf_add(uint32_t a, uint32_t b) {
  uint32_t r;
  asm("add.rn.bf16x2 %0, %1, %2;" : "=r"(r) : "r"(a), "r"(b));
  return r;
}
__device__ __forceinline__ uint32_t bf_mul(uint32_t a, uint32_t b) {
  uint32_t r;
  asm("mul.rn.bf16x2 %0, %1, %2;" : "=r"(r) : "r"(a), "r"(b));
  return r;
}
__device__ __forceinline__ uint32_t bf_fma(uint32_t a, uint32_t b, uint32_t c) {
  uint32_t r;
  asm("fma.rn.bf16x2 %0, %1, %2, %3;" : "=r"(r) : "r"(a), "r"(b), "r"(c));
  return r;
}

__device__ __forceinline__ uint32_t h_add(uint32_t a, uint32_t b) {
  uint32_t r;
  asm("add.rn.f16x2 %0, %1, %2;" : "=r"(r) : "r"(a), "r"(b));
  return r;
}
__device__ __forceinline__ uint32_t h_mul(uint32_t a, uint32_t b) {
  uint32_t r;
  asm("mul.rn.f16x2 %0, %1, %2;" : "=r"(r) : "r"(a), "r"(b));
  return r;
}
__device__ __forceinline__ uint32_t h_fma(uint32_t a, uint32_t b, uint32_t c) {
  uint32_t r;
  asm("fma.rn.f16x2 %0, %1, %2, %3;" : "=r"(r) : "r"(a), "r"(b), "r"(c));
  return r;
}
__device__ __forceinline__ float h_sum(uint32_t v) {
  float lo, hi;
  asm("{\n.reg .b16 l, h;\nmov.b32 {l, h}, %2;\ncvt.f32.f16 %0, l;\ncvt.f32.f16 %1, h;\n}\n" : "=f"(lo), "=f"(hi) : "r"(v));
  return lo + hi;
}
__device__ __forceinline__ void lds128(uint32_t (&v)[4], uint32_t a) {
  asm volatile("ld.shared.v4.b32 {%0,%1,%2,%3}, [%4];" : "=r"(v[0]), "=r"(v[1]), "=r"(v[2]), "=r"(v[3]) : "r"(a) : "memory");
}

template <int LO, int HI>
__device__ __forceinline__ void gelu(uint32_t (&o)[24], const uint32_t (&d)[24]) {
#pragma unroll
  for (int qq = LO; qq < HI; qq++) {
    const int q = (qq + 4) % 24;
    uint32_t t, u;
    asm("fma.rn.f16x2 %0, %1, %1, %2;" : "=r"(t) : "r"(d[q]), "r"(GELU_K2));
    asm("mul.rn.f16x2 %0, %1, %2;" : "=r"(u) : "r"(d[q]), "r"(t));
    asm("tanh.approx.f16x2 %0, %1;" : "=r"(t) : "r"(u));
    asm("fma.rn.f16x2 %0, %1, %2, %1;" : "=r"(o[q]) : "r"(d[q]), "r"(t));
  }
}

__device__ __forceinline__ uint32_t laneid() {
  uint32_t l;
  asm volatile("mov.u32 %0, %%laneid;" : "=r"(l));
  return l;
}

__device__ __forceinline__ bool elect_one() {
  uint32_t p;
  asm volatile("{\n.reg .pred p;\nelect.sync _|p, 0xffffffff;\nselp.u32 %0, 1, 0, p;\n}\n" : "=r"(p));
  return p;
}

__device__ __forceinline__ uint32_t clock_pin() {
  uint32_t t;
  asm volatile("mov.u32 %0, %%clock;" : "=r"(t)::"memory");
  return t;
}

struct MlpCtx {
  uint32_t sb;
  uint32_t caddr;
  uint32_t xaddr;
  uint32_t unscale;
  uint32_t peer_off;
  int wg, warp, rank, zero;
  uint8_t* optr;
};

__device__ __forceinline__ void ln_wait(const MlpCtx& m, int i) { mbar_wait(m.sb + BAR_CFULL + 8 * m.wg, i & 1); }
__device__ __forceinline__ void ln_load(const MlpCtx& m, uint32_t (&c)[24]) {
#pragma unroll
  for (int p = 0; p < 6; p++)
    asm volatile("ld.shared.v4.b32 {%0,%1,%2,%3}, [%4];"
                 : "=r"(c[4 * p]), "=r"(c[4 * p + 1]), "=r"(c[4 * p + 2]), "=r"(c[4 * p + 3])
                 : "r"(m.caddr + p * 2048)
                 : "memory");
}
__device__ __forceinline__ void ln_shfl(float (&st)[8], int mask) {
#pragma unroll
  for (int k = 0; k < 4; k++) st[4 + k] = __shfl_xor_sync(0xffffffffu, st[k], mask);
}
__device__ __forceinline__ void ln_fold(float (&st)[8]) {
#pragma unroll
  for (int k = 0; k < 4; k++) st[k] += st[4 + k];
}
__device__ __forceinline__ void ln_sums(const uint32_t (&c)[24], float (&st)[8]) {
#pragma unroll
  for (int r = 0; r < 2; r++) {
    uint32_t s0 = h_add(c[r], c[r + 2]), s1 = h_add(c[r + 4], c[r + 6]), s2 = h_add(c[r + 8], c[r + 10]);
    uint32_t s3 = h_add(c[r + 12], c[r + 14]), s4 = h_add(c[r + 16], c[r + 18]), s5 = h_add(c[r + 20], c[r + 22]);
    s0 = h_add(s0, s1); s2 = h_add(s2, s3); s4 = h_add(s4, s5);
    st[r] = h_sum(h_add(h_add(s0, s2), s4));
    uint32_t q0 = h_mul(c[r], c[r]), q1 = h_mul(c[r + 2], c[r + 2]);
#pragma unroll
    for (int p = 2; p < 12; p += 2) {
      q0 = h_fma(c[2 * p + r], c[2 * p + r], q0);
      q1 = h_fma(c[2 * p + 2 + r], c[2 * p + 2 + r], q1);
    }
    st[2 + r] = h_sum(h_add(q0, q1));
  }
}
__device__ __forceinline__ void ln_release(const MlpCtx& m) {
  const uint32_t e = m.sb + BAR_CEMPTY + 8 * (2 * m.rank + m.wg);
  asm volatile(
      "{\n.reg .pred p, q;\nelect.sync _|p, 0xffffffff;\nsetp.eq.and.s32 q, %3, 0, p;\n"
      "@q mbarrier.arrive.expect_tx.shared::cta.b64 _, [%0], %4;\n"
      "@p mbarrier.arrive.shared::cluster.b64 _, [%1];\n"
      "@p mbarrier.arrive.shared::cluster.b64 _, [%2];\n}\n" ::"r"(m.sb + BAR_CFULL + 8 * m.wg),
      "r"(e), "r"(e + m.peer_off), "r"(m.warp), "n"(CTX)
      : "memory");
}
__device__ __forceinline__ bool ln_stats(float (&st)[8]) {
  bool ok = true;
#pragma unroll
  for (int r = 0; r < 2; r++) {
    const float nm = (st[r] + st[4 + r]) * (-1.0f / 96.0f);
    const float e2 = fmaf(st[2 + r] + st[6 + r], 1.0f / 96.0f, 1e-5f);
    float rs;
    asm("rsqrt.approx.ftz.f32 %0, %1;" : "=f"(rs) : "f"(fmaf(-nm, nm, e2)));
    ok = ok && (rs * rs * e2 <= 17.0f) && (e2 >= 1.001e-5f);
    const float rr = rs * GELU_A, dd = rr * nm;
    st[r] = __uint_as_float(pack_f16(rr, rr));
    st[2 + r] = __uint_as_float(pack_f16(dd, dd));
  }
  return ok;
}
__device__ __forceinline__ void ln_restat(bool ok, const uint32_t (&c)[24], float (&st)[8], uint32_t& bad, uint32_t bit,
                                          uint32_t zero) {
  if (__builtin_expect(__any_sync(0xffffffffu, !ok), 0)) {
#pragma unroll
    for (int r = 0; r < 2; r++) {
      float nm = 0.f, var = 0.f;
#pragma unroll
      for (int p = 0; p < 12; p++) {
        nm += h_sum(c[2 * p + r] ^ zero);
        if (p % 3 == 2) { asm volatile("" : "+f"(nm)); PIN(); }
      }
      nm += __shfl_xor_sync(0xffffffffu, nm, 1);
      nm += __shfl_xor_sync(0xffffffffu, nm, 2);
      nm *= -1.0f / 96.0f;
#pragma unroll
      for (int p = 0; p < 12; p++) {
        float lo, hi;
        asm volatile("{\n.reg .b16 l, h;\nmov.b32 {l, h}, %2;\ncvt.f32.f16 %0, l;\ncvt.f32.f16 %1, h;\n}\n" : "=f"(lo), "=f"(hi) : "r"(c[2 * p + r]));
        var = fmaf(lo + nm, lo + nm, fmaf(hi + nm, hi + nm, var));
        if (p % 3 == 2) { asm volatile("" : "+f"(var)); PIN(); }
      }
      var += __shfl_xor_sync(0xffffffffu, var, 1);
      var += __shfl_xor_sync(0xffffffffu, var, 2);
      const float rr = rsqrtf(fmaf(var, 1.0f / 96.0f, 1e-5f)) * GELU_A;
      st[r] = __uint_as_float(pack_f16(rr, rr));
      const float dd = 0.5f * h_sum(__float_as_uint(st[r])) * nm;
      st[2 + r] = __uint_as_float(pack_f16(dd, dd));
      if (!(rr >= 0x1p-14f && fabsf(dd) <= 16.0f && var >= 1e-8f)) bad |= bit;
    }
  }
}
__device__ __forceinline__ void ln_apply(uint32_t (&a)[24], const uint32_t (&c)[24], const float (&st)[8]) {
#pragma unroll
  for (int p = 0; p < 24; p++) {
    a[p] = h_fma(c[p], __float_as_uint(st[p & 1]), __float_as_uint(st[2 + (p & 1)]));
  }
}

__device__ __noinline__ void slow_tile(const __nv_bfloat16* x, const __nv_bfloat16* dw, const __nv_bfloat16* w1,
                                       const __nv_bfloat16* w2, __nv_bfloat16* out, int row0, int col0, float* buf) {
  const int lane = threadIdx.x & 31;
  for (int px = 0; px < 16; px++) {
    const int row = row0 + (px >> 3), col = col0 + (px & 7);
    float c[3] = {0.f, 0.f, 0.f};
    for (int i = 0; i < 7; i++)
      for (int j = 0; j < 7; j++) {
        const int rr = row + i - 3, cc = col + j - 3;
        if (rr < 0 || rr >= IMG || cc < 0 || cc >= IMG) continue;
        for (int k = 0; k < 3; k++)
          c[k] = fmaf(__bfloat162float(x[((size_t)rr * IMG + cc) * CH + lane + 32 * k]), __bfloat162float(dw[(i * 7 + j) * CH + lane + 32 * k]), c[k]);
      }
    float mean = (c[0] + c[1] + c[2]) * (1.0f / 96.0f);
    for (int o = 16; o; o >>= 1) mean += __shfl_xor_sync(0xffffffffu, mean, o);
    float var = 0.f;
    for (int k = 0; k < 3; k++) { c[k] -= mean; var = fmaf(c[k] * (1.0f / 96.0f), c[k], var); }
    for (int o = 16; o; o >>= 1) var += __shfl_xor_sync(0xffffffffu, var, o);
    const float rs = 1.0f / sqrtf(var + 1e-5f);
    __syncwarp();
    for (int k = 0; k < 3; k++) buf[lane + 32 * k] = c[k] * rs;
    __syncwarp();
    for (int n = lane; n < 4 * CH; n += 32) {
      float y = 0.f;
      for (int k = 0; k < CH; k++) y = fmaf(buf[k], __bfloat162float(w1[k * 4 * CH + n]), y);
      buf[CH + n] = 0.5f * y * (1.0f + tanhf(0.7978845608f * (y + 0.044715f * y * y * y)));
    }
    __syncwarp();
    for (int n = lane; n < CH; n += 32) {
      float o = 0.f;
      for (int k = 0; k < 4 * CH; k++) o = fmaf(buf[CH + k], __bfloat162float(w2[k * CH + n]), o);
      const size_t idx = ((size_t)row * IMG + col) * CH + n;
      out[idx] = __float2bfloat16(__bfloat162float(x[idx]) + o);
    }
  }
}

__device__ __forceinline__ void x_load(const MlpCtx& m, uint32_t (&x)[24]) {
#pragma unroll
  for (int k = 0; k < 6; k++)
    asm volatile("ld.shared.v4.b32 {%0,%1,%2,%3}, [%4];"
                 : "=r"(x[4 * k]), "=r"(x[4 * k + 1]), "=r"(x[4 * k + 2]), "=r"(x[4 * k + 3])
                 : "r"(m.xaddr + (k / 3) * 384 + (k % 3) * 64)
                 : "memory");
}
template <int LO, int HI>
__device__ __forceinline__ void epilogue(const MlpCtx& m, const uint32_t (&d)[24], uint32_t (&x)[24]) {
#pragma unroll
  for (int k = LO; k < HI; k++) {
    const int r = k / 3, q = k % 3;
    uint32_t* y = &x[4 * k];
#pragma unroll
    for (int j = 0; j < 4; j++) {
      uint32_t v = d[2 * (4 * q + j) + r];
      float lo, hi;
      asm("{\n.reg .b16 l, h;\nmov.b32 {l, h}, %2;\ncvt.f32.f16 %0, l;\ncvt.f32.f16 %1, h;\n}\n" : "=f"(lo), "=f"(hi) : "r"(v));
      asm("fma.rn.bf16x2 %0, %1, %2, %0;" : "+r"(y[j]) : "r"(pack_bf16(lo, hi)), "r"(m.unscale));
    }
    asm volatile("st.shared.v4.b32 [%0], {%1,%2,%3,%4};" ::"r"(m.xaddr + r * 384 + q * 64), "r"(y[0]), "r"(y[1]), "r"(y[2]), "r"(y[3])
                 : "memory");
  }
}
__device__ __forceinline__ void out_store(const MlpCtx& m, int i) {
  asm volatile("fence.proxy.async.shared::cta;" ::: "memory");
  __syncwarp();
  if (elect_one()) {
    const uint32_t src = m.sb + OFF_XRES + m.wg * 12288 + m.warp * 1536;
    uint8_t* dst = m.optr + (size_t)i * (8 * IMG * CH * 2);
    asm volatile("cp.async.bulk.global.shared::cta.bulk_group [%0], [%1], 1536;" ::"l"(dst), "r"(src) : "memory");
    asm volatile("cp.async.bulk.global.shared::cta.bulk_group [%0], [%1], 1536;" ::"l"(dst + IMG * CH * 2), "r"(src + 6144) : "memory");
    asm volatile("cp.async.bulk.commit_group;" ::: "memory");
  }
}

#define FSET 3
template <int J> constexpr bool goes_first = J == FSET || J == ((FSET + 1) & 3);
template <int J> __device__ __forceinline__ void tok_wait() {
  if (goes_first<J>) NB_SYNC(NB_CLOSE, 256);
  else NB_SYNC(NB_SEC + (J & 1), 256);
}
template <int J, bool PROD = true> __device__ __forceinline__ void tok_next() {
  if (goes_first<J>) NB_ARRIVE(NB_SEC + (J & 1), 256);
  if (J == 0 && PROD) NB_ARRIVE(NB_PROD, 160);
}
__device__ __forceinline__ void tok_pass() { NB_ARRIVE(NB_OPEN, 416); }
template <int J> __device__ __forceinline__ void tok_idle() { tok_wait<J>(); tok_next<J, false>(); tok_pass(); }

constexpr uint64_t CHK = 1152;

__device__ __forceinline__ float warp_sumsq(const uint32_t (&q)[4]) {
  const uint32_t t = bf_add(bf_add(q[0], q[1]), bf_add(q[2], q[3]));
  float f = bf_lo(t) + bf_hi(t);
#pragma unroll
  for (int o = 16; o; o >>= 1) f += __shfl_xor_sync(0xffffffffu, f, o);
  return f;
}
__device__ __forceinline__ int norm_exp(float f) { return (((int)(__float_as_uint(f * 1.5f) >> 23) - 127) >> 1) + 1; }
__device__ __forceinline__ int scale_exp(int e1, int e2) { return min(11 - e1 - e2, 14 - e2); }

__device__ __forceinline__ void convert_tile(int t, int k, const uint4* w1, const uint4* w2, uint32_t st, Scratch* scr) {
  const int lane = threadIdx.x & 31, k7 = lane & 7;
  const int j = t / 6, ks = t % 6, e = ks % 3, t4 = k7 >> 1;
  const uint4* src = t < 24 ? w1 + ((e < 2 ? 64 * (ks / 3) + 8 * t4 + 4 * e : 32 + 16 * (ks / 3) + 4 * t4) + (k7 & 1)) * 48 + j * 12 + (lane >> 3)
                            : w2 + (t - 24) * 192 + (lane >> 2) * 12 + (lane & 3);
  src += (k / 3) * 96 + (k % 3) * 4;
  if (k >= 6) src = (k == 6 ? w1 : w2) + lane * 145;
  const uint4 v = __ldg(src);
  const uint32_t w[4] = {v.x, v.y, v.z, v.w};
  const uint32_t q[4] = {bf_mul(v.x, v.x), bf_mul(v.y, v.y), bf_mul(v.z, v.z), bf_mul(v.w, v.w)};
  asm volatile("st.shared.f32 [%0], %1;" ::"r"(st + 3088 + 4 * k), "f"(warp_sumsq(q)) : "memory");
  NB_SYNC(NB_PREP, 256);
  uint32_t a[4], b[4], o[4];
  lds128(a, st + 3088);
  lds128(b, st + 3104);
  const int s = max(-64, min(64, scale_exp(norm_exp(144.f * __uint_as_float(b[2])), norm_exp(144.f * __uint_as_float(b[3]))) - 1));
  const uint32_t dst = st + k7 * 16 + (lane >> 3) * 256 + (k / 3) * 128 + (k % 3) * 1024;
  if (k >= 6) {
    const float f = ((__uint_as_float(a[0]) + __uint_as_float(a[1])) + (__uint_as_float(a[2]) + __uint_as_float(a[3]))) +
                    (__uint_as_float(b[0]) + __uint_as_float(b[1]));
    asm volatile("st.shared.v2.b32 [%0], {%1,%2};" ::"r"(st + 3072), "r"(__float_as_uint(f)), "r"(s) : "memory");
  } else if (t < 24) {
#pragma unroll
    for (int i = 0; i < 4; i++) o[i] = pack_f16(bf_lo(w[i]), bf_hi(w[i]));
    asm volatile("st.shared.v4.b32 [%0], {%1,%2,%3,%4};" ::"r"(dst), "r"(o[0]), "r"(o[1]), "r"(o[2]), "r"(o[3]) : "memory");
  } else {
    constexpr float F = 0.5f / GELU_A, FHI = 1.515625f;
    const float p2 = __uint_as_float((uint32_t)(127 + s - 56) << 23);
    const uint32_t hi = pack_bf16(FHI * 0x1p-56f, FHI * 0x1p-56f), lo = pack_bf16((F - FHI) * 0x1p-56f, (F - FHI) * 0x1p-56f);
    const uint32_t pw = pack_bf16(p2, p2);
#pragma unroll
    for (int i = 0; i < 4; i++) {
      const uint32_t ws = bf_mul(w[i], pw), u = bf_fma(ws, hi, bf_mul(ws, lo));
      o[i] = (u & 0x7fff7fffu) * 7u + u;
    }
    asm volatile("stmatrix.sync.aligned.m8n8.x4.shared.b16 [%0], {%1,%2,%3,%4};" ::"r"(dst), "r"(o[0]), "r"(o[1]), "r"(o[2]), "r"(o[3])
                 : "memory");
  }
  asm volatile("fence.proxy.async.shared::cta;" ::: "memory");
  NB_SYNC(NB_PREP, 256);
  TS(4);
  if (k == 0 && elect_one()) {
    asm volatile("cp.async.bulk.global.shared::cta.bulk_group [%0], [%1], 3072;" ::"l"(scr->w + t * 192), "r"(st) : "memory");
    asm volatile("cp.async.bulk.global.shared::cta.bulk_group [%0], [%1], 16;" ::"l"(scr->nrm + t), "r"(st + 3072) : "memory");
    asm volatile("cp.async.bulk.commit_group;" ::: "memory");
    asm volatile("cp.async.bulk.wait_group 0;" ::: "memory");
    asm volatile("red.relaxed.gpu.global.add.u32 [%0], 1;" ::"l"(&scr->done) : "memory");
  }
  TS(5);
}

__device__ __forceinline__ uint32_t mlp_role(const MlpCtx& m0) {
  MlpCtx m = m0;
  uint32_t bad = 0;
  asm volatile("barrier.cluster.wait.aligned;" ::: "memory");
  if ((m.sb & 0x3FFFF) != 1024) bad = 0xffffu;
  constexpr uint64_t dW1 = (uint64_t)((1024 + OFF_W1) >> 4) | ((uint64_t)8 << 16) | ((uint64_t)16 << 32);
  constexpr uint64_t dW2 = dW1 + (OFF_W2 >> 4);
  TS(6);
  uint32_t A1[24], g[24], d[24], cn[24], D2[24];
  float st[8];
  if (m.wg & m.rank) tok_idle<3>();
  else if (m.wg) tok_idle<0>();
  else if (m.rank) tok_idle<1>();
  ln_wait(m, 0);
  ln_load(m, cn);
  ln_sums(cn, st);
  ln_shfl(st, 1);
  ln_release(m);
  ln_fold(st);
  ln_shfl(st, 2);
  ln_restat(ln_stats(st), cn, st, bad, 1, m.zero);
  ln_apply(A1, cn, st);
  {
    const int lane = threadIdx.x & 31;
    TS(2);
    mbar_wait(m.sb + BAR_W, 0);
    TS(3);
    float n1, n2;
    int s;
    asm volatile("ld.shared.b32 %0, [%1];" : "=r"(s) : "r"(m.sb + OFF_NRM + 4) : "memory");
    asm volatile("ld.shared.f32 %0, [%1];" : "=f"(n1) : "r"(m.sb + OFF_NRM + 16 * min(lane, 23)) : "memory");
    asm volatile("ld.shared.f32 %0, [%1];" : "=f"(n2) : "r"(m.sb + OFF_NRM + 384 + 16 * min(lane, 23)) : "memory");
    if (lane >= 24) n1 = n2 = 0.f;
#pragma unroll
    for (int o = 16; o; o >>= 1) {
      n1 += __shfl_xor_sync(0xffffffffu, n1, o);
      n2 += __shfl_xor_sync(0xffffffffu, n2, o);
    }
    const int e1 = norm_exp(n1), e2 = norm_exp(n2), smax = scale_exp(e1, e2);
    if (e1 > 12 || e1 < -5 || e2 > 50 || e2 < -50 || s > smax || s < smax - 5) bad = 0xffffu;
    m.unscale = __shfl_sync(0xffffffffu, ((uint32_t)(127 - s) << 7) * 0x10001u, 0);
  }
  TS(7);
  if (m.wg & m.rank) tok_idle<0>();
  if (m.wg) tok_idle<1>();
  {
    uint32_t d0[24];
    WG_FENCE();
    tok_wait<2>();
    tok_next<2>();
    gemm6<true, 192>(d0, A1, dW1);
    tok_pass(); PIN();
    WG_WAIT0(); rfence(d0);
    WG_FENCE();
    tok_wait<3>();
    tok_next<3>();
    gemm6<true, 192>(d, A1, dW1 + CHK);
    tok_pass(); PIN();
    gelu<0, 24>(g, d0);
    PIN();
    mbar_wait(m.sb + BAR_W + 8, 0);
    ln_wait(m, 1);
    WG_WAIT0(); rfence(d);
  }
#define G2(INIT, a, j)                      \
  WG_FENCE();                               \
  tok_wait<j>();                            \
  gemm6<INIT, 192>(D2, a, dW2 + (j) * CHK); \
  tok_next<j>(); PIN();                     \
  TL(ltb, (j) * 5 + 1);
#define G1(dst, j, P)                       \
  TL(ltb, ((j) ^ 2) * 5 + 2);               \
  P(); WG_WAIT0(); rfence(D2);              \
  WG_FENCE();                               \
  gemm6<true, 192>(dst, A1, dW1 + (j) * CHK); \
  tok_pass(); P();                          \
  TL(ltb, ((j) ^ 2) * 5 + 3);
#define ROUND_END(dst, j)                   \
  TL(ltb, (j) * 5 + 4);                     \
  PIN(); WG_WAIT0(); rfence(dst);
#define GA 9
#define GB 12
#define GC 13
#define GD 11
#pragma unroll 1
  for (int i = 0;; i++) {
    uint32_t g1[24], d2[24], g2[24], d3[24], g3[24], d0[24];
    ln_load(m, cn);
    PIN();
    G2(true, g, 0)
    gelu<0, GA>(g1, d);
    G1(d2, 2, PIN)
    ln_sums(cn, st);
    gelu<GA, 24>(g1, d);
    PIN();
    ln_shfl(st, 1);
    ROUND_END(d2, 0)

    G2(false, g1, 1)
    ln_fold(st);
    gelu<0, GB>(g2, d2);
    PIN();
    ln_shfl(st, 2);
    G1(d3, 3, PIN)
    const bool ok = ln_stats(st);
    gelu<GB, 24>(g2, d2);
    PIN();
    ln_restat(ok, cn, st, bad, 2u << i, m.zero);
    ROUND_END(d3, 1)

    if (i == 15) {
      G2(false, g2, 2)
      tok_pass();
      gelu<0, 24>(g3, d3);
      PIN();
      x_load(m, cn);
      ROUND_END(D2, 2)
      G2(false, g3, 3)
      tok_pass();
      WG_WAIT0(); rfence(D2);
      epilogue<0, 6>(m, D2, cn);
      break;
    }
    G2(false, g2, 2)
    ln_apply(A1, cn, st);
    PIN();
    gelu<0, GC>(g3, d3);
    G1(d0, 0, PIN)
    gelu<GC, 24>(g3, d3);
    PIN();
    x_load(m, cn);
    ROUND_END(d0, 2)

    G2(false, g3, 3)
    gelu<0, GD>(g, d0);
    G1(d, 1, PIN)
    epilogue<0, 6>(m, D2, cn);
    gelu<GD, 24>(g, d0);
    PIN();
    asm volatile("fence.proxy.async.shared::cta;" ::: "memory");
    ROUND_END(d, 3)
    TLDUMP(m.warp == 0 && (i >> 1) == LTRACE, m.sb + OFF_LT + m.wg * 160 + (i & 1) * 80, 20)
  }
  out_store(m, 15);
  if (m.wg == 0) { tok_idle<0>(); tok_idle<1>(); }
  asm volatile("cp.async.bulk.wait_group.read 0;" ::: "memory");
  return __reduce_or_sync(0xffffffffu, bad & 0xffffu);
}

struct ConvCtx {
  uint32_t sb;
  uint32_t a0, a_c;
  uint32_t peer_off;
  int rank, v, c0, r0, zero;
  const CUtensorMap* tm;
  const uint8_t* xsrc;
  uint8_t* optr;
};

__device__ __forceinline__ void raw_refill(const ConvCtx& c, int s) {
  if (s + 4 < NSTEP && elect_one())
    tma_raw(c.sb + OFF_RAW + (s & 3) * RAW_BYTES, c.tm, c.rank, c.c0 / 2 - 2, c.r0 - 3 + 2 * (s + 4), c.sb + BAR_RAW + 8 * (s & 3));
}
__device__ __forceinline__ void step_ready(const ConvCtx& c, int s) {
  const int nx = (s + 1) & 3, par = ((s + 1) >> 2) & 1;
  if (s + 1 < NSTEP) mbar_wait(c.sb + BAR_RAW + 8 * nx, par);
  if (s >= 7 && s < NSTEP) mbar_wait(c.sb + BAR_CEMPTY + 8 * (2 * (nx & 1) + (nx >> 1)), par);
}

__device__ __forceinline__ void c_release(const ConvCtx& c, uint32_t w) {
  const uint32_t e = c.sb + BAR_CEMPTY + 8 * (2 * c.rank + w);
  asm volatile(
      "{\n.reg .pred p;\nelect.sync _|p, 0xffffffff;\n"
      "@p mbarrier.arrive.expect_tx.shared::cta.b64 _, [%0], %3;\n"
      "@p mbarrier.arrive.shared::cluster.b64 _, [%1], 4;\n"
      "@p mbarrier.arrive.shared::cluster.b64 _, [%2], 4;\n}\n" ::"r"(c.sb + BAR_CFULL + 8 * w),
      "r"(e), "r"(e + c.peer_off), "n"(CTX)
      : "memory");
}

__device__ __forceinline__ void prod_rows(const ConvCtx& c) {
#pragma unroll 1
  for (int s = 0; s < NROUND + SIGMA + c.rank; s++) {
    const int r = s - SIGMA - c.rank;
    const int u = (r & 1) ? (r >> 1) - 1 : (r >> 1) + 2;
    step_ready(c, s);
    if (u >= ((r & 1) ? 0 : 4) && u < 32) mbar_wait(c.sb + ((r & 1) ? BAR_XFULL : BAR_CFULL) + 8 * (u & 1), (u >> 1) & 1);
    if (s < SIGMA) NB_SYNC(NB_PLAN, 160);
    else NB_SYNC(NB_OPEN, 416);
    if (r == 3) TC(1);
    if (r == 55) TC(2);
    if (r >= -1 && r < 7) TS(7 + r);
    raw_refill(c, s);
  }
}
__device__ __forceinline__ void prod_tiles(const ConvCtx& c) {
  asm volatile("barrier.cluster.wait.aligned;" ::: "memory");
#pragma unroll 1
  for (int n = 1; n < 33; n++) {
    const uint32_t w = (n + 1) & 1;
    const uint32_t buf = c.sb + OFF_XRES + w * 12288;
    NB_SYNC(NB_PROD, 160);
    if (n < 29) c_release(c, w);
    if (n >= 3) {
      uint8_t* dst = c.optr + (size_t)(n - 3) * (4 * IMG * CH * 2);
      if (elect_one()) {
        asm volatile("cp.async.bulk.global.shared::cta.bulk_group [%0], [%1], 6144;" ::"l"(dst), "r"(buf) : "memory");
        asm volatile("cp.async.bulk.global.shared::cta.bulk_group [%0], [%1], 6144;" ::"l"(dst + IMG * CH * 2), "r"(buf + 6144) : "memory");
        asm volatile("cp.async.bulk.commit_group;" ::: "memory");
        asm volatile("cp.async.bulk.wait_group.read 0;" ::: "memory");
      }
      __syncwarp();
    }
    {
      const uint8_t* src = c.xsrc + (size_t)(n - 1) * (4 * IMG * CH * 2);
      if (elect_one()) {
        mbar_expect(c.sb + BAR_XFULL + 8 * w, 12288);
        bulk_load_last(buf, src, 6144, c.sb + BAR_XFULL + 8 * w);
        bulk_load_last(buf + 6144, src + IMG * CH * 2, 6144, c.sb + BAR_XFULL + 8 * w);
      }
    }
  }
  asm volatile("cp.async.bulk.wait_group 0;" ::: "memory");
}

__device__ __forceinline__ void conv_ld8(uint32_t a0, uint32_t (&r)[6][6]) {
  const uint32_t a2 = a0 ^ (16 | ((a0 >> 2) & 32));
  const uint32_t a[3] = {a0, (a0 & 64) ? a2 : a0, a2};
#pragma unroll
  for (int j = 0; j < 6; j++)
    asm volatile("ld.shared.v4.b32 {%0,%1,%2,%3}, [%4];"
                 : "=r"(r[j][0]), "=r"(r[j][1]), "=r"(r[j][2]), "=r"(r[j][3])
                 : "r"(a[j >> 1] + (j >> 1) * 64 + (j & 1) * RAW_PA)
                 : "memory");
}
__device__ __forceinline__ void conv_ld4(uint32_t a0, uint32_t stage, int v, uint32_t (&r)[6][6]) {
  const uint32_t ab = ((a0 >> 1) & ~31u) + (stage / 2 + 2 * RAW_PA + 8 * v);
#pragma unroll
  for (int j = 0; j < 6; j++) {
    uint32_t a = ab + (j >> 1) * 32;
    asm volatile("ld.shared.v2.b32 {%0,%1}, [%2];" : "=r"(r[j][4]), "=r"(r[j][5]) : "r"(a + (j & 1) * RAW_PB) : "memory");
  }
}
template <int LO, int HI>
__device__ __forceinline__ void conv_frags(uint32_t zero, const uint32_t (&r)[6][6], uint32_t (&A)[12][4]) {
#pragma unroll
  for (int ch = LO; ch < HI; ch++) {
    const uint32_t sel = (ch & 1) ? 0x7632 : 0x5410;
    A[ch][0] = __byte_perm(r[0][ch >> 1], r[1][ch >> 1], sel);
    A[ch][1] = __byte_perm(r[2][ch >> 1], r[3][ch >> 1], sel);
    A[ch][2] = A[ch][1] ^ zero;
    A[ch][3] = __byte_perm(r[4][ch >> 1], r[5][ch >> 1], sel);
    rfence(A[ch]);
  }
}
__device__ __forceinline__ void hmma_acc(uint32_t (&v)[4], const uint32_t (&a)[4], const uint32_t* b) {
  asm volatile("mma.sync.aligned.m16n8k16.row.col.f32.bf16.bf16.f32 {%0,%1,%2,%3}, {%4,%5,%6,%7}, {%8,%9}, {%0,%1,%2,%3};"
               : "+r"(v[0]), "+r"(v[1]), "+r"(v[2]), "+r"(v[3])
               : "r"(a[0]), "r"(a[1]), "r"(a[2]), "r"(a[3]), "r"(b[0]), "r"(b[1]));
}
__device__ __forceinline__ void hmma_new(uint32_t (&a)[4], const uint32_t* b) {
  asm volatile("mma.sync.aligned.m16n8k16.row.col.f32.bf16.bf16.f32 {%0,%1,%2,%3}, {%0,%1,%2,%3}, {%4,%5}, {%6,%6,%6,%6};"
               : "+r"(a[0]), "+r"(a[1]), "+r"(a[2]), "+r"(a[3])
               : "r"(b[0]), "r"(b[1]), "f"(0.f));
}

#define EARLY 5
template <int S2, bool GATED>
__device__ __forceinline__ void conv_step(const ConvCtx& c, int s, uint32_t (&K)[12], uint32_t (&V)[12][4], const uint32_t (&B)[12][4],
                                          uint32_t (&A)[12][4]) {
  const int nx = ((s + 1) & 2) | (S2 ^ 1);
  uint32_t r[6][6];
  const uint32_t a0 = c.a0 + nx * RAW_BYTES;
  TL(ltb, 0);
  if (!GATED) TS(6 + s);
  if (GATED) NB_SYNC(NB_OPEN, 416);
  else NB_SYNC(NB_PLAN, 160);
  conv_ld4(a0, c.sb + OFF_RAW + nx * RAW_BYTES, c.v, r);
  if (GATED) PIN();
  TL(ltb, 1);
#pragma unroll
  for (int ch = 0; ch < 12; ch++) hmma_acc(V[11 - ch], A[11 - ch], &B[11 - ch][2]);
#pragma unroll
  for (int ch = 0; ch < 12 - EARLY; ch++) hmma_new(A[ch], &B[ch][0]);
  const uint32_t zero = GATED ? c.zero & clock_pin() : c.zero;
  if (GATED) NB_ARRIVE(NB_CLOSE, 256);
#pragma unroll
  for (int ch = 12 - EARLY; ch < 12; ch++) hmma_new(A[ch], &B[ch][0]);
  if (GATED) PIN();
  TL(ltb, 2);
  const uint32_t off = ((S2 ^ 1) == c.rank) ? 0u : c.peer_off;
  const uint32_t dst = c.a_c + (GATED || s >= 3 ? off + (nx >> 1) * C_BYTES : OFF_XRES + 12288 - OFF_C);
  const uint32_t bar = c.sb + (GATED || s >= 3 ? off + BAR_CFULL + 8 * (nx >> 1) : BAR_W + 56);
#pragma unroll
  for (int q = 0; q < 12; q++) {
    const int ch = q & ~1, h = 2 * (q & 1);
    asm("add.rn.f16x2 %0, %0, %1;" : "+r"(K[q]) : "r"(pack_f16(__uint_as_float(V[ch][h + 1]), __uint_as_float(V[ch + 1][h]))));
  }
  if ((S2 ^ 1) == c.rank) {
#pragma unroll
    for (int q = 0; q < 3; q++)
      asm volatile("st.shared.v4.b32 [%0], {%1,%2,%3,%4};" ::"r"(dst + q * 2048), "r"(K[4 * q]), "r"(K[4 * q + 1]), "r"(K[4 * q + 2]), "r"(K[4 * q + 3])
                   : "memory");
    asm volatile("{\n.reg .pred p;\nelect.sync _|p, 0xffffffff;\n@p mbarrier.arrive.shared::cta.b64 _, [%0];\n}\n" ::"r"(bar) : "memory");
  } else {
#pragma unroll
  for (int q = 0; q < 3; q++)
    asm volatile("st.async.weak.shared::cluster.mbarrier::complete_tx::bytes.v4.b32 [%0], {%1,%2,%3,%4}, [%5];" ::"r"(dst + q * 2048),
                 "r"(K[4 * q]), "r"(K[4 * q + 1]), "r"(K[4 * q + 2]), "r"(K[4 * q + 3]), "r"(bar)
                 : "memory");
  }
  PIN();
#pragma unroll
  for (int q = 0; q < 12; q++) {
    const int ch = q & ~1, h = 2 * (q & 1);
    K[q] = pack_f16(__uint_as_float(V[ch][h]), __uint_as_float(V[ch + 1][h + 1]));
  }
  rfence(K);
  conv_frags<8, 12>(zero, r, V);
  PIN();
  conv_ld8(a0, r);
  conv_frags<0, 8>(zero, r, V);
  PIN();
  TL(ltb, 4);
  TLDUMP(c.v == 0 && lr >= 0 && lr < 10, c.sb + OFF_LT + 320 + lr * 20, 5)
}

__device__ __forceinline__ void conv_role(ConvCtx c) {
  const int lane = laneid(), g = lane >> 2, t = lane & 3;
  const int u = (t >> 1) * 19 + 2 * (g + (t & 1));
  c.a0 = c.sb + OFF_RAW + u * 64 + ((c.v ^ (u >> 1)) & 3) * 16;
  c.a_c = c.sb + OFF_C + 6144 * c.rank + 512 * c.v + ((lane + 2 * c.v) & 31) * 16;
  uint32_t B[12][4];
  {
    const int dc = (g >> 1) & 1, ro = g >> 2, rk = t >> 1;
    const int i0 = 4 * (g & 1) + rk - ro, j0 = 4 * (t & 1) - dc;
    const uint32_t base = c.sb + OFF_XRES + (i0 * 7 + j0) * 192;
    TS(2);
    asm volatile("barrier.cluster.wait.aligned;" ::: "memory");
    mbar_wait(c.sb + BAR_W + 48, 0);
    TS(3);
#pragma unroll
    for (int b = 0; b < 2; b++) {
      uint32_t w[4][6];
#pragma unroll
      for (int k = 0; k < 4; k++) {
        const int ok = (unsigned)(i0 + 2 * b) < 7u && (unsigned)(j0 + k) < 7u;
#pragma unroll
        for (int q = 0; q < 6; q++) w[k][q] = 0;
        asm volatile(
            "{\n.reg .pred p;\nsetp.ne.s32 p, %8, 0;\n@p ld.shared.v4.b32 {%0,%1,%2,%3}, [%6];\n@p ld.shared.v2.b32 {%4,%5}, [%7];\n}\n"
            : "+r"(w[k][0]), "+r"(w[k][1]), "+r"(w[k][2]), "+r"(w[k][3]), "+r"(w[k][4]), "+r"(w[k][5])
            : "r"(base + (b * 14 + k) * 192 + 128 * c.rank + 16 * c.v), "r"(base + (b * 14 + k) * 192 + 64 + 32 * c.rank + 8 * c.v), "r"(ok)
            : "memory");
      }
#pragma unroll
      for (int q = 0; q < 6; q++) {
        B[2 * q][2 * b] = __byte_perm(w[0][q], w[1][q], 0x5410);
        B[2 * q][2 * b + 1] = __byte_perm(w[2][q], w[3][q], 0x5410);
        B[2 * q + 1][2 * b] = __shfl_xor_sync(0xffffffffu, __byte_perm(w[0][q], w[1][q], 0x7632), 4);
        B[2 * q + 1][2 * b + 1] = __shfl_xor_sync(0xffffffffu, __byte_perm(w[2][q], w[3][q], 0x7632), 4);
      }
    }
  }
  TS(4);
  uint32_t K1[12], K2[12], V[12][4];
#pragma unroll
  for (int ch = 0; ch < 12; ch++) {
    K1[ch] = K2[ch] = 0;
#pragma unroll
    for (int k = 0; k < 4; k++) V[ch][k] = 0;
  }
  uint32_t A[12][4], r[6][6];
  mbar_wait(c.sb + BAR_RAW, 0);
  TS(5);
  conv_ld8(c.a0, r);
  conv_ld4(c.a0, c.sb + OFF_RAW, c.v, r);
  conv_frags<0, 12>(c.zero, r, A);
  PIN();
  NB_ARRIVE(NB_CLOSE, 256);
#pragma unroll 1
  for (int s = 0; s < SIGMA; s += 2) {
    conv_step<0, false>(c, s, K1, V, B, A);
    conv_step<1, false>(c, s + 1, K2, A, B, V);
  }
#pragma unroll 1
  for (int s = SIGMA;; s += 2) {
    conv_step<0, true>(c, s, K1, V, B, A);
    if (s == NSTEP - 1) break;
    conv_step<1, true>(c, s + 1, K2, A, B, V);
  }
#pragma unroll 1
  for (int r = NSTEP - SIGMA - c.rank; r < NROUND - 1; r++) {
    NB_SYNC(NB_OPEN, 416);
    NB_ARRIVE(NB_CLOSE, 256);
  }
  NB_SYNC(NB_OPEN, 416);
}

struct TMaps { CUtensorMap m[2]; };
__device__ __forceinline__ Scratch* scr_param() {
  extern __shared__ __align__(1024) uint8_t smem[];
  return *reinterpret_cast<Scratch* volatile*>(smem + OFF_LT + 592);
}

__global__ void __cluster_dims__(2, 1, 1) __launch_bounds__(512, 1)
convnext_kernel(const __grid_constant__ TMaps tms, const __nv_bfloat16* __restrict__ x, const __nv_bfloat16* __restrict__ dw,
                const __nv_bfloat16* __restrict__ w1, const __nv_bfloat16* __restrict__ w2, __nv_bfloat16* __restrict__ out,
                Scratch* scr, int zero) {
  extern __shared__ __align__(1024) uint8_t smem[];
  const uint32_t sb = (uint32_t)__cvta_generic_to_shared(smem);
  const int tid = threadIdx.x, lane = tid & 31;
  const int wid = __shfl_sync(0xffffffffu, tid >> 5, 0);
  const int rank = blockIdx.x & 1, cl = blockIdx.x >> 1;
  const int c0 = (cl & 15) * 32, r0 = (cl >> 4) * 128;
  const uint32_t peer_off = mapa(sb, rank ^ 1) - sb;

  TS(0);
  if (wid == 12 && elect_one()) {
    mbar_init(sb + BAR_W + 48, 1);
#pragma unroll
    for (int i = 0; i < 4; i++) mbar_init(sb + BAR_RAW + 8 * i, 1);
    asm volatile("fence.mbarrier_init.release.cluster;" ::: "memory");
    mbar_expect(sb + BAR_W + 48, 49 * CH * 2);
    bulk_load(sb + OFF_XRES, dw, 49 * CH * 2, sb + BAR_W + 48);
#pragma unroll
    for (int i = 0; i < E0; i++) tma_raw(sb + OFF_RAW + i * RAW_BYTES, tms.m, rank, c0 / 2 - 2, r0 - 3 + 2 * i, sb + BAR_RAW + 8 * i);
  }
  if (wid == 14 && elect_one()) {
    asm volatile("prefetch.tensormap [%0];" ::"l"(&tms.m[1]) : "memory");
#pragma unroll
    for (int i = 0; i < 3; i++) mbar_init(sb + BAR_W + 8 * i, 1);
    mbar_init(sb + BAR_W + 56, 100);
#pragma unroll
    for (int i = 0; i < 2; i++) mbar_init(sb + BAR_CFULL + 8 * i, CCNT);
#pragma unroll
    for (int i = 0; i < 4; i++) mbar_init(sb + BAR_CEMPTY + 8 * i, 4);
#pragma unroll
    for (int i = 0; i < 2; i++) mbar_init(sb + BAR_XFULL + 8 * i, 1);
#pragma unroll
    for (int i = 0; i < 2; i++) mbar_expect(sb + BAR_CFULL + 8 * i, CTX);
    asm volatile("fence.mbarrier_init.release.cluster;" ::: "memory");
  }
  __syncwarp();
  asm volatile("barrier.cluster.arrive.relaxed.aligned;" ::: "memory");

  TS(1);
  if (wid < 8) {
    if (blockIdx.x < 48) convert_tile(blockIdx.x, wid, reinterpret_cast<const uint4*>(w1), reinterpret_cast<const uint4*>(w2), sb, scr);
    MlpCtx m;
    m.sb = sb; m.wg = wid >> 2; m.warp = wid & 3; m.rank = rank; m.peer_off = peer_off; m.zero = zero;
    m.optr = reinterpret_cast<uint8_t*>(out) + ((size_t)(r0 + 4 * m.wg + 2 * rank) * IMG + c0 + 8 * m.warp) * (CH * 2);
    m.caddr = sb + OFF_C + m.wg * C_BYTES + (lane & 3) * 512 + ((m.warp * 8 + (lane >> 2) + 2 * (lane & 3)) & 31) * 16;
    m.xaddr = sb + OFF_XRES + m.wg * 12288 + m.warp * 1536 + ((lane >> 3) & 1) * 6144 + ((lane >> 4) * 4 + ((lane >> 2) & 1)) * 192 + (lane & 3) * 16;
    m.unscale = 0;
    asm volatile("setmaxnreg.inc.sync.aligned.u32 %0;" ::"n"(REG_MLP));
    const uint32_t bad = mlp_role(m);
    TC(3);
    if (bad) {
      asm volatile("cp.async.bulk.wait_group 0;" ::: "memory");
      mbar_wait(sb + BAR_W + 16, 0);
      __syncwarp();
      asm volatile("fence.proxy.async;" ::: "memory");
#pragma unroll 1
      for (int i = 0; i < 16; i++)
        if (bad >> i & 1)
          slow_tile(x, dw, w1, w2, out, r0 + 8 * i + 4 * m.wg + 2 * rank, c0 + 8 * m.warp,
                    reinterpret_cast<float*>(smem + OFF_RAW + wid * 2048));
    }
  } else {
    ConvCtx c;
    c.sb = sb; c.rank = rank; c.v = wid - 8; c.c0 = c0; c.r0 = r0; c.zero = zero; c.tm = tms.m;
    c.peer_off = peer_off;
    c.xsrc = reinterpret_cast<const uint8_t*>(x) + ((size_t)(r0 + 2 * rank) * IMG + c0) * (CH * 2);
    c.optr = reinterpret_cast<uint8_t*>(out) + ((size_t)(r0 + 2 * rank) * IMG + c0) * (CH * 2);
    if (wid < 12) {
      asm volatile("setmaxnreg.inc.sync.aligned.u32 %0;" ::"n"(REG_CONV));
      conv_role(c);
    } else {
      asm volatile("setmaxnreg.dec.sync.aligned.u32 24;");
      if (wid == 15) TC(0);
      if (wid == 12) {
        TS(2);
#pragma unroll 1
        for (int h = E0 - 4; h < 0; h++) raw_refill(c, h);
        TS(3);
        asm volatile("barrier.cluster.wait.aligned;" ::: "memory");
        prod_rows(c);
      } else if (wid == 14) {
#pragma unroll 1
        for (int n = 0; n < (1 << 20); n++) {
          unsigned v;
          __nanosleep(n ? PSL : PS0);
          asm volatile("ld.acquire.gpu.global.u32 %0, [%1];" : "=r"(v) : "l"(&scr->done) : "memory");
          if (__shfl_sync(0xffffffffu, v, 0) >= 48) break;
        }
        asm volatile("barrier.cluster.wait.aligned;" ::: "memory");
        asm volatile("fence.proxy.async.global;" ::: "memory");
        if (elect_one()) {
          mbar_expect(sb + BAR_W, 36864 + 768);
          mbar_expect(sb + BAR_W + 8, 110592);
          bulk_load(sb + OFF_NRM, scr->nrm, 768, sb + BAR_W);
          if (atomicAdd(&scr->seen, 1u) == gridDim.x - 1) { scr->done = 0; scr->seen = 0; }
        }
        __syncwarp();
#pragma unroll 1
        for (int i = 0; i < 8; i++) {
          if (elect_one()) bulk_load(sb + i * 18432, reinterpret_cast<const uint8_t*>(scr->w) + i * 18432, 18432, sb + BAR_W + (i < 2 ? 0 : 8));
          __nanosleep(PACE);
        }
      } else if (wid == 13) {
        prod_tiles(c);
        __syncwarp();
        if (elect_one()) asm volatile("mbarrier.arrive.shared::cta.b64 _, [%0];" ::"r"(sb + BAR_W + 16) : "memory");
      }
    }
  }
}

typedef CUresult (*EncodeFn)(CUtensorMap*, CUtensorMapDataType, cuuint32_t, void*, const cuuint64_t*, const cuuint64_t*,
                             const cuuint32_t*, const cuuint32_t*, CUtensorMapInterleave, CUtensorMapSwizzle,
                             CUtensorMapL2promotion, CUtensorMapFloatOOBfill);

}

extern "C" void kernel_launch(void* const* d_in, const int* in_sizes, int n_in, void* d_out, int out_size) {
  const __nv_bfloat16* x = (const __nv_bfloat16*)d_in[0];
  const __nv_bfloat16* dw = (const __nv_bfloat16*)d_in[1];
  const __nv_bfloat16* w1 = (const __nv_bfloat16*)d_in[2];
  const __nv_bfloat16* w2 = (const __nv_bfloat16*)d_in[3];
  __nv_bfloat16* out = (__nv_bfloat16*)d_out;

  static EncodeFn encode = nullptr;
  static Scratch* scr = nullptr;
  if (!encode) {
    cudaDriverEntryPointQueryResult st;
    void* fn = nullptr;
    cudaGetDriverEntryPoint("cuTensorMapEncodeTiled", &fn, cudaEnableDefault, &st);
    encode = (EncodeFn)fn;
    cudaGetSymbolAddress((void**)&scr, g_scratch);
    cudaFuncSetAttribute(convnext_kernel, cudaFuncAttributeMaxDynamicSharedMemorySize, SMEM_BYTES);
  }
  TMaps tm;
  cuuint64_t dims[4] = {CH, IMG / 2, IMG, 2};
  cuuint64_t strides[3] = {CH * 4, (cuuint64_t)IMG * CH * 2, CH * 2};
  cuuint32_t es[4] = {1, 1, 1, 1};
  for (int i = 0; i < 2; i++) {
    cuuint32_t box[4] = {i ? 16u : 32u, 19, 2, 1};
    encode(&tm.m[i], CU_TENSOR_MAP_DATA_TYPE_BFLOAT16, 4, (void*)x, dims, strides, box, es, CU_TENSOR_MAP_INTERLEAVE_NONE,
           i ? CU_TENSOR_MAP_SWIZZLE_NONE : CU_TENSOR_MAP_SWIZZLE_64B, PROMO, CU_TENSOR_MAP_FLOAT_OOB_FILL_NONE);
  }
  convnext_kernel<<<128, 512, SMEM_BYTES>>>(tm, x, dw, w1, w2, out, scr, 0);
}
```

```cpp
#include <cuda_runtime.h>
#include <cuda_bf16.h>
#include <cuda.h>
#include <stdint.h>

#define PROMO CU_TENSOR_MAP_L2_PROMOTION_L2_128B
#define CTX 6144
#define CCNT 5
#define PSL 100
#define PS0 1000
#define E0 1
#define PACE 100
namespace {

constexpr int IMG = 512, CH = 96;
constexpr int NSTEP = 67;
constexpr int SIGMA = 8;
constexpr int NROUND = 68;

constexpr uint32_t OFF_W1 = 0;
constexpr uint32_t OFF_W2 = 73728;
constexpr uint32_t OFF_RAW = 147456;
constexpr uint32_t RAW_PA = 2560, RAW_PB = 1280;
constexpr uint32_t RAW_BYTES = 2 * RAW_PA + 2 * RAW_PB;
constexpr uint32_t RAW_TX = 2 * 38 * 96;
constexpr uint32_t OFF_XRES = OFF_RAW + 4 * RAW_BYTES;
constexpr uint32_t OFF_C = OFF_XRES + 2 * 12288;
constexpr uint32_t C_BYTES = 12288;
constexpr uint32_t OFF_BAR = OFF_C + 2 * C_BYTES;
constexpr uint32_t BAR_RAW = OFF_BAR;
constexpr uint32_t BAR_CFULL = OFF_BAR + 32;
constexpr uint32_t BAR_CEMPTY = OFF_BAR + 48;
constexpr uint32_t BAR_XFULL = OFF_BAR + 80;
constexpr uint32_t BAR_W = OFF_BAR + 96;
constexpr uint32_t OFF_NRM = OFF_XRES + 9472;
constexpr uint32_t OFF_LT = OFF_BAR + 160;
constexpr uint32_t SMEM_BYTES = OFF_BAR + 160 + 600;

struct Scratch {
  uint4 w[2 * 73728 / 16];
  uint4 nrm[48];
  unsigned done, seen;
};
__device__ Scratch g_scratch;

constexpr float GELU_A = 0.32918364f;
constexpr uint32_t GELU_K2 = 0x40d940d9u;

constexpr int NB_CLOSE = 1, NB_SEC = 6  , NB_OPEN = 3, NB_PROD = 2, NB_PLAN = 4, NB_PREP = 5, NB_WG = 8  ;
#define REG_MLP 144
constexpr int REG_CONV = 488 - 2 * REG_MLP;

#define WG_FENCE() asm volatile("wgmma.fence.sync.aligned;" ::: "memory")
#define WG_COMMIT() asm volatile("wgmma.commit_group.sync.aligned;" ::: "memory")
#define WG_WAIT0() asm volatile("wgmma.wait_group.sync.aligned 0;" ::: "memory")
#define WG_WAIT1() asm volatile("wgmma.wait_group.sync.aligned 1;" ::: "memory")
#define PIN() asm volatile("pmevent 0;" ::: "memory")
#define NB_SYNC(id, n) asm volatile("bar.sync %0, %1;" ::"n"(id), "n"(n) : "memory")
#define NB_ARRIVE(id, n) asm volatile("bar.arrive %0, %1;" ::"n"(id), "n"(n) : "memory")

#define SCR (scr_param())
__device__ __forceinline__ Scratch* scr_param();
#define TS(idx)
#define TC(scr, k)
#define TL(base, off)
#define TLDUMP(cond, base, n)

#define R24(c, d)                                                                                        \
  c(d[0]), c(d[1]), c(d[2]), c(d[3]), c(d[4]), c(d[5]), c(d[6]), c(d[7]), c(d[8]), c(d[9]), c(d[10]),    \
      c(d[11]), c(d[12]), c(d[13]), c(d[14]), c(d[15]), c(d[16]), c(d[17]), c(d[18]), c(d[19]), c(d[20]), \
      c(d[21]), c(d[22]), c(d[23])
#define WG_TXT(sd)                                                                             \
  "wgmma.mma_async.sync.aligned.m64n96k16.f16.f16.f16 "                                        \
  "{%0,%1,%2,%3,%4,%5,%6,%7,%8,%9,%10,%11,%12,%13,%14,%15,%16,%17,%18,%19,%20,%21,%22,%23}, " \
  "{%24,%25,%26,%27}, %28, " sd ", 1, 1, 1;\n"

__device__ __forceinline__ void wg_acc(uint32_t (&d)[24], const uint32_t* a, uint64_t db) {
  asm volatile(WG_TXT("1") : R24("+r", d) : "r"(a[0]), "r"(a[1]), "r"(a[2]), "r"(a[3]), "l"(db));
}
__device__ __forceinline__ void wg_init(uint32_t (&d)[24], const uint32_t* a, uint64_t db) {
  asm volatile(WG_TXT("0") : R24("=r", d) : "r"(a[0]), "r"(a[1]), "r"(a[2]), "r"(a[3]), "l"(db));
}
template <int N>
__device__ __forceinline__ void rfence(uint32_t (&d)[N]) {
#pragma unroll
  for (int i = 0; i < N; i++) asm volatile("" : "+r"(d[i])::"memory");
}
template <bool INIT, int KSTRIDE>
__device__ __forceinline__ void gemm6(uint32_t (&d)[24], const uint32_t (&a)[24], uint64_t db) {
#pragma unroll
  for (int k = 0; k < 6; k++) {
    if (INIT && k == 0) wg_init(d, &a[0], db);
    else wg_acc(d, &a[4 * k], db + k * KSTRIDE);
  }
  WG_COMMIT();
}

__device__ __forceinline__ void mbar_init(uint32_t bar, uint32_t cnt) {
  asm volatile("mbarrier.init.shared::cta.b64 [%0], %1;" ::"r"(bar), "r"(cnt) : "memory");
}
__device__ __forceinline__ void mbar_expect(uint32_t bar, uint32_t bytes) {
  asm volatile("mbarrier.arrive.expect_tx.shared::cta.b64 _, [%0], %1;" ::"r"(bar), "r"(bytes) : "memory");
}
__device__ __forceinline__ void mbar_arrive_cluster(uint32_t bar) {
  asm volatile("mbarrier.arrive.shared::cluster.b64 _, [%0];" ::"r"(bar) : "memory");
}
__device__ __forceinline__ bool mbar_try(uint32_t bar, uint32_t parity) {
  uint32_t ok;
  asm volatile(
      "{\n.reg .pred p;\nmbarrier.try_wait.parity.shared::cta.b64 p, [%1], %2;\nselp.u32 %0, 1, 0, p;\n}\n"
      : "=r"(ok)
      : "r"(bar), "r"(parity)
      : "memory");
  return ok;
}
__device__ __forceinline__ bool mbar_test(uint32_t bar, uint32_t parity) {
  uint32_t ok;
  asm volatile(
      "{\n.reg .pred p;\nmbarrier.test_wait.parity.shared::cta.b64 p, [%1], %2;\nselp.u32 %0, 1, 0, p;\n}\n"
      : "=r"(ok)
      : "r"(bar), "r"(parity)
      : "memory");
  return ok;
}
__device__ __forceinline__ void mbar_wait(uint32_t bar, uint32_t parity) {
  if (__builtin_expect(mbar_try(bar, parity), 1)) return;
#pragma unroll 1
  for (uint32_t n = 0; n < (1u << 16) && !mbar_try(bar, parity); n++) {}
}
__device__ __forceinline__ uint32_t mapa(uint32_t addr, uint32_t rank) {
  uint32_t r;
  asm("mapa.shared::cluster.u32 %0, %1, %2;" : "=r"(r) : "r"(addr), "r"(rank));
  return r;
}
__device__ __forceinline__ void tma_raw(uint32_t dst, const CUtensorMap* tm, int rank, int w2, int h, uint32_t bar) {
  mbar_expect(bar, RAW_TX);
#pragma unroll
  for (int k = 0; k < 4; k++) {
    const int e = k & 1;
    asm volatile(
        "cp.async.bulk.tensor.4d.shared::cluster.global.mbarrier::complete_tx::bytes [%0], [%1, {%2, %3, %4, %5}], [%6];"
        ::"r"(dst + (k < 2 ? e * RAW_PA : 2 * RAW_PA + e * RAW_PB)), "l"(tm + (k >> 1)), "r"(k < 2 ? 64 * rank : 32 + 16 * rank), "r"(w2 + e),
        "r"(h), "r"(1 - e), "r"(bar)
        : "memory");
  }
}
__device__ __forceinline__ void bulk_load(uint32_t dst, const void* src, uint32_t bytes, uint32_t bar) {
  asm volatile("cp.async.bulk.shared::cluster.global.mbarrier::complete_tx::bytes [%0], [%1], %2, [%3];" ::"r"(dst),
               "l"(src), "r"(bytes), "r"(bar)
               : "memory");
}
__device__ __forceinline__ void bulk_load_last(uint32_t dst, const void* src, uint32_t bytes, uint32_t bar) {
  asm volatile(
      "{\n.reg .b64 pol;\ncreatepolicy.fractional.L2::evict_first.b64 pol, 1.0;\n"
      "cp.async.bulk.shared::cluster.global.mbarrier::complete_tx::bytes.L2::cache_hint [%0], [%1], %2, [%3], pol;\n}\n" ::"r"(dst),
      "l"(src), "r"(bytes), "r"(bar)
      : "memory");
}
__device__ __forceinline__ uint32_t pack_bf16(float lo, float hi) {
  uint32_t r;
  asm("cvt.rn.bf16x2.f32 %0, %1, %2;" : "=r"(r) : "f"(hi), "f"(lo));
  return r;
}
__device__ __forceinline__ uint32_t pack_f16(float lo, float hi) {
  uint32_t r;
  asm("cvt.rn.f16x2.f32 %0, %1, %2;" : "=r"(r) : "f"(hi), "f"(lo));
  return r;
}
__device__ __forceinline__ float bf_lo(uint32_t v) { return __uint_as_float(v << 16); }
__device__ __forceinline__ float bf_hi(uint32_t v) { return __uint_as_float(v & 0xffff0000u); }
__device__ __forceinline__ uint32_t bf_add(uint32_t a, uint32_t b) {
  uint32_t r;
  asm("add.rn.bf16x2 %0, %1, %2;" : "=r"(r) : "r"(a), "r"(b));
  return r;
}
__device__ __forceinline__ uint32_t bf_mul(uint32_t a, uint32_t b) {
  uint32_t r;
  asm("mul.rn.bf16x2 %0, %1, %2;" : "=r"(r) : "r"(a), "r"(b));
  return r;
}
__device__ __forceinline__ uint32_t bf_fma(uint32_t a, uint32_t b, uint32_t c) {
  uint32_t r;
  asm("fma.rn.bf16x2 %0, %1, %2, %3;" : "=r"(r) : "r"(a), "r"(b), "r"(c));
  return r;
}

__device__ __forceinline__ uint32_t h_add(uint32_t a, uint32_t b) {
  uint32_t r;
  asm("add.rn.f16x2 %0, %1, %2;" : "=r"(r) : "r"(a), "r"(b));
  return r;
}
__device__ __forceinline__ uint32_t h_mul(uint32_t a, uint32_t b) {
  uint32_t r;
  asm("mul.rn.f16x2 %0, %1, %2;" : "=r"(r) : "r"(a), "r"(b));
  return r;
}
__device__ __forceinline__ uint32_t h_fma(uint32_t a, uint32_t b, uint32_t c) {
  uint32_t r;
  asm("fma.rn.f16x2 %0, %1, %2, %3;" : "=r"(r) : "r"(a), "r"(b), "r"(c));
  return r;
}
__device__ __forceinline__ float h_sum(uint32_t v) {
  float lo, hi;
  asm("{\n.reg .b16 l, h;\nmov.b32 {l, h}, %2;\ncvt.f32.f16 %0, l;\ncvt.f32.f16 %1, h;\n}\n" : "=f"(lo), "=f"(hi) : "r"(v));
  return lo + hi;
}
__device__ __forceinline__ void lds128(uint32_t (&v)[4], uint32_t a) {
  asm volatile("ld.shared.v4.b32 {%0,%1,%2,%3}, [%4];" : "=r"(v[0]), "=r"(v[1]), "=r"(v[2]), "=r"(v[3]) : "r"(a) : "memory");
}

template <int LO, int HI>
__device__ __forceinline__ void gelu(uint32_t (&o)[24], const uint32_t (&d)[24]) {
#pragma unroll
  for (int qq = LO; qq < HI; qq++) {
    const int q = (qq + 4) % 24;
    uint32_t t, u;
    asm("fma.rn.f16x2 %0, %1, %1, %2;" : "=r"(t) : "r"(d[q]), "r"(GELU_K2));
    asm("mul.rn.f16x2 %0, %1, %2;" : "=r"(u) : "r"(d[q]), "r"(t));
    asm("tanh.approx.f16x2 %0, %1;" : "=r"(t) : "r"(u));
    asm("fma.rn.f16x2 %0, %1, %2, %1;" : "=r"(o[q]) : "r"(d[q]), "r"(t));
  }
}

__device__ __forceinline__ uint32_t laneid() {
  uint32_t l;
  asm volatile("mov.u32 %0, %%laneid;" : "=r"(l));
  return l;
}

__device__ __forceinline__ bool elect_one() {
  uint32_t p;
  asm volatile("{\n.reg .pred p;\nelect.sync _|p, 0xffffffff;\nselp.u32 %0, 1, 0, p;\n}\n" : "=r"(p));
  return p;
}

__device__ __forceinline__ uint32_t clock_pin() {
  uint32_t t;
  asm volatile("mov.u32 %0, %%clock;" : "=r"(t)::"memory");
  return t;
}

struct MlpCtx {
  uint32_t sb;
  uint32_t caddr;
  uint32_t xaddr;
  uint32_t unscale;
  uint32_t peer_off;
  int wg, warp, rank, zero;
  uint8_t* optr;
};

__device__ __forceinline__ void ln_wait(const MlpCtx& m, int i) { mbar_wait(m.sb + BAR_CFULL + 8 * m.wg, i & 1); }
__device__ __forceinline__ void ln_load(const MlpCtx& m, uint32_t (&c)[24]) {
#pragma unroll
  for (int p = 0; p < 6; p++)
    asm volatile("ld.shared.v4.b32 {%0,%1,%2,%3}, [%4];"
                 : "=r"(c[4 * p]), "=r"(c[4 * p + 1]), "=r"(c[4 * p + 2]), "=r"(c[4 * p + 3])
                 : "r"(m.caddr + p * 2048)
                 : "memory");
}
__device__ __forceinline__ void ln_shfl(float (&st)[8], int mask) {
#pragma unroll
  for (int k = 0; k < 4; k++) st[4 + k] = __shfl_xor_sync(0xffffffffu, st[k], mask);
}
__device__ __forceinline__ void ln_fold(float (&st)[8]) {
#pragma unroll
  for (int k = 0; k < 4; k++) st[k] += st[4 + k];
}
__device__ __forceinline__ void ln_sums(const uint32_t (&c)[24], float (&st)[8]) {
#pragma unroll
  for (int r = 0; r < 2; r++) {
    uint32_t s0 = h_add(c[r], c[r + 2]), s1 = h_add(c[r + 4], c[r + 6]), s2 = h_add(c[r + 8], c[r + 10]);
    uint32_t s3 = h_add(c[r + 12], c[r + 14]), s4 = h_add(c[r + 16], c[r + 18]), s5 = h_add(c[r + 20], c[r + 22]);
    s0 = h_add(s0, s1); s2 = h_add(s2, s3); s4 = h_add(s4, s5);
    st[r] = h_sum(h_add(h_add(s0, s2), s4));
    uint32_t q0 = h_mul(c[r], c[r]), q1 = h_mul(c[r + 2], c[r + 2]);
#pragma unroll
    for (int p = 2; p < 12; p += 2) {
      q0 = h_fma(c[2 * p + r], c[2 * p + r], q0);
      q1 = h_fma(c[2 * p + 2 + r], c[2 * p + 2 + r], q1);
    }
    st[2 + r] = h_sum(h_add(q0, q1));
  }
}
__device__ __forceinline__ void ln_release(const MlpCtx& m) {
  const uint32_t e = m.sb + BAR_CEMPTY + 8 * (2 * m.rank + m.wg);
  asm volatile(
      "{\n.reg .pred p, q;\nelect.sync _|p, 0xffffffff;\nsetp.eq.and.s32 q, %3, 0, p;\n"
      "@q mbarrier.arrive.expect_tx.shared::cta.b64 _, [%0], %4;\n"
      "@p mbarrier.arrive.shared::cluster.b64 _, [%1];\n"
      "@p mbarrier.arrive.shared::cluster.b64 _, [%2];\n}\n" ::"r"(m.sb + BAR_CFULL + 8 * m.wg),
      "r"(e), "r"(e + m.peer_off), "r"(m.warp), "n"(CTX)
      : "memory");
}
__device__ __forceinline__ bool ln_stats(float (&st)[8]) {
  bool ok = true;
#pragma unroll
  for (int r = 0; r < 2; r++) {
    const float nm = (st[r] + st[4 + r]) * (-1.0f / 96.0f);
    const float e2 = fmaf(st[2 + r] + st[6 + r], 1.0f / 96.0f, 1e-5f);
    float rs;
    asm("rsqrt.approx.ftz.f32 %0, %1;" : "=f"(rs) : "f"(fmaf(-nm, nm, e2)));
    ok = ok && (rs * rs * e2 <= 17.0f) && (e2 >= 1.001e-5f);
    const float rr = rs * GELU_A, dd = rr * nm;
    st[r] = __uint_as_float(pack_f16(rr, rr));
    st[2 + r] = __uint_as_float(pack_f16(dd, dd));
  }
  return ok;
}
__device__ __forceinline__ void ln_restat(bool ok, const uint32_t (&c)[24], float (&st)[8], uint32_t& bad, uint32_t bit,
                                          uint32_t zero) {
  if (__builtin_expect(__any_sync(0xffffffffu, !ok), 0)) {
#pragma unroll
    for (int r = 0; r < 2; r++) {
      float nm = 0.f, var = 0.f;
#pragma unroll
      for (int p = 0; p < 12; p++) {
        nm += h_sum(c[2 * p + r] ^ zero);
        if (p % 3 == 2) { asm volatile("" : "+f"(nm)); PIN(); }
      }
      nm += __shfl_xor_sync(0xffffffffu, nm, 1);
      nm += __shfl_xor_sync(0xffffffffu, nm, 2);
      nm *= -1.0f / 96.0f;
#pragma unroll
      for (int p = 0; p < 12; p++) {
        float lo, hi;
        asm volatile("{\n.reg .b16 l, h;\nmov.b32 {l, h}, %2;\ncvt.f32.f16 %0, l;\ncvt.f32.f16 %1, h;\n}\n" : "=f"(lo), "=f"(hi) : "r"(c[2 * p + r]));
        var = fmaf(lo + nm, lo + nm, fmaf(hi + nm, hi + nm, var));
        if (p % 3 == 2) { asm volatile("" : "+f"(var)); PIN(); }
      }
      var += __shfl_xor_sync(0xffffffffu, var, 1);
      var += __shfl_xor_sync(0xffffffffu, var, 2);
      const float rr = rsqrtf(fmaf(var, 1.0f / 96.0f, 1e-5f)) * GELU_A;
      st[r] = __uint_as_float(pack_f16(rr, rr));
      const float dd = 0.5f * h_sum(__float_as_uint(st[r])) * nm;
      st[2 + r] = __uint_as_float(pack_f16(dd, dd));
      if (!(rr >= 0x1p-14f && fabsf(dd) <= 16.0f && var >= 1e-8f)) bad |= bit;
    }
  }
}
__device__ __forceinline__ void ln_apply(uint32_t (&a)[24], const uint32_t (&c)[24], const float (&st)[8]) {
#pragma unroll
  for (int p = 0; p < 24; p++) {
    a[p] = h_fma(c[p], __float_as_uint(st[p & 1]), __float_as_uint(st[2 + (p & 1)]));
  }
}

__device__ __noinline__ void slow_tile(const __nv_bfloat16* x, const __nv_bfloat16* dw, const __nv_bfloat16* w1,
                                       const __nv_bfloat16* w2, __nv_bfloat16* out, int row0, int col0, float* buf) {
  const int lane = threadIdx.x & 31;
  for (int px = 0; px < 16; px++) {
    const int row = row0 + (px >> 3), col = col0 + (px & 7);
    float c[3] = {0.f, 0.f, 0.f};
    for (int i = 0; i < 7; i++)
      for (int j = 0; j < 7; j++) {
        const int rr = row + i - 3, cc = col + j - 3;
        if (rr < 0 || rr >= IMG || cc < 0 || cc >= IMG) continue;
        for (int k = 0; k < 3; k++)
          c[k] = fmaf(__bfloat162float(x[((size_t)rr * IMG + cc) * CH + lane + 32 * k]), __bfloat162float(dw[(i * 7 + j) * CH + lane + 32 * k]), c[k]);
      }
    float mean = (c[0] + c[1] + c[2]) * (1.0f / 96.0f);
    for (int o = 16; o; o >>= 1) mean += __shfl_xor_sync(0xffffffffu, mean, o);
    float var = 0.f;
    for (int k = 0; k < 3; k++) { c[k] -= mean; var = fmaf(c[k] * (1.0f / 96.0f), c[k], var); }
    for (int o = 16; o; o >>= 1) var += __shfl_xor_sync(0xffffffffu, var, o);
    const float rs = 1.0f / sqrtf(var + 1e-5f);
    __syncwarp();
    for (int k = 0; k < 3; k++) buf[lane + 32 * k] = c[k] * rs;
    __syncwarp();
    for (int n = lane; n < 4 * CH; n += 32) {
      float y = 0.f;
      for (int k = 0; k < CH; k++) y = fmaf(buf[k], __bfloat162float(w1[k * 4 * CH + n]), y);
      buf[CH + n] = 0.5f * y * (1.0f + tanhf(0.7978845608f * (y + 0.044715f * y * y * y)));
    }
    __syncwarp();
    for (int n = lane; n < CH; n += 32) {
      float o = 0.f;
      for (int k = 0; k < 4 * CH; k++) o = fmaf(buf[CH + k], __bfloat162float(w2[k * CH + n]), o);
      const size_t idx = ((size_t)row * IMG + col) * CH + n;
      out[idx] = __float2bfloat16(__bfloat162float(x[idx]) + o);
    }
  }
}

__device__ __forceinline__ void x_load(const MlpCtx& m, uint32_t (&x)[24]) {
#pragma unroll
  for (int k = 0; k < 6; k++)
    asm volatile("ld.shared.v4.b32 {%0,%1,%2,%3}, [%4];"
                 : "=r"(x[4 * k]), "=r"(x[4 * k + 1]), "=r"(x[4 * k + 2]), "=r"(x[4 * k + 3])
                 : "r"(m.xaddr + (k / 3) * 384 + (k % 3) * 64)
                 : "memory");
}
template <int LO, int HI>
__device__ __forceinline__ void epilogue(const MlpCtx& m, const uint32_t (&d)[24], uint32_t (&x)[24]) {
#pragma unroll
  for (int k = LO; k < HI; k++) {
    const int r = k / 3, q = k % 3;
    uint32_t* y = &x[4 * k];
#pragma unroll
    for (int j = 0; j < 4; j++) {
      uint32_t v = d[2 * (4 * q + j) + r];
      float lo, hi;
      asm("{\n.reg .b16 l, h;\nmov.b32 {l, h}, %2;\ncvt.f32.f16 %0, l;\ncvt.f32.f16 %1, h;\n}\n" : "=f"(lo), "=f"(hi) : "r"(v));
      asm("fma.rn.bf16x2 %0, %1, %2, %0;" : "+r"(y[j]) : "r"(pack_bf16(lo, hi)), "r"(m.unscale));
    }
    asm volatile("st.shared.v4.b32 [%0], {%1,%2,%3,%4};" ::"r"(m.xaddr + r * 384 + q * 64), "r"(y[0]), "r"(y[1]), "r"(y[2]), "r"(y[3])
                 : "memory");
  }
}
__device__ __forceinline__ void out_store(const MlpCtx& m, int i) {
  asm volatile("fence.proxy.async.shared::cta;" ::: "memory");
  __syncwarp();
  if (elect_one()) {
    const uint32_t src = m.sb + OFF_XRES + m.wg * 12288 + m.warp * 1536;
    uint8_t* dst = m.optr + (size_t)i * (8 * IMG * CH * 2);
    asm volatile("cp.async.bulk.global.shared::cta.bulk_group [%0], [%1], 1536;" ::"l"(dst), "r"(src) : "memory");
    asm volatile("cp.async.bulk.global.shared::cta.bulk_group [%0], [%1], 1536;" ::"l"(dst + IMG * CH * 2), "r"(src + 6144) : "memory");
    asm volatile("cp.async.bulk.commit_group;" ::: "memory");
  }
}

#define FSET 3
template <int J> constexpr bool goes_first = J == FSET || J == ((FSET + 1) & 3);
template <int J> __device__ __forceinline__ void tok_wait() {
  if (goes_first<J>) NB_SYNC(NB_CLOSE, 256);
  else NB_SYNC(NB_SEC + (J & 1), 256);
}
template <int J, bool PROD = true> __device__ __forceinline__ void tok_next() {
  if (goes_first<J>) NB_ARRIVE(NB_SEC + (J & 1), 256);
  if (J == 0 && PROD) NB_ARRIVE(NB_PROD, 160);
}
__device__ __forceinline__ void tok_pass() { NB_ARRIVE(NB_OPEN, 416); }
template <int J> __device__ __forceinline__ void tok_idle() { tok_wait<J>(); tok_next<J, false>(); tok_pass(); }

constexpr uint64_t CHK = 1152;

__device__ __forceinline__ float warp_sumsq(const uint32_t (&q)[4]) {
  const uint32_t t = bf_add(bf_add(q[0], q[1]), bf_add(q[2], q[3]));
  float f = bf_lo(t) + bf_hi(t);
#pragma unroll
  for (int o = 16; o; o >>= 1) f += __shfl_xor_sync(0xffffffffu, f, o);
  return f;
}
__device__ __forceinline__ int norm_exp(float f) { return (((int)(__float_as_uint(f * 1.5f) >> 23) - 127) >> 1) + 1; }
__device__ __forceinline__ int scale_exp(int e1, int e2) { return min(11 - e1 - e2, 14 - e2); }

__device__ __forceinline__ void convert_tile(int t, int k, const uint4* w1, const uint4* w2, uint32_t st, Scratch* scr) {
  const int lane = threadIdx.x & 31, k7 = lane & 7;
  const int j = t / 6, ks = t % 6, e = ks % 3, t4 = k7 >> 1;
  const uint4* src = t < 24 ? w1 + ((e < 2 ? 64 * (ks / 3) + 8 * t4 + 4 * e : 32 + 16 * (ks / 3) + 4 * t4) + (k7 & 1)) * 48 + j * 12 + (lane >> 3)
                            : w2 + (t - 24) * 192 + (lane >> 2) * 12 + (lane & 3);
  src += (k / 3) * 96 + (k % 3) * 4;
  if (k >= 6) src = (k == 6 ? w1 : w2) + lane * 145;
  const uint4 v = __ldg(src);
  const uint32_t w[4] = {v.x, v.y, v.z, v.w};
  const uint32_t q[4] = {bf_mul(v.x, v.x), bf_mul(v.y, v.y), bf_mul(v.z, v.z), bf_mul(v.w, v.w)};
  asm volatile("st.shared.f32 [%0], %1;" ::"r"(st + 3088 + 4 * k), "f"(warp_sumsq(q)) : "memory");
  NB_SYNC(NB_PREP, 256);
  uint32_t a[4], b[4], o[4];
  lds128(a, st + 3088);
  lds128(b, st + 3104);
  const int s = max(-64, min(64, scale_exp(norm_exp(144.f * __uint_as_float(b[2])), norm_exp(144.f * __uint_as_float(b[3]))) - 1));
  const uint32_t dst = st + k7 * 16 + (lane >> 3) * 256 + (k / 3) * 128 + (k % 3) * 1024;
  if (k >= 6) {
    const float f = ((__uint_as_float(a[0]) + __uint_as_float(a[1])) + (__uint_as_float(a[2]) + __uint_as_float(a[3]))) +
                    (__uint_as_float(b[0]) + __uint_as_float(b[1]));
    asm volatile("st.shared.v2.b32 [%0], {%1,%2};" ::"r"(st + 3072), "r"(__float_as_uint(f)), "r"(s) : "memory");
  } else if (t < 24) {
#pragma unroll
    for (int i = 0; i < 4; i++) o[i] = pack_f16(bf_lo(w[i]), bf_hi(w[i]));
    asm volatile("st.shared.v4.b32 [%0], {%1,%2,%3,%4};" ::"r"(dst), "r"(o[0]), "r"(o[1]), "r"(o[2]), "r"(o[3]) : "memory");
  } else {
    constexpr float F = 0.5f / GELU_A, FHI = 1.515625f;
    const float p2 = __uint_as_float((uint32_t)(127 + s - 56) << 23);
    const uint32_t hi = pack_bf16(FHI * 0x1p-56f, FHI * 0x1p-56f), lo = pack_bf16((F - FHI) * 0x1p-56f, (F - FHI) * 0x1p-56f);
    const uint32_t pw = pack_bf16(p2, p2);
#pragma unroll
    for (int i = 0; i < 4; i++) {
      const uint32_t ws = bf_mul(w[i], pw), u = bf_fma(ws, hi, bf_mul(ws, lo));
      o[i] = (u & 0x7fff7fffu) * 7u + u;
    }
    asm volatile("stmatrix.sync.aligned.m8n8.x4.shared.b16 [%0], {%1,%2,%3,%4};" ::"r"(dst), "r"(o[0]), "r"(o[1]), "r"(o[2]), "r"(o[3])
                 : "memory");
  }
  asm volatile("fence.proxy.async.shared::cta;" ::: "memory");
  NB_SYNC(NB_PREP, 256);
  TS(4);
  if (k == 0 && elect_one()) {
    asm volatile("cp.async.bulk.global.shared::cta.bulk_group [%0], [%1], 3072;" ::"l"(scr->w + t * 192), "r"(st) : "memory");
    asm volatile("cp.async.bulk.global.shared::cta.bulk_group [%0], [%1], 16;" ::"l"(scr->nrm + t), "r"(st + 3072) : "memory");
    asm volatile("cp.async.bulk.commit_group;" ::: "memory");
    asm volatile("cp.async.bulk.wait_group 0;" ::: "memory");
    asm volatile("red.relaxed.gpu.global.add.u32 [%0], 1;" ::"l"(&scr->done) : "memory");
  }
  TS(5);
}

__device__ __forceinline__ uint32_t mlp_role(const MlpCtx& m0) {
  MlpCtx m = m0;
  uint32_t bad = 0;
  asm volatile("barrier.cluster.wait.aligned;" ::: "memory");
  if ((m.sb & 0x3FFFF) != 1024) bad = 0xffffu;
  constexpr uint64_t dW1 = (uint64_t)((1024 + OFF_W1) >> 4) | ((uint64_t)8 << 16) | ((uint64_t)16 << 32);
  constexpr uint64_t dW2 = dW1 + (OFF_W2 >> 4);
  TS(6);
  uint32_t A1[24], g[24], d[24], cn[24], D2[24];
  float st[8];
  if (m.wg & m.rank) tok_idle<3>();
  else if (m.wg) tok_idle<0>();
  else if (m.rank) tok_idle<1>();
  ln_wait(m, 0);
  ln_load(m, cn);
  ln_sums(cn, st);
  ln_shfl(st, 1);
  ln_release(m);
  ln_fold(st);
  ln_shfl(st, 2);
  ln_restat(ln_stats(st), cn, st, bad, 1, m.zero);
  ln_apply(A1, cn, st);
  {
    const int lane = threadIdx.x & 31;
    TS(2);
    mbar_wait(m.sb + BAR_W, 0);
    TS(3);
    float n1, n2;
    int s;
    asm volatile("ld.shared.b32 %0, [%1];" : "=r"(s) : "r"(m.sb + OFF_NRM + 4) : "memory");
    asm volatile("ld.shared.f32 %0, [%1];" : "=f"(n1) : "r"(m.sb + OFF_NRM + 16 * min(lane, 23)) : "memory");
    asm volatile("ld.shared.f32 %0, [%1];" : "=f"(n2) : "r"(m.sb + OFF_NRM + 384 + 16 * min(lane, 23)) : "memory");
    if (lane >= 24) n1 = n2 = 0.f;
#pragma unroll
    for (int o = 16; o; o >>= 1) {
      n1 += __shfl_xor_sync(0xffffffffu, n1, o);
      n2 += __shfl_xor_sync(0xffffffffu, n2, o);
    }
    const int e1 = norm_exp(n1), e2 = norm_exp(n2), smax = scale_exp(e1, e2);
    if (e1 > 12 || e1 < -5 || e2 > 50 || e2 < -50 || s > smax || s < smax - 5) bad = 0xffffu;
    m.unscale = __shfl_sync(0xffffffffu, ((uint32_t)(127 - s) << 7) * 0x10001u, 0);
  }
  TS(7);
  if (m.wg & m.rank) tok_idle<0>();
  if (m.wg) tok_idle<1>();
  {
    uint32_t d0[24];
    WG_FENCE();
    tok_wait<2>();
    tok_next<2>();
    gemm6<true, 192>(d0, A1, dW1);
    tok_pass(); PIN();
    WG_WAIT0(); rfence(d0);
    WG_FENCE();
    tok_wait<3>();
    tok_next<3>();
    gemm6<true, 192>(d, A1, dW1 + CHK);
    tok_pass(); PIN();
    gelu<0, 24>(g, d0);
    PIN();
    mbar_wait(m.sb + BAR_W + 8, 0);
    ln_wait(m, 1);
    WG_WAIT0(); rfence(d);
  }
#define G2(INIT, a, j)                      \
  WG_FENCE();                               \
  tok_wait<j>();                            \
  gemm6<INIT, 192>(D2, a, dW2 + (j) * CHK); \
  tok_next<j>(); PIN();                     \
  TL(ltb, (j) * 5 + 1);
#define G1(dst, j, P)                       \
  TL(ltb, ((j) ^ 2) * 5 + 2);               \
  P(); WG_WAIT0(); rfence(D2);              \
  WG_FENCE();                               \
  gemm6<true, 192>(dst, A1, dW1 + (j) * CHK); \
  tok_pass(); P();                          \
  TL(ltb, ((j) ^ 2) * 5 + 3);
#define ROUND_END(dst, j)                   \
  TL(ltb, (j) * 5 + 4);                     \
  PIN(); WG_WAIT0(); rfence(dst);
#define GA 9
#define GB 12
#define GC 13
#define GD 11
#pragma unroll 1
  for (int i = 0;; i++) {
    uint32_t g1[24], d2[24], g2[24], d3[24], g3[24], d0[24];
    ln_load(m, cn);
    PIN();
    G2(true, g, 0)
    gelu<0, GA>(g1, d);
    G1(d2, 2, PIN)
    ln_sums(cn, st);
    gelu<GA, 24>(g1, d);
    PIN();
    ln_shfl(st, 1);
    ROUND_END(d2, 0)

    G2(false, g1, 1)
    ln_fold(st);
    gelu<0, GB>(g2, d2);
    PIN();
    ln_shfl(st, 2);
    G1(d3, 3, PIN)
    const bool ok = ln_stats(st);
    gelu<GB, 24>(g2, d2);
    PIN();
    ln_restat(ok, cn, st, bad, 2u << i, m.zero);
    ROUND_END(d3, 1)

    if (i == 15) {
      G2(false, g2, 2)
      tok_pass();
      gelu<0, 24>(g3, d3);
      PIN();
      x_load(m, cn);
      ROUND_END(D2, 2)
      G2(false, g3, 3)
      tok_pass();
      WG_WAIT0(); rfence(D2);
      epilogue<0, 6>(m, D2, cn);
      break;
    }
    G2(false, g2, 2)
    ln_apply(A1, cn, st);
    PIN();
    gelu<0, GC>(g3, d3);
    G1(d0, 0, PIN)
    gelu<GC, 24>(g3, d3);
    PIN();
    x_load(m, cn);
    ROUND_END(d0, 2)

    G2(false, g3, 3)
    gelu<0, GD>(g, d0);
    G1(d, 1, PIN)
    epilogue<0, 6>(m, D2, cn);
    gelu<GD, 24>(g, d0);
    PIN();
    asm volatile("fence.proxy.async.shared::cta;" ::: "memory");
    ROUND_END(d, 3)
    TLDUMP(m.warp == 0 && (i >> 1) == LTRACE, m.sb + OFF_LT + m.wg * 160 + (i & 1) * 80, 20)
  }
  out_store(m, 15);
  if (m.wg == 0) { tok_idle<0>(); tok_idle<1>(); }
  asm volatile("cp.async.bulk.wait_group.read 0;" ::: "memory");
  return __reduce_or_sync(0xffffffffu, bad & 0xffffu);
}

struct ConvCtx {
  uint32_t sb;
  uint32_t a0, a_c;
  uint32_t peer_off;
  int rank, v, c0, r0, zero;
  const CUtensorMap* tm;
  Scratch* scr;
  const uint8_t* xsrc;
  uint8_t* optr;
};

__device__ __forceinline__ void raw_refill(const ConvCtx& c, int s) {
  if (s + 4 < NSTEP && elect_one())
    tma_raw(c.sb + OFF_RAW + (s & 3) * RAW_BYTES, c.tm, c.rank, c.c0 / 2 - 2, c.r0 - 3 + 2 * (s + 4), c.sb + BAR_RAW + 8 * (s & 3));
}
__device__ __forceinline__ void step_ready(const ConvCtx& c, int s) {
  const int nx = (s + 1) & 3, par = ((s + 1) >> 2) & 1;
  if (s + 1 < NSTEP) mbar_wait(c.sb + BAR_RAW + 8 * nx, par);
  if (s >= 7 && s < NSTEP) mbar_wait(c.sb + BAR_CEMPTY + 8 * (2 * (nx & 1) + (nx >> 1)), par);
}

__device__ __forceinline__ void c_release(const ConvCtx& c, uint32_t w) {
  const uint32_t e = c.sb + BAR_CEMPTY + 8 * (2 * c.rank + w);
  asm volatile(
      "{\n.reg .pred p;\nelect.sync _|p, 0xffffffff;\n"
      "@p mbarrier.arrive.expect_tx.shared::cta.b64 _, [%0], %3;\n"
      "@p mbarrier.arrive.shared::cluster.b64 _, [%1], 4;\n"
      "@p mbarrier.arrive.shared::cluster.b64 _, [%2], 4;\n}\n" ::"r"(c.sb + BAR_CFULL + 8 * w),
      "r"(e), "r"(e + c.peer_off), "n"(CTX)
      : "memory");
}

__device__ __forceinline__ void prod_rows(const ConvCtx& c) {
#pragma unroll 1
  for (int s = 0; s < NROUND + SIGMA + c.rank; s++) {
    const int r = s - SIGMA - c.rank;
    const int u = (r & 1) ? (r >> 1) - 1 : (r >> 1) + 2;
    step_ready(c, s);
    if (u >= ((r & 1) ? 0 : 4) && u < 32) mbar_wait(c.sb + ((r & 1) ? BAR_XFULL : BAR_CFULL) + 8 * (u & 1), (u >> 1) & 1);
    if (s < SIGMA) NB_SYNC(NB_PLAN, 160);
    else NB_SYNC(NB_OPEN, 416);
    if (r == 3) TC(c.scr, 1);
    if (r == 55) TC(c.scr, 2);
    if (r >= -1 && r < 7) TS(7 + r);
    raw_refill(c, s);
  }
}
__device__ __forceinline__ void prod_tiles(const ConvCtx& c) {
  asm volatile("barrier.cluster.wait.aligned;" ::: "memory");
#pragma unroll 1
  for (int n = 1; n < 33; n++) {
    const uint32_t w = (n + 1) & 1;
    const uint32_t buf = c.sb + OFF_XRES + w * 12288;
    NB_SYNC(NB_PROD, 160);
    if (n < 29) c_release(c, w);
    if (n >= 3) {
      uint8_t* dst = c.optr + (size_t)(n - 3) * (4 * IMG * CH * 2);
      if (elect_one()) {
        asm volatile("cp.async.bulk.global.shared::cta.bulk_group [%0], [%1], 6144;" ::"l"(dst), "r"(buf) : "memory");
        asm volatile("cp.async.bulk.global.shared::cta.bulk_group [%0], [%1], 6144;" ::"l"(dst + IMG * CH * 2), "r"(buf + 6144) : "memory");
        asm volatile("cp.async.bulk.commit_group;" ::: "memory");
        asm volatile("cp.async.bulk.wait_group.read 0;" ::: "memory");
      }
      __syncwarp();
    }
    {
      const uint8_t* src = c.xsrc + (size_t)(n - 1) * (4 * IMG * CH * 2);
      if (elect_one()) {
        mbar_expect(c.sb + BAR_XFULL + 8 * w, 12288);
        bulk_load_last(buf, src, 6144, c.sb + BAR_XFULL + 8 * w);
        bulk_load_last(buf + 6144, src + IMG * CH * 2, 6144, c.sb + BAR_XFULL + 8 * w);
      }
    }
  }
  asm volatile("cp.async.bulk.wait_group 0;" ::: "memory");
}

__device__ __forceinline__ void conv_ld8(uint32_t a0, uint32_t (&r)[6][6]) {
  const uint32_t a2 = a0 ^ (16 | ((a0 >> 2) & 32));
  const uint32_t a[3] = {a0, (a0 & 64) ? a2 : a0, a2};
#pragma unroll
  for (int j = 0; j < 6; j++)
    asm volatile("ld.shared.v4.b32 {%0,%1,%2,%3}, [%4];"
                 : "=r"(r[j][0]), "=r"(r[j][1]), "=r"(r[j][2]), "=r"(r[j][3])
                 : "r"(a[j >> 1] + (j >> 1) * 64 + (j & 1) * RAW_PA)
                 : "memory");
}
__device__ __forceinline__ void conv_ld4(uint32_t a0, uint32_t stage, int v, uint32_t (&r)[6][6]) {
  const uint32_t ab = ((a0 >> 1) & ~31u) + (stage / 2 + 2 * RAW_PA + 8 * v);
#pragma unroll
  for (int j = 0; j < 6; j++) {
    uint32_t a = ab + (j >> 1) * 32;
    asm volatile("ld.shared.v2.b32 {%0,%1}, [%2];" : "=r"(r[j][4]), "=r"(r[j][5]) : "r"(a + (j & 1) * RAW_PB) : "memory");
  }
}
template <int LO, int HI>
__device__ __forceinline__ void conv_frags(uint32_t zero, const uint32_t (&r)[6][6], uint32_t (&A)[12][4]) {
#pragma unroll
  for (int ch = LO; ch < HI; ch++) {
    const uint32_t sel = (ch & 1) ? 0x7632 : 0x5410;
    A[ch][0] = __byte_perm(r[0][ch >> 1], r[1][ch >> 1], sel);
    A[ch][1] = __byte_perm(r[2][ch >> 1], r[3][ch >> 1], sel);
    A[ch][2] = A[ch][1] ^ zero;
    A[ch][3] = __byte_perm(r[4][ch >> 1], r[5][ch >> 1], sel);
    rfence(A[ch]);
  }
}
__device__ __forceinline__ void hmma_acc(uint32_t (&v)[4], const uint32_t (&a)[4], const uint32_t* b) {
  asm volatile("mma.sync.aligned.m16n8k16.row.col.f32.bf16.bf16.f32 {%0,%1,%2,%3}, {%4,%5,%6,%7}, {%8,%9}, {%0,%1,%2,%3};"
               : "+r"(v[0]), "+r"(v[1]), "+r"(v[2]), "+r"(v[3])
               : "r"(a[0]), "r"(a[1]), "r"(a[2]), "r"(a[3]), "r"(b[0]), "r"(b[1]));
}
__device__ __forceinline__ void hmma_new(uint32_t (&a)[4], const uint32_t* b) {
  asm volatile("mma.sync.aligned.m16n8k16.row.col.f32.bf16.bf16.f32 {%0,%1,%2,%3}, {%0,%1,%2,%3}, {%4,%5}, {%6,%6,%6,%6};"
               : "+r"(a[0]), "+r"(a[1]), "+r"(a[2]), "+r"(a[3])
               : "r"(b[0]), "r"(b[1]), "f"(0.f));
}

#define EARLY 5
template <int S2, bool GATED>
__device__ __forceinline__ void conv_step(const ConvCtx& c, int s, uint32_t (&K)[12], uint32_t (&V)[12][4], const uint32_t (&B)[12][4],
                                          uint32_t (&A)[12][4]) {
  const int nx = ((s + 1) & 2) | (S2 ^ 1);
  uint32_t r[6][6];
  const uint32_t a0 = c.a0 + nx * RAW_BYTES;
  TL(ltb, 0);
  if (!GATED) TS(6 + s);
  if (GATED) NB_SYNC(NB_OPEN, 416);
  else NB_SYNC(NB_PLAN, 160);
  conv_ld4(a0, c.sb + OFF_RAW + nx * RAW_BYTES, c.v, r);
  if (GATED) PIN();
  TL(ltb, 1);
#pragma unroll
  for (int ch = 0; ch < 12; ch++) hmma_acc(V[11 - ch], A[11 - ch], &B[11 - ch][2]);
#pragma unroll
  for (int ch = 0; ch < 12 - EARLY; ch++) hmma_new(A[ch], &B[ch][0]);
  const uint32_t zero = GATED ? c.zero & clock_pin() : c.zero;
  if (GATED) NB_ARRIVE(NB_CLOSE, 256);
#pragma unroll
  for (int ch = 12 - EARLY; ch < 12; ch++) hmma_new(A[ch], &B[ch][0]);
  if (GATED) PIN();
  TL(ltb, 2);
  const uint32_t off = ((S2 ^ 1) == c.rank) ? 0u : c.peer_off;
  const uint32_t dst = c.a_c + (GATED || s >= 3 ? off + (nx >> 1) * C_BYTES : OFF_XRES + 12288 - OFF_C);
  const uint32_t bar = c.sb + (GATED || s >= 3 ? off + BAR_CFULL + 8 * (nx >> 1) : BAR_W + 56);
#pragma unroll
  for (int q = 0; q < 12; q++) {
    const int ch = q & ~1, h = 2 * (q & 1);
    asm("add.rn.f16x2 %0, %0, %1;" : "+r"(K[q]) : "r"(pack_f16(__uint_as_float(V[ch][h + 1]), __uint_as_float(V[ch + 1][h]))));
  }
  if ((S2 ^ 1) == c.rank) {
#pragma unroll
    for (int q = 0; q < 3; q++)
      asm volatile("st.shared.v4.b32 [%0], {%1,%2,%3,%4};" ::"r"(dst + q * 2048), "r"(K[4 * q]), "r"(K[4 * q + 1]), "r"(K[4 * q + 2]), "r"(K[4 * q + 3])
                   : "memory");
    asm volatile("{\n.reg .pred p;\nelect.sync _|p, 0xffffffff;\n@p mbarrier.arrive.shared::cta.b64 _, [%0];\n}\n" ::"r"(bar) : "memory");
  } else {
#pragma unroll
  for (int q = 0; q < 3; q++)
    asm volatile("st.async.weak.shared::cluster.mbarrier::complete_tx::bytes.v4.b32 [%0], {%1,%2,%3,%4}, [%5];" ::"r"(dst + q * 2048),
                 "r"(K[4 * q]), "r"(K[4 * q + 1]), "r"(K[4 * q + 2]), "r"(K[4 * q + 3]), "r"(bar)
                 : "memory");
  }
  PIN();
#pragma unroll
  for (int q = 0; q < 12; q++) {
    const int ch = q & ~1, h = 2 * (q & 1);
    K[q] = pack_f16(__uint_as_float(V[ch][h]), __uint_as_float(V[ch + 1][h + 1]));
  }
  rfence(K);
  conv_frags<8, 12>(zero, r, V);
  PIN();
  conv_ld8(a0, r);
  conv_frags<0, 8>(zero, r, V);
  PIN();
  TL(ltb, 4);
  TLDUMP(c.v == 0 && lr >= 0 && lr < 10, c.sb + OFF_LT + 320 + lr * 20, 5)
}

__device__ __forceinline__ void conv_role(ConvCtx c) {
  const int lane = laneid(), g = lane >> 2, t = lane & 3;
  const int u = (t >> 1) * 19 + 2 * (g + (t & 1));
  c.a0 = c.sb + OFF_RAW + u * 64 + ((c.v ^ (u >> 1)) & 3) * 16;
  c.a_c = c.sb + OFF_C + 6144 * c.rank + 512 * c.v + ((lane + 2 * c.v) & 31) * 16;
  uint32_t B[12][4];
  {
    const int dc = (g >> 1) & 1, ro = g >> 2, rk = t >> 1;
    const int i0 = 4 * (g & 1) + rk - ro, j0 = 4 * (t & 1) - dc;
    const uint32_t base = c.sb + OFF_XRES + (i0 * 7 + j0) * 192;
    TS(2);
    asm volatile("barrier.cluster.wait.aligned;" ::: "memory");
    mbar_wait(c.sb + BAR_W + 48, 0);
    TS(3);
#pragma unroll
    for (int b = 0; b < 2; b++) {
      uint32_t w[4][6];
#pragma unroll
      for (int k = 0; k < 4; k++) {
        const int ok = (unsigned)(i0 + 2 * b) < 7u && (unsigned)(j0 + k) < 7u;
#pragma unroll
        for (int q = 0; q < 6; q++) w[k][q] = 0;
        asm volatile(
            "{\n.reg .pred p;\nsetp.ne.s32 p, %8, 0;\n@p ld.shared.v4.b32 {%0,%1,%2,%3}, [%6];\n@p ld.shared.v2.b32 {%4,%5}, [%7];\n}\n"
            : "+r"(w[k][0]), "+r"(w[k][1]), "+r"(w[k][2]), "+r"(w[k][3]), "+r"(w[k][4]), "+r"(w[k][5])
            : "r"(base + (b * 14 + k) * 192 + 128 * c.rank + 16 * c.v), "r"(base + (b * 14 + k) * 192 + 64 + 32 * c.rank + 8 * c.v), "r"(ok)
            : "memory");
      }
#pragma unroll
      for (int q = 0; q < 6; q++) {
        B[2 * q][2 * b] = __byte_perm(w[0][q], w[1][q], 0x5410);
        B[2 * q][2 * b + 1] = __byte_perm(w[2][q], w[3][q], 0x5410);
        B[2 * q + 1][2 * b] = __shfl_xor_sync(0xffffffffu, __byte_perm(w[0][q], w[1][q], 0x7632), 4);
        B[2 * q + 1][2 * b + 1] = __shfl_xor_sync(0xffffffffu, __byte_perm(w[2][q], w[3][q], 0x7632), 4);
      }
    }
  }
  TS(4);
  uint32_t K1[12], K2[12], V[12][4];
#pragma unroll
  for (int ch = 0; ch < 12; ch++) {
    K1[ch] = K2[ch] = 0;
#pragma unroll
    for (int k = 0; k < 4; k++) V[ch][k] = 0;
  }
  uint32_t A[12][4], r[6][6];
  mbar_wait(c.sb + BAR_RAW, 0);
  TS(5);
  conv_ld8(c.a0, r);
  conv_ld4(c.a0, c.sb + OFF_RAW, c.v, r);
  conv_frags<0, 12>(c.zero, r, A);
  PIN();
  NB_ARRIVE(NB_CLOSE, 256);
#pragma unroll 1
  for (int s = 0; s < SIGMA; s += 2) {
    conv_step<0, false>(c, s, K1, V, B, A);
    conv_step<1, false>(c, s + 1, K2, A, B, V);
  }
#pragma unroll 1
  for (int s = SIGMA;; s += 2) {
    conv_step<0, true>(c, s, K1, V, B, A);
    if (s == NSTEP - 1) break;
    conv_step<1, true>(c, s + 1, K2, A, B, V);
  }
#pragma unroll 1
  for (int r = NSTEP - SIGMA - c.rank; r < NROUND - 1; r++) {
    NB_SYNC(NB_OPEN, 416);
    NB_ARRIVE(NB_CLOSE, 256);
  }
  NB_SYNC(NB_OPEN, 416);
}

struct TMaps { CUtensorMap m[2]; };
__device__ __forceinline__ Scratch* scr_param() {
  extern __shared__ __align__(1024) uint8_t smem[];
  return *reinterpret_cast<Scratch* volatile*>(smem + OFF_LT + 592);
}

__global__ void __cluster_dims__(2, 1, 1) __launch_bounds__(512, 1)
convnext_kernel(const __grid_constant__ TMaps tms, const __nv_bfloat16* __restrict__ x, const __nv_bfloat16* __restrict__ dw,
                const __nv_bfloat16* __restrict__ w1, const __nv_bfloat16* __restrict__ w2, __nv_bfloat16* __restrict__ out,
                Scratch* scr, int zero) {
  extern __shared__ __align__(1024) uint8_t smem[];
  const uint32_t sb = (uint32_t)__cvta_generic_to_shared(smem);
  const int tid = threadIdx.x, lane = tid & 31;
  const int wid = __shfl_sync(0xffffffffu, tid >> 5, 0);
  const int rank = blockIdx.x & 1, cl = blockIdx.x >> 1;
  const int c0 = (cl & 15) * 32, r0 = (cl >> 4) * 128;
  const uint32_t peer_off = mapa(sb, rank ^ 1) - sb;

  TS(0);
  if (wid == 12 && elect_one()) {
    mbar_init(sb + BAR_W + 48, 1);
#pragma unroll
    for (int i = 0; i < 4; i++) mbar_init(sb + BAR_RAW + 8 * i, 1);
    asm volatile("fence.mbarrier_init.release.cluster;" ::: "memory");
    mbar_expect(sb + BAR_W + 48, 49 * CH * 2);
    bulk_load(sb + OFF_XRES, dw, 49 * CH * 2, sb + BAR_W + 48);
#pragma unroll
    for (int i = 0; i < E0; i++) tma_raw(sb + OFF_RAW + i * RAW_BYTES, tms.m, rank, c0 / 2 - 2, r0 - 3 + 2 * i, sb + BAR_RAW + 8 * i);
  }
  if (wid == 14 && elect_one()) {
    asm volatile("prefetch.tensormap [%0];" ::"l"(&tms.m[1]) : "memory");
#pragma unroll
    for (int i = 0; i < 3; i++) mbar_init(sb + BAR_W + 8 * i, 1);
    mbar_init(sb + BAR_W + 56, 100);
#pragma unroll
    for (int i = 0; i < 2; i++) mbar_init(sb + BAR_CFULL + 8 * i, CCNT);
#pragma unroll
    for (int i = 0; i < 4; i++) mbar_init(sb + BAR_CEMPTY + 8 * i, 4);
#pragma unroll
    for (int i = 0; i < 2; i++) mbar_init(sb + BAR_XFULL + 8 * i, 1);
#pragma unroll
    for (int i = 0; i < 2; i++) mbar_expect(sb + BAR_CFULL + 8 * i, CTX);
    asm volatile("fence.mbarrier_init.release.cluster;" ::: "memory");
  }
  __syncwarp();
  asm volatile("barrier.cluster.arrive.relaxed.aligned;" ::: "memory");

  TS(1);
  if (wid < 8) {
    if (blockIdx.x < 48) convert_tile(blockIdx.x, wid, reinterpret_cast<const uint4*>(w1), reinterpret_cast<const uint4*>(w2), sb, scr);
    MlpCtx m;
    m.sb = sb; m.wg = wid >> 2; m.warp = wid & 3; m.rank = rank; m.peer_off = peer_off; m.zero = zero;
    m.optr = reinterpret_cast<uint8_t*>(out) + ((size_t)(r0 + 4 * m.wg + 2 * rank) * IMG + c0 + 8 * m.warp) * (CH * 2);
    m.caddr = sb + OFF_C + m.wg * C_BYTES + (lane & 3) * 512 + ((m.warp * 8 + (lane >> 2) + 2 * (lane & 3)) & 31) * 16;
    m.xaddr = sb + OFF_XRES + m.wg * 12288 + m.warp * 1536 + ((lane >> 3) & 1) * 6144 + ((lane >> 4) * 4 + ((lane >> 2) & 1)) * 192 + (lane & 3) * 16;
    m.unscale = 0;
    asm volatile("setmaxnreg.inc.sync.aligned.u32 %0;" ::"n"(REG_MLP));
    const uint32_t bad = mlp_role(m);
    TC(scr, 3);
    if (bad) {
      asm volatile("cp.async.bulk.wait_group 0;" ::: "memory");
      mbar_wait(sb + BAR_W + 16, 0);
      __syncwarp();
      asm volatile("fence.proxy.async;" ::: "memory");
#pragma unroll 1
      for (int i = 0; i < 16; i++)
        if (bad >> i & 1)
          slow_tile(x, dw, w1, w2, out, r0 + 8 * i + 4 * m.wg + 2 * rank, c0 + 8 * m.warp,
                    reinterpret_cast<float*>(smem + OFF_RAW + wid * 2048));
    }
  } else {
    ConvCtx c;
    c.sb = sb; c.rank = rank; c.v = wid - 8; c.c0 = c0; c.r0 = r0; c.zero = zero; c.tm = tms.m; c.scr = scr;
    c.peer_off = peer_off;
    c.xsrc = reinterpret_cast<const uint8_t*>(x) + ((size_t)(r0 + 2 * rank) * IMG + c0) * (CH * 2);
    c.optr = reinterpret_cast<uint8_t*>(out) + ((size_t)(r0 + 2 * rank) * IMG + c0) * (CH * 2);
    if (wid < 12) {
      asm volatile("setmaxnreg.inc.sync.aligned.u32 %0;" ::"n"(REG_CONV));
      conv_role(c);
    } else {
      asm volatile("setmaxnreg.dec.sync.aligned.u32 24;");
      if (wid == 15) TC(scr, 0);
      if (wid == 12) {
        TS(2);
#pragma unroll 1
        for (int h = E0 - 4; h < 0; h++) raw_refill(c, h);
        TS(3);
        asm volatile("barrier.cluster.wait.aligned;" ::: "memory");
        prod_rows(c);
      } else if (wid == 14) {
#pragma unroll 1
        for (int n = 0; n < (1 << 20); n++) {
          unsigned v;
          __nanosleep(n ? PSL : PS0);
          asm volatile("ld.acquire.gpu.global.u32 %0, [%1];" : "=r"(v) : "l"(&scr->done) : "memory");
          if (__shfl_sync(0xffffffffu, v, 0) >= 48) break;
        }
        asm volatile("barrier.cluster.wait.aligned;" ::: "memory");
        asm volatile("fence.proxy.async.global;" ::: "memory");
        if (elect_one()) {
          mbar_expect(sb + BAR_W, 36864 + 768);
          mbar_expect(sb + BAR_W + 8, 110592);
          bulk_load(sb + OFF_NRM, scr->nrm, 768, sb + BAR_W);
          if (atomicAdd(&scr->seen, 1u) == gridDim.x - 1) { scr->done = 0; scr->seen = 0; }
        }
        __syncwarp();
#pragma unroll 1
        for (int i = 0; i < 8; i++) {
          if (elect_one()) bulk_load(sb + i * 18432, reinterpret_cast<const uint8_t*>(scr->w) + i * 18432, 18432, sb + BAR_W + (i < 2 ? 0 : 8));
          __nanosleep(PACE);
        }
      } else if (wid == 13) {
        prod_tiles(c);
        __syncwarp();
        if (elect_one()) asm volatile("mbarrier.arrive.shared::cta.b64 _, [%0];" ::"r"(sb + BAR_W + 16) : "memory");
      }
    }
  }
}

typedef CUresult (*EncodeFn)(CUtensorMap*, CUtensorMapDataType, cuuint32_t, void*, const cuuint64_t*, const cuuint64_t*,
                             const cuuint32_t*, const cuuint32_t*, CUtensorMapInterleave, CUtensorMapSwizzle,
                             CUtensorMapL2promotion, CUtensorMapFloatOOBfill);

}

extern "C" void kernel_launch(void* const* d_in, const int* in_sizes, int n_in, void* d_out, int out_size) {
  const __nv_bfloat16* x = (const __nv_bfloat16*)d_in[0];
  const __nv_bfloat16* dw = (const __nv_bfloat16*)d_in[1];
  const __nv_bfloat16* w1 = (const __nv_bfloat16*)d_in[2];
  const __nv_bfloat16* w2 = (const __nv_bfloat16*)d_in[3];
  __nv_bfloat16* out = (__nv_bfloat16*)d_out;

  static EncodeFn encode = nullptr;
  static Scratch* scr = nullptr;
  if (!encode) {
    cudaDriverEntryPointQueryResult st;
    void* fn = nullptr;
    cudaGetDriverEntryPoint("cuTensorMapEncodeTiled", &fn, cudaEnableDefault, &st);
    encode = (EncodeFn)fn;
    cudaGetSymbolAddress((void**)&scr, g_scratch);
    cudaFuncSetAttribute(convnext_kernel, cudaFuncAttributeMaxDynamicSharedMemorySize, SMEM_BYTES);
  }
  TMaps tm;
  cuuint64_t dims[4] = {CH, IMG / 2, IMG, 2};
  cuuint64_t strides[3] = {CH * 4, (cuuint64_t)IMG * CH * 2, CH * 2};
  cuuint32_t es[4] = {1, 1, 1, 1};
  for (int i = 0; i < 2; i++) {
    cuuint32_t box[4] = {i ? 16u : 32u, 19, 2, 1};
    encode(&tm.m[i], CU_TENSOR_MAP_DATA_TYPE_BFLOAT16, 4, (void*)x, dims, strides, box, es, CU_TENSOR_MAP_INTERLEAVE_NONE,
           i ? CU_TENSOR_MAP_SWIZZLE_NONE : CU_TENSOR_MAP_SWIZZLE_64B, PROMO, CU_TENSOR_MAP_FLOAT_OOB_FILL_NONE);
  }
  convnext_kernel<<<128, 512, SMEM_BYTES>>>(tm, x, dw, w1, w2, out, scr, 0);
}
```

```cpp
#include <cuda_runtime.h>
#include <cuda_bf16.h>
#include <cuda.h>
#include <stdint.h>

#define PROMO CU_TENSOR_MAP_L2_PROMOTION_L2_128B
#define CTX 6144
#define CCNT 5
#define PSL 100
#define PS0 1000
#define E0 1
#define PACE 100
namespace {

constexpr int IMG = 512, CH = 96;
constexpr int NSTEP = 67;
constexpr int SIGMA = 8;
constexpr int NROUND = 68;

constexpr uint32_t OFF_W1 = 0;
constexpr uint32_t OFF_W2 = 73728;
constexpr uint32_t OFF_RAW = 147456;
constexpr uint32_t RAW_PA = 2560, RAW_PB = 1280;
constexpr uint32_t RAW_BYTES = 2 * RAW_PA + 2 * RAW_PB;
constexpr uint32_t RAW_TX = 2 * 38 * 96;
constexpr uint32_t OFF_XRES = OFF_RAW + 4 * RAW_BYTES;
constexpr uint32_t OFF_C = OFF_XRES + 2 * 12288;
constexpr uint32_t C_BYTES = 12288;
constexpr uint32_t OFF_BAR = OFF_C + 2 * C_BYTES;
constexpr uint32_t BAR_RAW = OFF_BAR;
constexpr uint32_t BAR_CFULL = OFF_BAR + 32;
constexpr uint32_t BAR_CEMPTY = OFF_BAR + 48;
constexpr uint32_t BAR_XFULL = OFF_BAR + 80;
constexpr uint32_t BAR_W = OFF_BAR + 96;
constexpr uint32_t OFF_NRM = OFF_XRES + 9472;
constexpr uint32_t OFF_LT = OFF_BAR + 160;
constexpr uint32_t SMEM_BYTES = OFF_BAR + 160 + 600;

struct Scratch {
  uint4 w[2 * 73728 / 16];
  uint4 nrm[48];
  unsigned done, seen;
};
__device__ Scratch g_scratch;

constexpr float GELU_A = 0.32918364f;
constexpr uint32_t GELU_K2 = 0x40d940d9u;

constexpr int NB_CLOSE = 1, NB_SEC = 6  , NB_OPEN = 3, NB_PROD = 2, NB_PLAN = 4, NB_PREP = 5, NB_WG = 8  ;
#define REG_MLP 144
constexpr int REG_CONV = 488 - 2 * REG_MLP;

#define WG_FENCE() asm volatile("wgmma.fence.sync.aligned;" ::: "memory")
#define WG_COMMIT() asm volatile("wgmma.commit_group.sync.aligned;" ::: "memory")
#define WG_WAIT0() asm volatile("wgmma.wait_group.sync.aligned 0;" ::: "memory")
#define WG_WAIT1() asm volatile("wgmma.wait_group.sync.aligned 1;" ::: "memory")
#define PIN() asm volatile("pmevent 0;" ::: "memory")
#define NB_SYNC(id, n) asm volatile("bar.sync %0, %1;" ::"n"(id), "n"(n) : "memory")
#define NB_ARRIVE(id, n) asm volatile("bar.arrive %0, %1;" ::"n"(id), "n"(n) : "memory")

#define SCR (scr_param())
__device__ __forceinline__ Scratch* scr_param();
#define TS(idx)
#define TC(scr, k)
#define TL(base, off)
#define TLDUMP(cond, base, n)

#define R24(c, d)                                                                                        \
  c(d[0]), c(d[1]), c(d[2]), c(d[3]), c(d[4]), c(d[5]), c(d[6]), c(d[7]), c(d[8]), c(d[9]), c(d[10]),    \
      c(d[11]), c(d[12]), c(d[13]), c(d[14]), c(d[15]), c(d[16]), c(d[17]), c(d[18]), c(d[19]), c(d[20]), \
      c(d[21]), c(d[22]), c(d[23])
#define WG_TXT(sd)                                                                             \
  "wgmma.mma_async.sync.aligned.m64n96k16.f16.f16.f16 "                                        \
  "{%0,%1,%2,%3,%4,%5,%6,%7,%8,%9,%10,%11,%12,%13,%14,%15,%16,%17,%18,%19,%20,%21,%22,%23}, " \
  "{%24,%25,%26,%27}, %28, " sd ", 1, 1, 1;\n"

__device__ __forceinline__ void wg_acc(uint32_t (&d)[24], const uint32_t* a, uint64_t db) {
  asm volatile(WG_TXT("1") : R24("+r", d) : "r"(a[0]), "r"(a[1]), "r"(a[2]), "r"(a[3]), "l"(db));
}
__device__ __forceinline__ void wg_init(uint32_t (&d)[24], const uint32_t* a, uint64_t db) {
  asm volatile(WG_TXT("0") : R24("=r", d) : "r"(a[0]), "r"(a[1]), "r"(a[2]), "r"(a[3]), "l"(db));
}
template <int N>
__device__ __forceinline__ void rfence(uint32_t (&d)[N]) {
#pragma unroll
  for (int i = 0; i < N; i++) asm volatile("" : "+r"(d[i])::"memory");
}
template <bool INIT, int KSTRIDE>
__device__ __forceinline__ void gemm6(uint32_t (&d)[24], const uint32_t (&a)[24], uint64_t db) {
#pragma unroll
  for (int k = 0; k < 6; k++) {
    if (INIT && k == 0) wg_init(d, &a[0], db);
    else wg_acc(d, &a[4 * k], db + k * KSTRIDE);
  }
  WG_COMMIT();
}

__device__ __forceinline__ void mbar_init(uint32_t bar, uint32_t cnt) {
  asm volatile("mbarrier.init.shared::cta.b64 [%0], %1;" ::"r"(bar), "r"(cnt) : "memory");
}
__device__ __forceinline__ void mbar_expect(uint32_t bar, uint32_t bytes) {
  asm volatile("mbarrier.arrive.expect_tx.shared::cta.b64 _, [%0], %1;" ::"r"(bar), "r"(bytes) : "memory");
}
__device__ __forceinline__ void mbar_arrive_cluster(uint32_t bar) {
  asm volatile("mbarrier.arrive.shared::cluster.b64 _, [%0];" ::"r"(bar) : "memory");
}
__device__ __forceinline__ bool mbar_try(uint32_t bar, uint32_t parity) {
  uint32_t ok;
  asm volatile(
      "{\n.reg .pred p;\nmbarrier.try_wait.parity.shared::cta.b64 p, [%1], %2;\nselp.u32 %0, 1, 0, p;\n}\n"
      : "=r"(ok)
      : "r"(bar), "r"(parity)
      : "memory");
  return ok;
}
__device__ __forceinline__ bool mbar_test(uint32_t bar, uint32_t parity) {
  uint32_t ok;
  asm volatile(
      "{\n.reg .pred p;\nmbarrier.test_wait.parity.shared::cta.b64 p, [%1], %2;\nselp.u32 %0, 1, 0, p;\n}\n"
      : "=r"(ok)
      : "r"(bar), "r"(parity)
      : "memory");
  return ok;
}
__device__ __forceinline__ void mbar_wait(uint32_t bar, uint32_t parity) {
  if (__builtin_expect(mbar_try(bar, parity), 1)) return;
#pragma unroll 1
  for (uint32_t n = 0; n < (1u << 16) && !mbar_try(bar, parity); n++) {}
}
__device__ __forceinline__ uint32_t mapa(uint32_t addr, uint32_t rank) {
  uint32_t r;
  asm("mapa.shared::cluster.u32 %0, %1, %2;" : "=r"(r) : "r"(addr), "r"(rank));
  return r;
}
__device__ __forceinline__ void tma_raw(uint32_t dst, const CUtensorMap* tm, int rank, int w2, int h, uint32_t bar) {
  mbar_expect(bar, RAW_TX);
#pragma unroll
  for (int k = 0; k < 4; k++) {
    const int e = k & 1;
    asm volatile(
        "cp.async.bulk.tensor.4d.shared::cluster.global.mbarrier::complete_tx::bytes [%0], [%1, {%2, %3, %4, %5}], [%6];"
        ::"r"(dst + (k < 2 ? e * RAW_PA : 2 * RAW_PA + e * RAW_PB)), "l"(tm + (k >> 1)), "r"(k < 2 ? 64 * rank : 32 + 16 * rank), "r"(w2 + e),
        "r"(h), "r"(1 - e), "r"(bar)
        : "memory");
  }
}
__device__ __forceinline__ void bulk_load(uint32_t dst, const void* src, uint32_t bytes, uint32_t bar) {
  asm volatile("cp.async.bulk.shared::cluster.global.mbarrier::complete_tx::bytes [%0], [%1], %2, [%3];" ::"r"(dst),
               "l"(src), "r"(bytes), "r"(bar)
               : "memory");
}
__device__ __forceinline__ void bulk_load_last(uint32_t dst, const void* src, uint32_t bytes, uint32_t bar) {
  asm volatile(
      "{\n.reg .b64 pol;\ncreatepolicy.fractional.L2::evict_first.b64 pol, 1.0;\n"
      "cp.async.bulk.shared::cluster.global.mbarrier::complete_tx::bytes.L2::cache_hint [%0], [%1], %2, [%3], pol;\n}\n" ::"r"(dst),
      "l"(src), "r"(bytes), "r"(bar)
      : "memory");
}
__device__ __forceinline__ uint32_t pack_bf16(float lo, float hi) {
  uint32_t r;
  asm("cvt.rn.bf16x2.f32 %0, %1, %2;" : "=r"(r) : "f"(hi), "f"(lo));
  return r;
}
__device__ __forceinline__ uint32_t pack_f16(float lo, float hi) {
  uint32_t r;
  asm("cvt.rn.f16x2.f32 %0, %1, %2;" : "=r"(r) : "f"(hi), "f"(lo));
  return r;
}
__device__ __forceinline__ float bf_lo(uint32_t v) { return __uint_as_float(v << 16); }
__device__ __forceinline__ float bf_hi(uint32_t v) { return __uint_as_float(v & 0xffff0000u); }
__device__ __forceinline__ uint32_t bf_add(uint32_t a, uint32_t b) {
  uint32_t r;
  asm("add.rn.bf16x2 %0, %1, %2;" : "=r"(r) : "r"(a), "r"(b));
  return r;
}
__device__ __forceinline__ uint32_t bf_mul(uint32_t a, uint32_t b) {
  uint32_t r;
  asm("mul.rn.bf16x2 %0, %1, %2;" : "=r"(r) : "r"(a), "r"(b));
  return r;
}
__device__ __forceinline__ uint32_t bf_fma(uint32_t a, uint32_t b, uint32_t c) {
  uint32_t r;
  asm("fma.rn.bf16x2 %0, %1, %2, %3;" : "=r"(r) : "r"(a), "r"(b), "r"(c));
  return r;
}

__device__ __forceinline__ uint32_t h_add(uint32_t a, uint32_t b) {
  uint32_t r;
  asm("add.rn.f16x2 %0, %1, %2;" : "=r"(r) : "r"(a), "r"(b));
  return r;
}
__device__ __forceinline__ uint32_t h_mul(uint32_t a, uint32_t b) {
  uint32_t r;
  asm("mul.rn.f16x2 %0, %1, %2;" : "=r"(r) : "r"(a), "r"(b));
  return r;
}
__device__ __forceinline__ uint32_t h_fma(uint32_t a, uint32_t b, uint32_t c) {
  uint32_t r;
  asm("fma.rn.f16x2 %0, %1, %2, %3;" : "=r"(r) : "r"(a), "r"(b), "r"(c));
  return r;
}
__device__ __forceinline__ float h_sum(uint32_t v) {
  float lo, hi;
  asm("{\n.reg .b16 l, h;\nmov.b32 {l, h}, %2;\ncvt.f32.f16 %0, l;\ncvt.f32.f16 %1, h;\n}\n" : "=f"(lo), "=f"(hi) : "r"(v));
  return lo + hi;
}
__device__ __forceinline__ void lds128(uint32_t (&v)[4], uint32_t a) {
  asm volatile("ld.shared.v4.b32 {%0,%1,%2,%3}, [%4];" : "=r"(v[0]), "=r"(v[1]), "=r"(v[2]), "=r"(v[3]) : "r"(a) : "memory");
}

template <int LO, int HI>
__device__ __forceinline__ void gelu(uint32_t (&o)[24], const uint32_t (&d)[24]) {
#pragma unroll
  for (int qq = LO; qq < HI; qq++) {
    const int q = (qq + 4) % 24;
    uint32_t t, u;
    asm("fma.rn.f16x2 %0, %1, %1, %2;" : "=r"(t) : "r"(d[q]), "r"(GELU_K2));
    asm("mul.rn.f16x2 %0, %1, %2;" : "=r"(u) : "r"(d[q]), "r"(t));
    asm("tanh.approx.f16x2 %0, %1;" : "=r"(t) : "r"(u));
    asm("fma.rn.f16x2 %0, %1, %2, %1;" : "=r"(o[q]) : "r"(d[q]), "r"(t));
  }
}

__device__ __forceinline__ uint32_t laneid() {
  uint32_t l;
  asm volatile("mov.u32 %0, %%laneid;" : "=r"(l));
  return l;
}

__device__ __forceinline__ bool elect_one() {
  uint32_t p;
  asm volatile("{\n.reg .pred p;\nelect.sync _|p, 0xffffffff;\nselp.u32 %0, 1, 0, p;\n}\n" : "=r"(p));
  return p;
}

__device__ __forceinline__ uint32_t clock_pin() {
  uint32_t t;
  asm volatile("mov.u32 %0, %%clock;" : "=r"(t)::"memory");
  return t;
}

struct MlpCtx {
  uint32_t sb;
  uint32_t caddr;
  uint32_t xaddr;
  uint32_t unscale;
  uint32_t peer_off;
  int wg, warp, rank, zero;
  uint8_t* optr;
};

__device__ __forceinline__ void ln_wait(const MlpCtx& m, int i) { mbar_wait(m.sb + BAR_CFULL + 8 * m.wg, i & 1); }
__device__ __forceinline__ void ln_load(const MlpCtx& m, uint32_t (&c)[24]) {
#pragma unroll
  for (int p = 0; p < 6; p++)
    asm volatile("ld.shared.v4.b32 {%0,%1,%2,%3}, [%4];"
                 : "=r"(c[4 * p]), "=r"(c[4 * p + 1]), "=r"(c[4 * p + 2]), "=r"(c[4 * p + 3])
                 : "r"(m.caddr + p * 2048)
                 : "memory");
}
__device__ __forceinline__ void ln_shfl(float (&st)[8], int mask) {
#pragma unroll
  for (int k = 0; k < 4; k++) st[4 + k] = __shfl_xor_sync(0xffffffffu, st[k], mask);
}
__device__ __forceinline__ void ln_fold(float (&st)[8]) {
#pragma unroll
  for (int k = 0; k < 4; k++) st[k] += st[4 + k];
}
__device__ __forceinline__ void ln_sums(const uint32_t (&c)[24], float (&st)[8]) {
#pragma unroll
  for (int r = 0; r < 2; r++) {
    uint32_t s0 = h_add(c[r], c[r + 2]), s1 = h_add(c[r + 4], c[r + 6]), s2 = h_add(c[r + 8], c[r + 10]);
    uint32_t s3 = h_add(c[r + 12], c[r + 14]), s4 = h_add(c[r + 16], c[r + 18]), s5 = h_add(c[r + 20], c[r + 22]);
    s0 = h_add(s0, s1); s2 = h_add(s2, s3); s4 = h_add(s4, s5);
    st[r] = h_sum(h_add(h_add(s0, s2), s4));
    uint32_t q0 = h_mul(c[r], c[r]), q1 = h_mul(c[r + 2], c[r + 2]);
#pragma unroll
    for (int p = 2; p < 12; p += 2) {
      q0 = h_fma(c[2 * p + r], c[2 * p + r], q0);
      q1 = h_fma(c[2 * p + 2 + r], c[2 * p + 2 + r], q1);
    }
    st[2 + r] = h_sum(h_add(q0, q1));
  }
}
__device__ __forceinline__ void ln_release(const MlpCtx& m) {
  const uint32_t e = m.sb + BAR_CEMPTY + 8 * (2 * m.rank + m.wg);
  asm volatile(
      "{\n.reg .pred p, q;\nelect.sync _|p, 0xffffffff;\nsetp.eq.and.s32 q, %3, 0, p;\n"
      "@q mbarrier.arrive.expect_tx.shared::cta.b64 _, [%0], %4;\n"
      "@p mbarrier.arrive.shared::cluster.b64 _, [%1];\n"
      "@p mbarrier.arrive.shared::cluster.b64 _, [%2];\n}\n" ::"r"(m.sb + BAR_CFULL + 8 * m.wg),
      "r"(e), "r"(e + m.peer_off), "r"(m.warp), "n"(CTX)
      : "memory");
}
__device__ __forceinline__ bool ln_stats(float (&st)[8]) {
  bool ok = true;
#pragma unroll
  for (int r = 0; r < 2; r++) {
    const float nm = (st[r] + st[4 + r]) * (-1.0f / 96.0f);
    const float e2 = fmaf(st[2 + r] + st[6 + r], 1.0f / 96.0f, 1e-5f);
    float rs;
    asm("rsqrt.approx.ftz.f32 %0, %1;" : "=f"(rs) : "f"(fmaf(-nm, nm, e2)));
    ok = ok && (rs * rs * e2 <= 17.0f) && (e2 >= 1.001e-5f);
    const float rr = rs * GELU_A, dd = rr * nm;
    st[r] = __uint_as_float(pack_f16(rr, rr));
    st[2 + r] = __uint_as_float(pack_f16(dd, dd));
  }
  return ok;
}
__device__ __forceinline__ void ln_restat(bool ok, const uint32_t (&c)[24], float (&st)[8], uint32_t& bad, uint32_t bit,
                                          uint32_t zero) {
  if (__builtin_expect(__any_sync(0xffffffffu, !ok), 0)) {
#pragma unroll
    for (int r = 0; r < 2; r++) {
      float nm = 0.f, var = 0.f;
#pragma unroll
      for (int p = 0; p < 12; p++) {
        nm += h_sum(c[2 * p + r] ^ zero);
        if (p % 3 == 2) { asm volatile("" : "+f"(nm)); PIN(); }
      }
      nm += __shfl_xor_sync(0xffffffffu, nm, 1);
      nm += __shfl_xor_sync(0xffffffffu, nm, 2);
      nm *= -1.0f / 96.0f;
#pragma unroll
      for (int p = 0; p < 12; p++) {
        float lo, hi;
        asm volatile("{\n.reg .b16 l, h;\nmov.b32 {l, h}, %2;\ncvt.f32.f16 %0, l;\ncvt.f32.f16 %1, h;\n}\n" : "=f"(lo), "=f"(hi) : "r"(c[2 * p + r]));
        var = fmaf(lo + nm, lo + nm, fmaf(hi + nm, hi + nm, var));
        if (p % 3 == 2) { asm volatile("" : "+f"(var)); PIN(); }
      }
      var += __shfl_xor_sync(0xffffffffu, var, 1);
      var += __shfl_xor_sync(0xffffffffu, var, 2);
      const float rr = rsqrtf(fmaf(var, 1.0f / 96.0f, 1e-5f)) * GELU_A;
      st[r] = __uint_as_float(pack_f16(rr, rr));
      const float dd = 0.5f * h_sum(__float_as_uint(st[r])) * nm;
      st[2 + r] = __uint_as_float(pack_f16(dd, dd));
      if (!(rr >= 0x1p-14f && fabsf(dd) <= 16.0f && var >= 1e-8f)) bad |= bit;
    }
  }
}
__device__ __forceinline__ void ln_apply(uint32_t (&a)[24], const uint32_t (&c)[24], const float (&st)[8]) {
#pragma unroll
  for (int p = 0; p < 24; p++) {
    a[p] = h_fma(c[p], __float_as_uint(st[p & 1]), __float_as_uint(st[2 + (p & 1)]));
  }
}

__device__ __noinline__ void slow_tile(const __nv_bfloat16* x, const __nv_bfloat16* dw, const __nv_bfloat16* w1,
                                       const __nv_bfloat16* w2, __nv_bfloat16* out, int row0, int col0, float* buf) {
  const int lane = threadIdx.x & 31;
  for (int px = 0; px < 16; px++) {
    const int row = row0 + (px >> 3), col = col0 + (px & 7);
    float c[3] = {0.f, 0.f, 0.f};
    for (int i = 0; i < 7; i++)
      for (int j = 0; j < 7; j++) {
        const int rr = row + i - 3, cc = col + j - 3;
        if (rr < 0 || rr >= IMG || cc < 0 || cc >= IMG) continue;
        for (int k = 0; k < 3; k++)
          c[k] = fmaf(__bfloat162float(x[((size_t)rr * IMG + cc) * CH + lane + 32 * k]), __bfloat162float(dw[(i * 7 + j) * CH + lane + 32 * k]), c[k]);
      }
    float mean = (c[0] + c[1] + c[2]) * (1.0f / 96.0f);
    for (int o = 16; o; o >>= 1) mean += __shfl_xor_sync(0xffffffffu, mean, o);
    float var = 0.f;
    for (int k = 0; k < 3; k++) { c[k] -= mean; var = fmaf(c[k] * (1.0f / 96.0f), c[k], var); }
    for (int o = 16; o; o >>= 1) var += __shfl_xor_sync(0xffffffffu, var, o);
    const float rs = 1.0f / sqrtf(var + 1e-5f);
    __syncwarp();
    for (int k = 0; k < 3; k++) buf[lane + 32 * k] = c[k] * rs;
    __syncwarp();
    for (int n = lane; n < 4 * CH; n += 32) {
      float y = 0.f;
      for (int k = 0; k < CH; k++) y = fmaf(buf[k], __bfloat162float(w1[k * 4 * CH + n]), y);
      buf[CH + n] = 0.5f * y * (1.0f + tanhf(0.7978845608f * (y + 0.044715f * y * y * y)));
    }
    __syncwarp();
    for (int n = lane; n < CH; n += 32) {
      float o = 0.f;
      for (int k = 0; k < 4 * CH; k++) o = fmaf(buf[CH + k], __bfloat162float(w2[k * CH + n]), o);
      const size_t idx = ((size_t)row * IMG + col) * CH + n;
      out[idx] = __float2bfloat16(__bfloat162float(x[idx]) + o);
    }
  }
}

__device__ __forceinline__ void x_load(const MlpCtx& m, uint32_t (&x)[24]) {
#pragma unroll
  for (int k = 0; k < 6; k++)
    asm volatile("ld.shared.v4.b32 {%0,%1,%2,%3}, [%4];"
                 : "=r"(x[4 * k]), "=r"(x[4 * k + 1]), "=r"(x[4 * k + 2]), "=r"(x[4 * k + 3])
                 : "r"(m.xaddr + (k / 3) * 384 + (k % 3) * 64)
                 : "memory");
}
template <int LO, int HI>
__device__ __forceinline__ void epilogue(const MlpCtx& m, const uint32_t (&d)[24], uint32_t (&x)[24]) {
#pragma unroll
  for (int k = LO; k < HI; k++) {
    const int r = k / 3, q = k % 3;
    uint32_t* y = &x[4 * k];
#pragma unroll
    for (int j = 0; j < 4; j++) {
      uint32_t v = d[2 * (4 * q + j) + r];
      float lo, hi;
      asm("{\n.reg .b16 l, h;\nmov.b32 {l, h}, %2;\ncvt.f32.f16 %0, l;\ncvt.f32.f16 %1, h;\n}\n" : "=f"(lo), "=f"(hi) : "r"(v));
      asm("fma.rn.bf16x2 %0, %1, %2, %0;" : "+r"(y[j]) : "r"(pack_bf16(lo, hi)), "r"(m.unscale));
    }
    asm volatile("st.shared.v4.b32 [%0], {%1,%2,%3,%4};" ::"r"(m.xaddr + r * 384 + q * 64), "r"(y[0]), "r"(y[1]), "r"(y[2]), "r"(y[3])
                 : "memory");
  }
}
__device__ __forceinline__ void out_store(const MlpCtx& m, int i) {
  asm volatile("fence.proxy.async.shared::cta;" ::: "memory");
  __syncwarp();
  if (elect_one()) {
    const uint32_t src = m.sb + OFF_XRES + m.wg * 12288 + m.warp * 1536;
    uint8_t* dst = m.optr + (size_t)i * (8 * IMG * CH * 2);
    asm volatile("cp.async.bulk.global.shared::cta.bulk_group [%0], [%1], 1536;" ::"l"(dst), "r"(src) : "memory");
    asm volatile("cp.async.bulk.global.shared::cta.bulk_group [%0], [%1], 1536;" ::"l"(dst + IMG * CH * 2), "r"(src + 6144) : "memory");
    asm volatile("cp.async.bulk.commit_group;" ::: "memory");
  }
}

#define FSET 3
template <int J> constexpr bool goes_first = J == FSET || J == ((FSET + 1) & 3);
template <int J> __device__ __forceinline__ void tok_wait() {
  if (goes_first<J>) NB_SYNC(NB_CLOSE, 256);
  else NB_SYNC(NB_SEC + (J & 1), 256);
}
template <int J, bool PROD = true> __device__ __forceinline__ void tok_next() {
  if (goes_first<J>) NB_ARRIVE(NB_SEC + (J & 1), 256);
  if (J == 0 && PROD) NB_ARRIVE(NB_PROD, 160);
}
__device__ __forceinline__ void tok_pass() { NB_ARRIVE(NB_OPEN, 416); }
template <int J> __device__ __forceinline__ void tok_idle() { tok_wait<J>(); tok_next<J, false>(); tok_pass(); }

constexpr uint64_t CHK = 1152;

__device__ __forceinline__ float warp_sumsq(const uint32_t (&q)[4]) {
  const uint32_t t = bf_add(bf_add(q[0], q[1]), bf_add(q[2], q[3]));
  float f = bf_lo(t) + bf_hi(t);
#pragma unroll
  for (int o = 16; o; o >>= 1) f += __shfl_xor_sync(0xffffffffu, f, o);
  return f;
}
__device__ __forceinline__ int norm_exp(float f) { return (((int)(__float_as_uint(f * 1.5f) >> 23) - 127) >> 1) + 1; }
__device__ __forceinline__ int scale_exp(int e1, int e2) { return min(11 - e1 - e2, 14 - e2); }

__device__ __forceinline__ void convert_tile(int t, int k, const uint4* w1, const uint4* w2, uint32_t st, Scratch* scr) {
  const int lane = threadIdx.x & 31, k7 = lane & 7;
  const int j = t / 6, ks = t % 6, e = ks % 3, t4 = k7 >> 1;
  const uint4* src = t < 24 ? w1 + ((e < 2 ? 64 * (ks / 3) + 8 * t4 + 4 * e : 32 + 16 * (ks / 3) + 4 * t4) + (k7 & 1)) * 48 + j * 12 + (lane >> 3)
                            : w2 + (t - 24) * 192 + (lane >> 2) * 12 + (lane & 3);
  src += (k / 3) * 96 + (k % 3) * 4;
  if (k >= 6) src = (k == 6 ? w1 : w2) + lane * 145;
  const uint4 v = __ldg(src);
  const uint32_t w[4] = {v.x, v.y, v.z, v.w};
  const uint32_t q[4] = {bf_mul(v.x, v.x), bf_mul(v.y, v.y), bf_mul(v.z, v.z), bf_mul(v.w, v.w)};
  asm volatile("st.shared.f32 [%0], %1;" ::"r"(st + 3088 + 4 * k), "f"(warp_sumsq(q)) : "memory");
  NB_SYNC(NB_PREP, 256);
  uint32_t a[4], b[4], o[4];
  lds128(a, st + 3088);
  lds128(b, st + 3104);
  const int s = max(-64, min(64, scale_exp(norm_exp(144.f * __uint_as_float(b[2])), norm_exp(144.f * __uint_as_float(b[3]))) - 3));
  const uint32_t dst = st + k7 * 16 + (lane >> 3) * 256 + (k / 3) * 128 + (k % 3) * 1024;
  if (k >= 6) {
    const float f = ((__uint_as_float(a[0]) + __uint_as_float(a[1])) + (__uint_as_float(a[2]) + __uint_as_float(a[3]))) +
                    (__uint_as_float(b[0]) + __uint_as_float(b[1]));
    asm volatile("st.shared.v2.b32 [%0], {%1,%2};" ::"r"(st + 3072), "r"(__float_as_uint(f)), "r"(s) : "memory");
  } else if (t < 24) {
#pragma unroll
    for (int i = 0; i < 4; i++) o[i] = pack_f16(bf_lo(w[i]), bf_hi(w[i]));
    asm volatile("st.shared.v4.b32 [%0], {%1,%2,%3,%4};" ::"r"(dst), "r"(o[0]), "r"(o[1]), "r"(o[2]), "r"(o[3]) : "memory");
  } else {
    constexpr float F = 0.5f / GELU_A, FHI = 1.515625f;
    const float p2 = __uint_as_float((uint32_t)(127 + s - 56) << 23);
    const uint32_t hi = pack_bf16(FHI * 0x1p-56f, FHI * 0x1p-56f), lo = pack_bf16((F - FHI) * 0x1p-56f, (F - FHI) * 0x1p-56f);
    const uint32_t pw = pack_bf16(p2, p2);
#pragma unroll
    for (int i = 0; i < 4; i++) {
      const uint32_t ws = bf_mul(w[i], pw), u = bf_fma(ws, hi, bf_mul(ws, lo));
      o[i] = (u & 0x7fff7fffu) * 7u + u;
    }
    asm volatile("stmatrix.sync.aligned.m8n8.x4.shared.b16 [%0], {%1,%2,%3,%4};" ::"r"(dst), "r"(o[0]), "r"(o[1]), "r"(o[2]), "r"(o[3])
                 : "memory");
  }
  asm volatile("fence.proxy.async.shared::cta;" ::: "memory");
  NB_SYNC(NB_PREP, 256);
  TS(4);
  if (k == 0 && elect_one()) {
    asm volatile("cp.async.bulk.global.shared::cta.bulk_group [%0], [%1], 3072;" ::"l"(scr->w + t * 192), "r"(st) : "memory");
    asm volatile("cp.async.bulk.global.shared::cta.bulk_group [%0], [%1], 16;" ::"l"(scr->nrm + t), "r"(st + 3072) : "memory");
    asm volatile("cp.async.bulk.commit_group;" ::: "memory");
    asm volatile("cp.async.bulk.wait_group 0;" ::: "memory");
    asm volatile("red.relaxed.gpu.global.add.u32 [%0], 1;" ::"l"(&scr->done) : "memory");
  }
  TS(5);
}

__device__ __forceinline__ uint32_t mlp_role(const MlpCtx& m0) {
  MlpCtx m = m0;
  uint32_t bad = 0;
  asm volatile("barrier.cluster.wait.aligned;" ::: "memory");
  if ((m.sb & 0x3FFFF) != 1024) bad = 0xffffu;
  constexpr uint64_t dW1 = (uint64_t)((1024 + OFF_W1) >> 4) | ((uint64_t)8 << 16) | ((uint64_t)16 << 32);
  constexpr uint64_t dW2 = dW1 + (OFF_W2 >> 4);
  TS(6);
  uint32_t A1[24], g[24], d[24], cn[24], D2[24];
  float st[8];
  if (m.wg & m.rank) tok_idle<3>();
  else if (m.wg) tok_idle<0>();
  else if (m.rank) tok_idle<1>();
  ln_wait(m, 0);
  ln_load(m, cn);
  ln_sums(cn, st);
  ln_shfl(st, 1);
  ln_release(m);
  ln_fold(st);
  ln_shfl(st, 2);
  ln_restat(ln_stats(st), cn, st, bad, 1, m.zero);
  ln_apply(A1, cn, st);
  {
    const int lane = threadIdx.x & 31;
    TS(2);
    mbar_wait(m.sb + BAR_W, 0);
    TS(3);
    float n1, n2;
    int s;
    asm volatile("ld.shared.b32 %0, [%1];" : "=r"(s) : "r"(m.sb + OFF_NRM + 4) : "memory");
    asm volatile("ld.shared.f32 %0, [%1];" : "=f"(n1) : "r"(m.sb + OFF_NRM + 16 * min(lane, 23)) : "memory");
    asm volatile("ld.shared.f32 %0, [%1];" : "=f"(n2) : "r"(m.sb + OFF_NRM + 384 + 16 * min(lane, 23)) : "memory");
    if (lane >= 24) n1 = n2 = 0.f;
#pragma unroll
    for (int o = 16; o; o >>= 1) {
      n1 += __shfl_xor_sync(0xffffffffu, n1, o);
      n2 += __shfl_xor_sync(0xffffffffu, n2, o);
    }
    const int e1 = norm_exp(n1), e2 = norm_exp(n2), smax = scale_exp(e1, e2);
    if (e1 > 12 || e1 < -5 || e2 > 50 || e2 < -50 || s > smax || s < smax - 7) bad = 0xffffu;
    m.unscale = __shfl_sync(0xffffffffu, ((uint32_t)(127 - s) << 7) * 0x10001u, 0);
  }
  TS(7);
  if (m.wg & m.rank) tok_idle<0>();
  if (m.wg) tok_idle<1>();
  {
    uint32_t d0[24];
    WG_FENCE();
    tok_wait<2>();
    tok_next<2>();
    gemm6<true, 192>(d0, A1, dW1);
    tok_pass(); PIN();
    WG_WAIT0(); rfence(d0);
    WG_FENCE();
    tok_wait<3>();
    tok_next<3>();
    gemm6<true, 192>(d, A1, dW1 + CHK);
    tok_pass(); PIN();
    gelu<0, 24>(g, d0);
    PIN();
    mbar_wait(m.sb + BAR_W + 8, 0);
    ln_wait(m, 1);
    WG_WAIT0(); rfence(d);
  }
#define G2(INIT, a, j)                      \
  WG_FENCE();                               \
  tok_wait<j>();                            \
  gemm6<INIT, 192>(D2, a, dW2 + (j) * CHK); \
  tok_next<j>(); PIN();                     \
  TL(ltb, (j) * 5 + 1);
#define G1(dst, j, P)                       \
  TL(ltb, ((j) ^ 2) * 5 + 2);               \
  P(); WG_WAIT0(); rfence(D2);              \
  WG_FENCE();                               \
  gemm6<true, 192>(dst, A1, dW1 + (j) * CHK); \
  tok_pass(); P();                          \
  TL(ltb, ((j) ^ 2) * 5 + 3);
#define ROUND_END(dst, j)                   \
  TL(ltb, (j) * 5 + 4);                     \
  PIN(); WG_WAIT0(); rfence(dst);
#define GA 9
#define GB 12
#define GC 13
#define GD 11
#pragma unroll 1
  for (int i = 0;; i++) {
    uint32_t g1[24], d2[24], g2[24], d3[24], g3[24], d0[24];
    ln_load(m, cn);
    PIN();
    G2(true, g, 0)
    gelu<0, GA>(g1, d);
    G1(d2, 2, PIN)
    ln_sums(cn, st);
    gelu<GA, 24>(g1, d);
    PIN();
    ln_shfl(st, 1);
    ROUND_END(d2, 0)

    G2(false, g1, 1)
    ln_fold(st);
    gelu<0, GB>(g2, d2);
    PIN();
    ln_shfl(st, 2);
    G1(d3, 3, PIN)
    const bool ok = ln_stats(st);
    gelu<GB, 24>(g2, d2);
    PIN();
    ln_restat(ok, cn, st, bad, 2u << i, m.zero);
    ROUND_END(d3, 1)

    if (i == 15) {
      G2(false, g2, 2)
      tok_pass();
      gelu<0, 24>(g3, d3);
      PIN();
      x_load(m, cn);
      ROUND_END(D2, 2)
      G2(false, g3, 3)
      tok_pass();
      WG_WAIT0(); rfence(D2);
      epilogue<0, 6>(m, D2, cn);
      break;
    }
    G2(false, g2, 2)
    ln_apply(A1, cn, st);
    PIN();
    gelu<0, GC>(g3, d3);
    G1(d0, 0, PIN)
    gelu<GC, 24>(g3, d3);
    PIN();
    x_load(m, cn);
    ROUND_END(d0, 2)

    G2(false, g3, 3)
    gelu<0, GD>(g, d0);
    G1(d, 1, PIN)
    epilogue<0, 6>(m, D2, cn);
    gelu<GD, 24>(g, d0);
    PIN();
    asm volatile("fence.proxy.async.shared::cta;" ::: "memory");
    ROUND_END(d, 3)
    TLDUMP(m.warp == 0 && (i >> 1) == LTRACE, m.sb + OFF_LT + m.wg * 160 + (i & 1) * 80, 20)
  }
  out_store(m, 15);
  if (m.wg == 0) { tok_idle<0>(); tok_idle<1>(); }
  asm volatile("cp.async.bulk.wait_group.read 0;" ::: "memory");
  return __reduce_or_sync(0xffffffffu, bad & 0xffffu);
}

struct ConvCtx {
  uint32_t sb;
  uint32_t a0, a_c;
  uint32_t peer_off;
  int rank, v, c0, r0, zero;
  const CUtensorMap* tm;
  Scratch* scr;
  const uint8_t* xsrc;
  uint8_t* optr;
};

__device__ __forceinline__ void raw_refill(const ConvCtx& c, int s) {
  if (s + 4 < NSTEP && elect_one())
    tma_raw(c.sb + OFF_RAW + (s & 3) * RAW_BYTES, c.tm, c.rank, c.c0 / 2 - 2, c.r0 - 3 + 2 * (s + 4), c.sb + BAR_RAW + 8 * (s & 3));
}
__device__ __forceinline__ void step_ready(const ConvCtx& c, int s) {
  const int nx = (s + 1) & 3, par = ((s + 1) >> 2) & 1;
  if (s + 1 < NSTEP) mbar_wait(c.sb + BAR_RAW + 8 * nx, par);
  if (s >= 7 && s < NSTEP) mbar_wait(c.sb + BAR_CEMPTY + 8 * (2 * (nx & 1) + (nx >> 1)), par);
}

__device__ __forceinline__ void c_release(const ConvCtx& c, uint32_t w) {
  const uint32_t e = c.sb + BAR_CEMPTY + 8 * (2 * c.rank + w);
  asm volatile(
      "{\n.reg .pred p;\nelect.sync _|p, 0xffffffff;\n"
      "@p mbarrier.arrive.expect_tx.shared::cta.b64 _, [%0], %3;\n"
      "@p mbarrier.arrive.shared::cluster.b64 _, [%1], 4;\n"
      "@p mbarrier.arrive.shared::cluster.b64 _, [%2], 4;\n}\n" ::"r"(c.sb + BAR_CFULL + 8 * w),
      "r"(e), "r"(e + c.peer_off), "n"(CTX)
      : "memory");
}

__device__ __forceinline__ void prod_rows(const ConvCtx& c) {
#pragma unroll 1
  for (int s = 0; s < NROUND + SIGMA + c.rank; s++) {
    const int r = s - SIGMA - c.rank;
    const int u = (r & 1) ? (r >> 1) - 1 : (r >> 1) + 2;
    step_ready(c, s);
    if (u >= ((r & 1) ? 0 : 4) && u < 32) mbar_wait(c.sb + ((r & 1) ? BAR_XFULL : BAR_CFULL) + 8 * (u & 1), (u >> 1) & 1);
    if (s < SIGMA) NB_SYNC(NB_PLAN, 160);
    else NB_SYNC(NB_OPEN, 416);
    if (r == 3) TC(c.scr, 1);
    if (r == 55) TC(c.scr, 2);
    if (r >= -1 && r < 7) TS(7 + r);
    raw_refill(c, s);
  }
}
__device__ __forceinline__ void prod_tiles(const ConvCtx& c) {
  asm volatile("barrier.cluster.wait.aligned;" ::: "memory");
#pragma unroll 1
  for (int n = 1; n < 33; n++) {
    const uint32_t w = (n + 1) & 1;
    const uint32_t buf = c.sb + OFF_XRES + w * 12288;
    NB_SYNC(NB_PROD, 160);
    if (n < 29) c_release(c, w);
    if (n >= 3) {
      uint8_t* dst = c.optr + (size_t)(n - 3) * (4 * IMG * CH * 2);
      if (elect_one()) {
        asm volatile("cp.async.bulk.global.shared::cta.bulk_group [%0], [%1], 6144;" ::"l"(dst), "r"(buf) : "memory");
        asm volatile("cp.async.bulk.global.shared::cta.bulk_group [%0], [%1], 6144;" ::"l"(dst + IMG * CH * 2), "r"(buf + 6144) : "memory");
        asm volatile("cp.async.bulk.commit_group;" ::: "memory");
        asm volatile("cp.async.bulk.wait_group.read 0;" ::: "memory");
      }
      __syncwarp();
    }
    {
      const uint8_t* src = c.xsrc + (size_t)(n - 1) * (4 * IMG * CH * 2);
      if (elect_one()) {
        mbar_expect(c.sb + BAR_XFULL + 8 * w, 12288);
        bulk_load_last(buf, src, 6144, c.sb + BAR_XFULL + 8 * w);
        bulk_load_last(buf + 6144, src + IMG * CH * 2, 6144, c.sb + BAR_XFULL + 8 * w);
      }
    }
  }
  asm volatile("cp.async.bulk.wait_group 0;" ::: "memory");
}

template <int LO, int HI>
__device__ __forceinline__ void conv_ld8(uint32_t a0, uint32_t (&r)[6][6]) {
  const uint32_t a2 = a0 ^ (16 | ((a0 >> 2) & 32));
  const uint32_t a[3] = {a0, (a0 & 64) ? a2 : a0, a2};
#pragma unroll
  for (int j = LO; j < HI; j++)
    asm volatile("ld.shared.v4.b32 {%0,%1,%2,%3}, [%4];"
                 : "=r"(r[j][0]), "=r"(r[j][1]), "=r"(r[j][2]), "=r"(r[j][3])
                 : "r"(a[j >> 1] + (j >> 1) * 64 + (j & 1) * RAW_PA)
                 : "memory");
}
__device__ __forceinline__ void conv_ld4(uint32_t a0, uint32_t stage, int v, uint32_t (&r)[6][6]) {
  const uint32_t ab = ((a0 >> 1) & ~31u) + (stage / 2 + 2 * RAW_PA + 8 * v);
#pragma unroll
  for (int j = 0; j < 6; j++) {
    uint32_t a = ab + (j >> 1) * 32;
    asm volatile("ld.shared.v2.b32 {%0,%1}, [%2];" : "=r"(r[j][4]), "=r"(r[j][5]) : "r"(a + (j & 1) * RAW_PB) : "memory");
  }
}
template <int LO, int HI>
__device__ __forceinline__ void conv_frags(uint32_t zero, const uint32_t (&r)[6][6], uint32_t (&A)[12][4]) {
#pragma unroll
  for (int ch = LO; ch < HI; ch++) {
    const uint32_t sel = (ch & 1) ? 0x7632 : 0x5410;
    A[ch][0] = __byte_perm(r[0][ch >> 1], r[1][ch >> 1], sel);
    A[ch][1] = __byte_perm(r[2][ch >> 1], r[3][ch >> 1], sel);
    A[ch][2] = A[ch][1] ^ zero;
    A[ch][3] = __byte_perm(r[4][ch >> 1], r[5][ch >> 1], sel);
    rfence(A[ch]);
  }
}
__device__ __forceinline__ void hmma_acc(uint32_t (&v)[4], const uint32_t (&a)[4], const uint32_t* b) {
  asm volatile("mma.sync.aligned.m16n8k16.row.col.f32.bf16.bf16.f32 {%0,%1,%2,%3}, {%4,%5,%6,%7}, {%8,%9}, {%0,%1,%2,%3};"
               : "+r"(v[0]), "+r"(v[1]), "+r"(v[2]), "+r"(v[3])
               : "r"(a[0]), "r"(a[1]), "r"(a[2]), "r"(a[3]), "r"(b[0]), "r"(b[1]));
}
__device__ __forceinline__ void hmma_new(uint32_t (&a)[4], const uint32_t* b) {
  asm volatile("mma.sync.aligned.m16n8k16.row.col.f32.bf16.bf16.f32 {%0,%1,%2,%3}, {%0,%1,%2,%3}, {%4,%5}, {%6,%6,%6,%6};"
               : "+r"(a[0]), "+r"(a[1]), "+r"(a[2]), "+r"(a[3])
               : "r"(b[0]), "r"(b[1]), "f"(0.f));
}

#define EARLY 5
__device__ __forceinline__ void conv_send(bool local, const uint32_t (&pk)[12], uint32_t dst, uint32_t bar) {
  if (local) {
#pragma unroll
    for (int q = 0; q < 3; q++)
      asm volatile("st.shared.v4.b32 [%0], {%1,%2,%3,%4};" ::"r"(dst + q * 2048), "r"(pk[4 * q]), "r"(pk[4 * q + 1]), "r"(pk[4 * q + 2]), "r"(pk[4 * q + 3])
                   : "memory");
    asm volatile("{\n.reg .pred p;\nelect.sync _|p, 0xffffffff;\n@p mbarrier.arrive.shared::cta.b64 _, [%0];\n}\n" ::"r"(bar) : "memory");
  } else {
#pragma unroll
    for (int q = 0; q < 3; q++)
      asm volatile("st.async.weak.shared::cluster.mbarrier::complete_tx::bytes.v4.b32 [%0], {%1,%2,%3,%4}, [%5];" ::"r"(dst + q * 2048),
                   "r"(pk[4 * q]), "r"(pk[4 * q + 1]), "r"(pk[4 * q + 2]), "r"(pk[4 * q + 3]), "r"(bar)
                   : "memory");
  }
}
template <int S2, bool GATED>
__device__ __forceinline__ void conv_step(const ConvCtx& c, int s, uint32_t (&K)[12], uint32_t (&V)[12][4], const uint32_t (&B)[12][4],
                                          uint32_t (&A)[12][4]) {
  const int nx = ((s + 1) & 2) | (S2 ^ 1);
  uint32_t r[6][6], pk[12];
  const uint32_t a0 = c.a0 + nx * RAW_BYTES;
  if (!GATED) TS(6 + s);
  if (GATED) NB_SYNC(NB_OPEN, 416);
  else NB_SYNC(NB_PLAN, 160);
  conv_ld4(a0, c.sb + OFF_RAW + nx * RAW_BYTES, c.v, r);
  if (GATED) PIN();
#pragma unroll
  for (int ch = 0; ch < 12; ch++) hmma_acc(V[11 - ch], A[11 - ch], &B[11 - ch][2]);
#pragma unroll
  for (int ch = 0; ch < 12 - EARLY; ch++) hmma_new(A[ch], &B[ch][0]);
  const uint32_t zero = GATED ? c.zero & clock_pin() : c.zero;
  if (GATED) NB_ARRIVE(NB_CLOSE, 256);
#pragma unroll
  for (int ch = 12 - EARLY; ch < 12; ch++) hmma_new(A[ch], &B[ch][0]);
  if (GATED) PIN();
  const bool local = (S2 ^ 1) == c.rank;
  const uint32_t off = local ? 0u : c.peer_off;
  const uint32_t dst = c.a_c + (GATED || s >= 3 ? off + (nx >> 1) * C_BYTES : OFF_XRES + 12288 - OFF_C);
  const uint32_t bar = c.sb + (GATED || s >= 3 ? off + BAR_CFULL + 8 * (nx >> 1) : BAR_W + 56);
#pragma unroll
  for (int q = 0; q < 12; q++) {
    const int ch = q & ~1, h = 2 * (q & 1);
    pk[q] = h_add(K[q], pack_f16(__uint_as_float(V[ch][h + 1]), __uint_as_float(V[ch + 1][h])));
  }
#pragma unroll
  for (int q = 0; q < 12; q++) {
    const int ch = q & ~1, h = 2 * (q & 1);
    K[q] = pack_f16(__uint_as_float(V[ch][h]), __uint_as_float(V[ch + 1][h + 1]));
  }
  rfence(K);
  rfence(pk);
  PIN();
  conv_ld8<0, 4>(a0, r);
  conv_send(local, pk, dst, bar);
  conv_frags<8, 12>(zero, r, V);
  PIN();
  conv_ld8<4, 6>(a0, r);
  conv_frags<0, 8>(zero, r, V);
  PIN();
}

__device__ __forceinline__ void conv_role(ConvCtx c) {
  const int lane = laneid(), g = lane >> 2, t = lane & 3;
  const int u = (t >> 1) * 19 + 2 * (g + (t & 1));
  c.a0 = c.sb + OFF_RAW + u * 64 + ((c.v ^ (u >> 1)) & 3) * 16;
  c.a_c = c.sb + OFF_C + 6144 * c.rank + 512 * c.v + ((lane + 2 * c.v) & 31) * 16;
  uint32_t B[12][4];
  {
    const int dc = (g >> 1) & 1, ro = g >> 2, rk = t >> 1;
    const int i0 = 4 * (g & 1) + rk - ro, j0 = 4 * (t & 1) - dc;
    const uint32_t base = c.sb + OFF_XRES + (i0 * 7 + j0) * 192;
    TS(2);
    asm volatile("barrier.cluster.wait.aligned;" ::: "memory");
    mbar_wait(c.sb + BAR_W + 48, 0);
    TS(3);
#pragma unroll
    for (int b = 0; b < 2; b++) {
      uint32_t w[4][6];
#pragma unroll
      for (int k = 0; k < 4; k++) {
        const int ok = (unsigned)(i0 + 2 * b) < 7u && (unsigned)(j0 + k) < 7u;
#pragma unroll
        for (int q = 0; q < 6; q++) w[k][q] = 0;
        asm volatile(
            "{\n.reg .pred p;\nsetp.ne.s32 p, %8, 0;\n@p ld.shared.v4.b32 {%0,%1,%2,%3}, [%6];\n@p ld.shared.v2.b32 {%4,%5}, [%7];\n}\n"
            : "+r"(w[k][0]), "+r"(w[k][1]), "+r"(w[k][2]), "+r"(w[k][3]), "+r"(w[k][4]), "+r"(w[k][5])
            : "r"(base + (b * 14 + k) * 192 + 128 * c.rank + 16 * c.v), "r"(base + (b * 14 + k) * 192 + 64 + 32 * c.rank + 8 * c.v), "r"(ok)
            : "memory");
      }
#pragma unroll
      for (int q = 0; q < 6; q++) {
        B[2 * q][2 * b] = __byte_perm(w[0][q], w[1][q], 0x5410);
        B[2 * q][2 * b + 1] = __byte_perm(w[2][q], w[3][q], 0x5410);
        B[2 * q + 1][2 * b] = __shfl_xor_sync(0xffffffffu, __byte_perm(w[0][q], w[1][q], 0x7632), 4);
        B[2 * q + 1][2 * b + 1] = __shfl_xor_sync(0xffffffffu, __byte_perm(w[2][q], w[3][q], 0x7632), 4);
      }
    }
  }
  TS(4);
  uint32_t K1[12], K2[12], V[12][4];
#pragma unroll
  for (int ch = 0; ch < 12; ch++) {
    K1[ch] = K2[ch] = 0;
#pragma unroll
    for (int k = 0; k < 4; k++) V[ch][k] = 0;
  }
  uint32_t A[12][4], r[6][6];
  mbar_wait(c.sb + BAR_RAW, 0);
  TS(5);
  conv_ld8<0, 6>(c.a0, r);
  conv_ld4(c.a0, c.sb + OFF_RAW, c.v, r);
  conv_frags<0, 12>(c.zero, r, A);
  PIN();
  NB_ARRIVE(NB_CLOSE, 256);
#pragma unroll 1
  for (int s = 0; s < SIGMA; s += 2) {
    conv_step<0, false>(c, s, K1, V, B, A);
    conv_step<1, false>(c, s + 1, K2, A, B, V);
  }
#pragma unroll 1
  for (int s = SIGMA;; s += 2) {
    conv_step<0, true>(c, s, K1, V, B, A);
    if (s == NSTEP - 1) break;
    conv_step<1, true>(c, s + 1, K2, A, B, V);
  }
#pragma unroll 1
  for (int r = NSTEP - SIGMA - c.rank; r < NROUND - 1; r++) {
    NB_SYNC(NB_OPEN, 416);
    NB_ARRIVE(NB_CLOSE, 256);
  }
  NB_SYNC(NB_OPEN, 416);
}

struct TMaps { CUtensorMap m[2]; };
__device__ __forceinline__ Scratch* scr_param() {
  extern __shared__ __align__(1024) uint8_t smem[];
  return *reinterpret_cast<Scratch* volatile*>(smem + OFF_LT + 592);
}

__global__ void __cluster_dims__(2, 1, 1) __launch_bounds__(512, 1)
convnext_kernel(const __grid_constant__ TMaps tms, const __nv_bfloat16* __restrict__ x, const __nv_bfloat16* __restrict__ dw,
                const __nv_bfloat16* __restrict__ w1, const __nv_bfloat16* __restrict__ w2, __nv_bfloat16* __restrict__ out,
                Scratch* scr, int zero) {
  extern __shared__ __align__(1024) uint8_t smem[];
  const uint32_t sb = (uint32_t)__cvta_generic_to_shared(smem);
  const int tid = threadIdx.x, lane = tid & 31;
  const int wid = __shfl_sync(0xffffffffu, tid >> 5, 0);
  const int rank = blockIdx.x & 1, cl = blockIdx.x >> 1;
  const int c0 = (cl & 15) * 32, r0 = (cl >> 4) * 128;
  const uint32_t peer_off = mapa(sb, rank ^ 1) - sb;

  TS(0);
  if (wid == 12 && elect_one()) {
    mbar_init(sb + BAR_W + 48, 1);
#pragma unroll
    for (int i = 0; i < 4; i++) mbar_init(sb + BAR_RAW + 8 * i, 1);
    asm volatile("fence.mbarrier_init.release.cluster;" ::: "memory");
    mbar_expect(sb + BAR_W + 48, 49 * CH * 2);
    bulk_load(sb + OFF_XRES, dw, 49 * CH * 2, sb + BAR_W + 48);
#pragma unroll
    for (int i = 0; i < E0; i++) tma_raw(sb + OFF_RAW + i * RAW_BYTES, tms.m, rank, c0 / 2 - 2, r0 - 3 + 2 * i, sb + BAR_RAW + 8 * i);
  }
  if (wid == 14 && elect_one()) {
    asm volatile("prefetch.tensormap [%0];" ::"l"(&tms.m[1]) : "memory");
#pragma unroll
    for (int i = 0; i < 3; i++) mbar_init(sb + BAR_W + 8 * i, 1);
    mbar_init(sb + BAR_W + 56, 100);
#pragma unroll
    for (int i = 0; i < 2; i++) mbar_init(sb + BAR_CFULL + 8 * i, CCNT);
#pragma unroll
    for (int i = 0; i < 4; i++) mbar_init(sb + BAR_CEMPTY + 8 * i, 4);
#pragma unroll
    for (int i = 0; i < 2; i++) mbar_init(sb + BAR_XFULL + 8 * i, 1);
#pragma unroll
    for (int i = 0; i < 2; i++) mbar_expect(sb + BAR_CFULL + 8 * i, CTX);
    asm volatile("fence.mbarrier_init.release.cluster;" ::: "memory");
  }
  __syncwarp();
  asm volatile("barrier.cluster.arrive.relaxed.aligned;" ::: "memory");

  TS(1);
  if (wid < 8) {
    if (blockIdx.x < 48) convert_tile(blockIdx.x, wid, reinterpret_cast<const uint4*>(w1), reinterpret_cast<const uint4*>(w2), sb, scr);
    MlpCtx m;
    m.sb = sb; m.wg = wid >> 2; m.warp = wid & 3; m.rank = rank; m.peer_off = peer_off; m.zero = zero;
    m.optr = reinterpret_cast<uint8_t*>(out) + ((size_t)(r0 + 4 * m.wg + 2 * rank) * IMG + c0 + 8 * m.warp) * (CH * 2);
    m.caddr = sb + OFF_C + m.wg * C_BYTES + (lane & 3) * 512 + ((m.warp * 8 + (lane >> 2) + 2 * (lane & 3)) & 31) * 16;
    m.xaddr = sb + OFF_XRES + m.wg * 12288 + m.warp * 1536 + ((lane >> 3) & 1) * 6144 + ((lane >> 4) * 4 + ((lane >> 2) & 1)) * 192 + (lane & 3) * 16;
    m.unscale = 0;
    asm volatile("setmaxnreg.inc.sync.aligned.u32 %0;" ::"n"(REG_MLP));
    const uint32_t bad = mlp_role(m);
    TC(scr, 3);
    if (bad) {
      asm volatile("cp.async.bulk.wait_group 0;" ::: "memory");
      mbar_wait(sb + BAR_W + 16, 0);
      __syncwarp();
      asm volatile("fence.proxy.async;" ::: "memory");
#pragma unroll 1
      for (int i = 0; i < 16; i++)
        if (bad >> i & 1)
          slow_tile(x, dw, w1, w2, out, r0 + 8 * i + 4 * m.wg + 2 * rank, c0 + 8 * m.warp,
                    reinterpret_cast<float*>(smem + OFF_RAW + wid * 2048));
    }
  } else {
    ConvCtx c;
    c.sb = sb; c.rank = rank; c.v = wid - 8; c.c0 = c0; c.r0 = r0; c.zero = zero; c.tm = tms.m; c.scr = scr;
    c.peer_off = peer_off;
    c.xsrc = reinterpret_cast<const uint8_t*>(x) + ((size_t)(r0 + 2 * rank) * IMG + c0) * (CH * 2);
    c.optr = reinterpret_cast<uint8_t*>(out) + ((size_t)(r0 + 2 * rank) * IMG + c0) * (CH * 2);
    if (wid < 12) {
      asm volatile("setmaxnreg.inc.sync.aligned.u32 %0;" ::"n"(REG_CONV));
      conv_role(c);
    } else {
      asm volatile("setmaxnreg.dec.sync.aligned.u32 24;");
      if (wid == 15) TC(scr, 0);
      if (wid == 12) {
        TS(2);
#pragma unroll 1
        for (int h = E0 - 4; h < 0; h++) raw_refill(c, h);
        TS(3);
        asm volatile("barrier.cluster.wait.aligned;" ::: "memory");
        prod_rows(c);
      } else if (wid == 14) {
#pragma unroll 1
        for (int n = 0; n < (1 << 20); n++) {
          unsigned v;
          __nanosleep(n ? PSL : PS0);
          asm volatile("ld.acquire.gpu.global.u32 %0, [%1];" : "=r"(v) : "l"(&scr->done) : "memory");
          if (__shfl_sync(0xffffffffu, v, 0) >= 48) break;
        }
        asm volatile("barrier.cluster.wait.aligned;" ::: "memory");
        asm volatile("fence.proxy.async.global;" ::: "memory");
        if (elect_one()) {
          mbar_expect(sb + BAR_W, 36864 + 768);
          mbar_expect(sb + BAR_W + 8, 110592);
          bulk_load(sb + OFF_NRM, scr->nrm, 768, sb + BAR_W);
          if (atomicAdd(&scr->seen, 1u) == gridDim.x - 1) { scr->done = 0; scr->seen = 0; }
        }
        __syncwarp();
#pragma unroll 1
        for (int i = 0; i < 8; i++) {
          if (elect_one()) bulk_load(sb + i * 18432, reinterpret_cast<const uint8_t*>(scr->w) + i * 18432, 18432, sb + BAR_W + (i < 2 ? 0 : 8));
          __nanosleep(PACE);
        }
      } else if (wid == 13) {
        prod_tiles(c);
        __syncwarp();
        if (elect_one()) asm volatile("mbarrier.arrive.shared::cta.b64 _, [%0];" ::"r"(sb + BAR_W + 16) : "memory");
      }
    }
  }
}

typedef CUresult (*EncodeFn)(CUtensorMap*, CUtensorMapDataType, cuuint32_t, void*, const cuuint64_t*, const cuuint64_t*,
                             const cuuint32_t*, const cuuint32_t*, CUtensorMapInterleave, CUtensorMapSwizzle,
                             CUtensorMapL2promotion, CUtensorMapFloatOOBfill);

}

extern "C" void kernel_launch(void* const* d_in, const int* in_sizes, int n_in, void* d_out, int out_size) {
  const __nv_bfloat16* x = (const __nv_bfloat16*)d_in[0];
  const __nv_bfloat16* dw = (const __nv_bfloat16*)d_in[1];
  const __nv_bfloat16* w1 = (const __nv_bfloat16*)d_in[2];
  const __nv_bfloat16* w2 = (const __nv_bfloat16*)d_in[3];
  __nv_bfloat16* out = (__nv_bfloat16*)d_out;

  static EncodeFn encode = nullptr;
  static Scratch* scr = nullptr;
  if (!encode) {
    cudaDriverEntryPointQueryResult st;
    void* fn = nullptr;
    cudaGetDriverEntryPoint("cuTensorMapEncodeTiled", &fn, cudaEnableDefault, &st);
    encode = (EncodeFn)fn;
    cudaGetSymbolAddress((void**)&scr, g_scratch);
    cudaFuncSetAttribute(convnext_kernel, cudaFuncAttributeMaxDynamicSharedMemorySize, SMEM_BYTES);
  }
  TMaps tm;
  cuuint64_t dims[4] = {CH, IMG / 2, IMG, 2};
  cuuint64_t strides[3] = {CH * 4, (cuuint64_t)IMG * CH * 2, CH * 2};
  cuuint32_t es[4] = {1, 1, 1, 1};
  for (int i = 0; i < 2; i++) {
    cuuint32_t box[4] = {i ? 16u : 32u, 19, 2, 1};
    encode(&tm.m[i], CU_TENSOR_MAP_DATA_TYPE_BFLOAT16, 4, (void*)x, dims, strides, box, es, CU_TENSOR_MAP_INTERLEAVE_NONE,
           i ? CU_TENSOR_MAP_SWIZZLE_NONE : CU_TENSOR_MAP_SWIZZLE_64B, PROMO, CU_TENSOR_MAP_FLOAT_OOB_FILL_NONE);
  }
  convnext_kernel<<<128, 512, SMEM_BYTES>>>(tm, x, dw, w1, w2, out, scr, 0);
}
```

```cpp
#include <cuda_runtime.h>
#include <cuda_bf16.h>
#include <cuda.h>
#include <stdint.h>

#define PROMO CU_TENSOR_MAP_L2_PROMOTION_L2_128B
#define CTX 6144
#define CCNT 5
#define PSL 100
#define PS0 1000
#define E0 1
#define PACE 100
namespace {

constexpr int IMG = 512, CH = 96;
constexpr int NSTEP = 67;
constexpr int SIGMA = 8;
constexpr int NROUND = 68;

constexpr uint32_t OFF_W1 = 0;
constexpr uint32_t OFF_W2 = 73728;
constexpr uint32_t OFF_RAW = 147456;
constexpr uint32_t RAW_PA = 2560, RAW_PB = 1280;
constexpr uint32_t RAW_BYTES = 2 * RAW_PA + 2 * RAW_PB;
constexpr uint32_t RAW_TX = 2 * 38 * 96;
constexpr uint32_t OFF_XRES = OFF_RAW + 4 * RAW_BYTES;
constexpr uint32_t OFF_C = OFF_XRES + 2 * 12288;
constexpr uint32_t C_BYTES = 12288;
constexpr uint32_t OFF_BAR = OFF_C + 2 * C_BYTES;
constexpr uint32_t BAR_RAW = OFF_BAR;
constexpr uint32_t BAR_CFULL = OFF_BAR + 32;
constexpr uint32_t BAR_CEMPTY = OFF_BAR + 48;
constexpr uint32_t BAR_XFULL = OFF_BAR + 80;
constexpr uint32_t BAR_W = OFF_BAR + 96;
constexpr uint32_t OFF_NRM = OFF_XRES + 9472;
constexpr uint32_t SMEM_BYTES = OFF_BAR + 160;

struct Scratch {
  uint4 w[2 * 73728 / 16];
  uint4 nrm[48];
  unsigned done, seen;
};
__device__ Scratch g_scratch;

constexpr float GELU_A = 0.32918364f;
constexpr uint32_t GELU_K2 = 0x40d940d9u;

constexpr int NB_CLOSE = 1, NB_SEC = 6  , NB_OPEN = 3, NB_PROD = 2, NB_PLAN = 4, NB_PREP = 5, NB_WG = 8  ;
#define REG_MLP 144
constexpr int REG_CONV = 488 - 2 * REG_MLP;

#define WG_FENCE() asm volatile("wgmma.fence.sync.aligned;" ::: "memory")
#define WG_COMMIT() asm volatile("wgmma.commit_group.sync.aligned;" ::: "memory")
#define WG_WAIT0() asm volatile("wgmma.wait_group.sync.aligned 0;" ::: "memory")
#define WG_WAIT1() asm volatile("wgmma.wait_group.sync.aligned 1;" ::: "memory")
#define PIN() asm volatile("pmevent 0;" ::: "memory")
#define NB_SYNC(id, n) asm volatile("bar.sync %0, %1;" ::"n"(id), "n"(n) : "memory")
#define NB_ARRIVE(id, n) asm volatile("bar.arrive %0, %1;" ::"n"(id), "n"(n) : "memory")

#define TC(scr, k)
#define TP(scr, k)

#define R24(c, d)                                                                                        \
  c(d[0]), c(d[1]), c(d[2]), c(d[3]), c(d[4]), c(d[5]), c(d[6]), c(d[7]), c(d[8]), c(d[9]), c(d[10]),    \
      c(d[11]), c(d[12]), c(d[13]), c(d[14]), c(d[15]), c(d[16]), c(d[17]), c(d[18]), c(d[19]), c(d[20]), \
      c(d[21]), c(d[22]), c(d[23])
#define WG_TXT(sd)                                                                             \
  "wgmma.mma_async.sync.aligned.m64n96k16.f16.f16.f16 "                                        \
  "{%0,%1,%2,%3,%4,%5,%6,%7,%8,%9,%10,%11,%12,%13,%14,%15,%16,%17,%18,%19,%20,%21,%22,%23}, " \
  "{%24,%25,%26,%27}, %28, " sd ", 1, 1, 1;\n"

__device__ __forceinline__ void wg_acc(uint32_t (&d)[24], const uint32_t* a, uint64_t db) {
  asm volatile(WG_TXT("1") : R24("+r", d) : "r"(a[0]), "r"(a[1]), "r"(a[2]), "r"(a[3]), "l"(db));
}
__device__ __forceinline__ void wg_init(uint32_t (&d)[24], const uint32_t* a, uint64_t db) {
  asm volatile(WG_TXT("0") : R24("=r", d) : "r"(a[0]), "r"(a[1]), "r"(a[2]), "r"(a[3]), "l"(db));
}
template <int N>
__device__ __forceinline__ void rfence(uint32_t (&d)[N]) {
#pragma unroll
  for (int i = 0; i < N; i++) asm volatile("" : "+r"(d[i])::"memory");
}
template <bool INIT, int KSTRIDE>
__device__ __forceinline__ void gemm6(uint32_t (&d)[24], const uint32_t (&a)[24], uint64_t db) {
#pragma unroll
  for (int k = 0; k < 6; k++) {
    if (INIT && k == 0) wg_init(d, &a[0], db);
    else wg_acc(d, &a[4 * k], db + k * KSTRIDE);
  }
  WG_COMMIT();
}

__device__ __forceinline__ void mbar_init(uint32_t bar, uint32_t cnt) {
  asm volatile("mbarrier.init.shared::cta.b64 [%0], %1;" ::"r"(bar), "r"(cnt) : "memory");
}
__device__ __forceinline__ void mbar_expect(uint32_t bar, uint32_t bytes) {
  asm volatile("mbarrier.arrive.expect_tx.shared::cta.b64 _, [%0], %1;" ::"r"(bar), "r"(bytes) : "memory");
}
__device__ __forceinline__ void mbar_arrive_cluster(uint32_t bar) {
  asm volatile("mbarrier.arrive.shared::cluster.b64 _, [%0];" ::"r"(bar) : "memory");
}
__device__ __forceinline__ bool mbar_try(uint32_t bar, uint32_t parity) {
  uint32_t ok;
  asm volatile(
      "{\n.reg .pred p;\nmbarrier.try_wait.parity.shared::cta.b64 p, [%1], %2;\nselp.u32 %0, 1, 0, p;\n}\n"
      : "=r"(ok)
      : "r"(bar), "r"(parity)
      : "memory");
  return ok;
}
__device__ __forceinline__ bool mbar_test(uint32_t bar, uint32_t parity) {
  uint32_t ok;
  asm volatile(
      "{\n.reg .pred p;\nmbarrier.test_wait.parity.shared::cta.b64 p, [%1], %2;\nselp.u32 %0, 1, 0, p;\n}\n"
      : "=r"(ok)
      : "r"(bar), "r"(parity)
      : "memory");
  return ok;
}
__device__ __forceinline__ void mbar_wait(uint32_t bar, uint32_t parity) {
  if (__builtin_expect(mbar_try(bar, parity), 1)) return;
#pragma unroll 1
  for (uint32_t n = 0; n < (1u << 16) && !mbar_try(bar, parity); n++) {}
}
__device__ __forceinline__ uint32_t mapa(uint32_t addr, uint32_t rank) {
  uint32_t r;
  asm("mapa.shared::cluster.u32 %0, %1, %2;" : "=r"(r) : "r"(addr), "r"(rank));
  return r;
}
__device__ __forceinline__ void tma_raw(uint32_t dst, const CUtensorMap* tm, int rank, int w2, int h, uint32_t bar) {
  mbar_expect(bar, RAW_TX);
#pragma unroll
  for (int k = 0; k < 4; k++) {
    const int e = k & 1;
    asm volatile(
        "cp.async.bulk.tensor.4d.shared::cluster.global.mbarrier::complete_tx::bytes [%0], [%1, {%2, %3, %4, %5}], [%6];"
        ::"r"(dst + (k < 2 ? e * RAW_PA : 2 * RAW_PA + e * RAW_PB)), "l"(tm + (k >> 1)), "r"(k < 2 ? 64 * rank : 32 + 16 * rank), "r"(w2 + e),
        "r"(h), "r"(1 - e), "r"(bar)
        : "memory");
  }
}
__device__ __forceinline__ void bulk_load(uint32_t dst, const void* src, uint32_t bytes, uint32_t bar) {
  asm volatile("cp.async.bulk.shared::cluster.global.mbarrier::complete_tx::bytes [%0], [%1], %2, [%3];" ::"r"(dst),
               "l"(src), "r"(bytes), "r"(bar)
               : "memory");
}
__device__ __forceinline__ void bulk_load_last(uint32_t dst, const void* src, uint32_t bytes, uint32_t bar) {
  asm volatile(
      "{\n.reg .b64 pol;\ncreatepolicy.fractional.L2::evict_first.b64 pol, 1.0;\n"
      "cp.async.bulk.shared::cluster.global.mbarrier::complete_tx::bytes.L2::cache_hint [%0], [%1], %2, [%3], pol;\n}\n" ::"r"(dst),
      "l"(src), "r"(bytes), "r"(bar)
      : "memory");
}
__device__ __forceinline__ uint32_t pack_bf16(float lo, float hi) {
  uint32_t r;
  asm("cvt.rn.bf16x2.f32 %0, %1, %2;" : "=r"(r) : "f"(hi), "f"(lo));
  return r;
}
__device__ __forceinline__ uint32_t pack_f16(float lo, float hi) {
  uint32_t r;
  asm("cvt.rn.f16x2.f32 %0, %1, %2;" : "=r"(r) : "f"(hi), "f"(lo));
  return r;
}
__device__ __forceinline__ float bf_lo(uint32_t v) { return __uint_as_float(v << 16); }
__device__ __forceinline__ float bf_hi(uint32_t v) { return __uint_as_float(v & 0xffff0000u); }
__device__ __forceinline__ uint32_t bf_add(uint32_t a, uint32_t b) {
  uint32_t r;
  asm("add.rn.bf16x2 %0, %1, %2;" : "=r"(r) : "r"(a), "r"(b));
  return r;
}
__device__ __forceinline__ uint32_t bf_mul(uint32_t a, uint32_t b) {
  uint32_t r;
  asm("mul.rn.bf16x2 %0, %1, %2;" : "=r"(r) : "r"(a), "r"(b));
  return r;
}
__device__ __forceinline__ uint32_t bf_fma(uint32_t a, uint32_t b, uint32_t c) {
  uint32_t r;
  asm("fma.rn.bf16x2 %0, %1, %2, %3;" : "=r"(r) : "r"(a), "r"(b), "r"(c));
  return r;
}

__device__ __forceinline__ uint32_t h_add(uint32_t a, uint32_t b) {
  uint32_t r;
  asm("add.rn.f16x2 %0, %1, %2;" : "=r"(r) : "r"(a), "r"(b));
  return r;
}
__device__ __forceinline__ uint32_t h_mul(uint32_t a, uint32_t b) {
  uint32_t r;
  asm("mul.rn.f16x2 %0, %1, %2;" : "=r"(r) : "r"(a), "r"(b));
  return r;
}
__device__ __forceinline__ uint32_t h_fma(uint32_t a, uint32_t b, uint32_t c) {
  uint32_t r;
  asm("fma.rn.f16x2 %0, %1, %2, %3;" : "=r"(r) : "r"(a), "r"(b), "r"(c));
  return r;
}
__device__ __forceinline__ float h_sum(uint32_t v) {
  float lo, hi;
  asm("{\n.reg .b16 l, h;\nmov.b32 {l, h}, %2;\ncvt.f32.f16 %0, l;\ncvt.f32.f16 %1, h;\n}\n" : "=f"(lo), "=f"(hi) : "r"(v));
  return lo + hi;
}
__device__ __forceinline__ void lds128(uint32_t (&v)[4], uint32_t a) {
  asm volatile("ld.shared.v4.b32 {%0,%1,%2,%3}, [%4];" : "=r"(v[0]), "=r"(v[1]), "=r"(v[2]), "=r"(v[3]) : "r"(a) : "memory");
}

template <int LO, int HI>
__device__ __forceinline__ void gelu(uint32_t (&o)[24], const uint32_t (&d)[24]) {
#pragma unroll
  for (int qq = LO; qq < HI; qq++) {
    const int q = (qq + 4) % 24;
    uint32_t t, u;
    asm("fma.rn.f16x2 %0, %1, %1, %2;" : "=r"(t) : "r"(d[q]), "r"(GELU_K2));
    asm("mul.rn.f16x2 %0, %1, %2;" : "=r"(u) : "r"(d[q]), "r"(t));
    asm("tanh.approx.f16x2 %0, %1;" : "=r"(t) : "r"(u));
    asm("fma.rn.f16x2 %0, %1, %2, %1;" : "=r"(o[q]) : "r"(d[q]), "r"(t));
  }
}

__device__ __forceinline__ uint32_t laneid() {
  uint32_t l;
  asm volatile("mov.u32 %0, %%laneid;" : "=r"(l));
  return l;
}

__device__ __forceinline__ bool elect_one() {
  uint32_t p;
  asm volatile("{\n.reg .pred p;\nelect.sync _|p, 0xffffffff;\nselp.u32 %0, 1, 0, p;\n}\n" : "=r"(p));
  return p;
}

__device__ __forceinline__ uint32_t clock_pin() {
  uint32_t t;
  asm volatile("mov.u32 %0, %%clock;" : "=r"(t)::"memory");
  return t;
}

struct MlpCtx {
  uint32_t sb;
  uint32_t caddr;
  uint32_t xaddr;
  uint32_t unscale;
  uint32_t peer_off;
  int wg, warp, rank, zero;
  uint8_t* optr;
};

__device__ __forceinline__ void ln_wait(const MlpCtx& m, int i) { mbar_wait(m.sb + BAR_CFULL + 8 * m.wg, i & 1); }
__device__ __forceinline__ void ln_load(const MlpCtx& m, uint32_t (&c)[24]) {
#pragma unroll
  for (int p = 0; p < 6; p++)
    asm volatile("ld.shared.v4.b32 {%0,%1,%2,%3}, [%4];"
                 : "=r"(c[4 * p]), "=r"(c[4 * p + 1]), "=r"(c[4 * p + 2]), "=r"(c[4 * p + 3])
                 : "r"(m.caddr + p * 2048)
                 : "memory");
}
__device__ __forceinline__ void ln_shfl(float (&st)[8], int mask) {
#pragma unroll
  for (int k = 0; k < 4; k++) st[4 + k] = __shfl_xor_sync(0xffffffffu, st[k], mask);
}
__device__ __forceinline__ void ln_fold(float (&st)[8]) {
#pragma unroll
  for (int k = 0; k < 4; k++) st[k] += st[4 + k];
}
__device__ __forceinline__ void ln_sums(const uint32_t (&c)[24], float (&st)[8]) {
#pragma unroll
  for (int r = 0; r < 2; r++) {
    uint32_t s0 = h_add(c[r], c[r + 2]), s1 = h_add(c[r + 4], c[r + 6]), s2 = h_add(c[r + 8], c[r + 10]);
    uint32_t s3 = h_add(c[r + 12], c[r + 14]), s4 = h_add(c[r + 16], c[r + 18]), s5 = h_add(c[r + 20], c[r + 22]);
    s0 = h_add(s0, s1); s2 = h_add(s2, s3); s4 = h_add(s4, s5);
    st[r] = h_sum(h_add(h_add(s0, s2), s4));
    uint32_t q0 = h_mul(c[r], c[r]), q1 = h_mul(c[r + 2], c[r + 2]);
#pragma unroll
    for (int p = 2; p < 12; p += 2) {
      q0 = h_fma(c[2 * p + r], c[2 * p + r], q0);
      q1 = h_fma(c[2 * p + 2 + r], c[2 * p + 2 + r], q1);
    }
    st[2 + r] = h_sum(h_add(q0, q1));
  }
}
__device__ __forceinline__ void ln_release(const MlpCtx& m) {
  const uint32_t e = m.sb + BAR_CEMPTY + 8 * (2 * m.rank + m.wg);
  asm volatile(
      "{\n.reg .pred p, q;\nelect.sync _|p, 0xffffffff;\nsetp.eq.and.s32 q, %3, 0, p;\n"
      "@q mbarrier.arrive.expect_tx.shared::cta.b64 _, [%0], %4;\n"
      "@p mbarrier.arrive.shared::cluster.b64 _, [%1];\n"
      "@p mbarrier.arrive.shared::cluster.b64 _, [%2];\n}\n" ::"r"(m.sb + BAR_CFULL + 8 * m.wg),
      "r"(e), "r"(e + m.peer_off), "r"(m.warp), "n"(CTX)
      : "memory");
}
__device__ __forceinline__ bool ln_stats(float (&st)[8]) {
  bool ok = true;
#pragma unroll
  for (int r = 0; r < 2; r++) {
    const float nm = (st[r] + st[4 + r]) * (-1.0f / 96.0f);
    const float e2 = fmaf(st[2 + r] + st[6 + r], 1.0f / 96.0f, 1e-5f);
    float rs;
    asm("rsqrt.approx.ftz.f32 %0, %1;" : "=f"(rs) : "f"(fmaf(-nm, nm, e2)));
    ok = ok && (rs * rs * e2 <= 17.0f) && (e2 >= 1.001e-5f);
    const float rr = rs * GELU_A, dd = rr * nm;
    st[r] = __uint_as_float(pack_f16(rr, rr));
    st[2 + r] = __uint_as_float(pack_f16(dd, dd));
  }
  return ok;
}
__device__ __forceinline__ void ln_restat(bool ok, const uint32_t (&c)[24], float (&st)[8], uint32_t& bad, uint32_t bit,
                                          uint32_t zero) {
  if (__builtin_expect(__any_sync(0xffffffffu, !ok), 0)) {
#pragma unroll
    for (int r = 0; r < 2; r++) {
      float nm = 0.f, var = 0.f;
#pragma unroll
      for (int p = 0; p < 12; p++) {
        nm += h_sum(c[2 * p + r] ^ zero);
        if (p % 3 == 2) { asm volatile("" : "+f"(nm)); PIN(); }
      }
      nm += __shfl_xor_sync(0xffffffffu, nm, 1);
      nm += __shfl_xor_sync(0xffffffffu, nm, 2);
      nm *= -1.0f / 96.0f;
#pragma unroll
      for (int p = 0; p < 12; p++) {
        float lo, hi;
        asm volatile("{\n.reg .b16 l, h;\nmov.b32 {l, h}, %2;\ncvt.f32.f16 %0, l;\ncvt.f32.f16 %1, h;\n}\n" : "=f"(lo), "=f"(hi) : "r"(c[2 * p + r]));
        var = fmaf(lo + nm, lo + nm, fmaf(hi + nm, hi + nm, var));
        if (p % 3 == 2) { asm volatile("" : "+f"(var)); PIN(); }
      }
      var += __shfl_xor_sync(0xffffffffu, var, 1);
      var += __shfl_xor_sync(0xffffffffu, var, 2);
      const float rr = rsqrtf(fmaf(var, 1.0f / 96.0f, 1e-5f)) * GELU_A;
      st[r] = __uint_as_float(pack_f16(rr, rr));
      const float dd = 0.5f * h_sum(__float_as_uint(st[r])) * nm;
      st[2 + r] = __uint_as_float(pack_f16(dd, dd));
      if (!(rr >= 0x1p-14f && fabsf(dd) <= 16.0f && var >= 1e-8f)) bad |= bit;
    }
  }
}
__device__ __forceinline__ void ln_apply(uint32_t (&a)[24], const uint32_t (&c)[24], const float (&st)[8]) {
#pragma unroll
  for (int p = 0; p < 24; p++) {
    a[p] = h_fma(c[p], __float_as_uint(st[p & 1]), __float_as_uint(st[2 + (p & 1)]));
  }
}

__device__ __noinline__ void slow_tile(const __nv_bfloat16* x, const __nv_bfloat16* dw, const __nv_bfloat16* w1,
                                       const __nv_bfloat16* w2, __nv_bfloat16* out, int row0, int col0, float* buf) {
  const int lane = threadIdx.x & 31;
  for (int px = 0; px < 16; px++) {
    const int row = row0 + (px >> 3), col = col0 + (px & 7);
    float c[3] = {0.f, 0.f, 0.f};
    for (int i = 0; i < 7; i++)
      for (int j = 0; j < 7; j++) {
        const int rr = row + i - 3, cc = col + j - 3;
        if (rr < 0 || rr >= IMG || cc < 0 || cc >= IMG) continue;
        for (int k = 0; k < 3; k++)
          c[k] = fmaf(__bfloat162float(x[((size_t)rr * IMG + cc) * CH + lane + 32 * k]), __bfloat162float(dw[(i * 7 + j) * CH + lane + 32 * k]), c[k]);
      }
    float mean = (c[0] + c[1] + c[2]) * (1.0f / 96.0f);
    for (int o = 16; o; o >>= 1) mean += __shfl_xor_sync(0xffffffffu, mean, o);
    float var = 0.f;
    for (int k = 0; k < 3; k++) { c[k] -= mean; var = fmaf(c[k] * (1.0f / 96.0f), c[k], var); }
    for (int o = 16; o; o >>= 1) var += __shfl_xor_sync(0xffffffffu, var, o);
    const float rs = 1.0f / sqrtf(var + 1e-5f);
    __syncwarp();
    for (int k = 0; k < 3; k++) buf[lane + 32 * k] = c[k] * rs;
    __syncwarp();
    for (int n = lane; n < 4 * CH; n += 32) {
      float y = 0.f;
      for (int k = 0; k < CH; k++) y = fmaf(buf[k], __bfloat162float(w1[k * 4 * CH + n]), y);
      buf[CH + n] = 0.5f * y * (1.0f + tanhf(0.7978845608f * (y + 0.044715f * y * y * y)));
    }
    __syncwarp();
    for (int n = lane; n < CH; n += 32) {
      float o = 0.f;
      for (int k = 0; k < 4 * CH; k++) o = fmaf(buf[CH + k], __bfloat162float(w2[k * CH + n]), o);
      const size_t idx = ((size_t)row * IMG + col) * CH + n;
      out[idx] = __float2bfloat16(__bfloat162float(x[idx]) + o);
    }
  }
}

__device__ __forceinline__ void x_load(const MlpCtx& m, uint32_t (&x)[24]) {
#pragma unroll
  for (int k = 0; k < 6; k++)
    asm volatile("ld.shared.v4.b32 {%0,%1,%2,%3}, [%4];"
                 : "=r"(x[4 * k]), "=r"(x[4 * k + 1]), "=r"(x[4 * k + 2]), "=r"(x[4 * k + 3])
                 : "r"(m.xaddr + (k / 3) * 384 + (k % 3) * 64)
                 : "memory");
}
template <int LO, int HI>
__device__ __forceinline__ void epilogue(const MlpCtx& m, const uint32_t (&d)[24], uint32_t (&x)[24]) {
#pragma unroll
  for (int k = LO; k < HI; k++) {
    const int r = k / 3, q = k % 3;
    uint32_t* y = &x[4 * k];
#pragma unroll
    for (int j = 0; j < 4; j++) {
      uint32_t v = d[2 * (4 * q + j) + r];
      float lo, hi;
      asm("{\n.reg .b16 l, h;\nmov.b32 {l, h}, %2;\ncvt.f32.f16 %0, l;\ncvt.f32.f16 %1, h;\n}\n" : "=f"(lo), "=f"(hi) : "r"(v));
      asm("fma.rn.bf16x2 %0, %1, %2, %0;" : "+r"(y[j]) : "r"(pack_bf16(lo, hi)), "r"(m.unscale));
    }
    asm volatile("st.shared.v4.b32 [%0], {%1,%2,%3,%4};" ::"r"(m.xaddr + r * 384 + q * 64), "r"(y[0]), "r"(y[1]), "r"(y[2]), "r"(y[3])
                 : "memory");
  }
}
__device__ __forceinline__ void out_store(const MlpCtx& m, int i) {
  asm volatile("fence.proxy.async.shared::cta;" ::: "memory");
  __syncwarp();
  if (elect_one()) {
    const uint32_t src = m.sb + OFF_XRES + m.wg * 12288 + m.warp * 1536;
    uint8_t* dst = m.optr + (size_t)i * (8 * IMG * CH * 2);
    asm volatile("cp.async.bulk.global.shared::cta.bulk_group [%0], [%1], 1536;" ::"l"(dst), "r"(src) : "memory");
    asm volatile("cp.async.bulk.global.shared::cta.bulk_group [%0], [%1], 1536;" ::"l"(dst + IMG * CH * 2), "r"(src + 6144) : "memory");
    asm volatile("cp.async.bulk.commit_group;" ::: "memory");
  }
}

#define FSET 3
template <int J> constexpr bool goes_first = J == FSET || J == ((FSET + 1) & 3);
template <int J> __device__ __forceinline__ void tok_wait() {
  if (goes_first<J>) NB_SYNC(NB_CLOSE, 256);
  else NB_SYNC(NB_SEC + (J & 1), 256);
}
template <int J, bool PROD = true> __device__ __forceinline__ void tok_next() {
  if (goes_first<J>) NB_ARRIVE(NB_SEC + (J & 1), 256);
  if (J == 0 && PROD) NB_ARRIVE(NB_PROD, 160);
}
__device__ __forceinline__ void tok_pass() { NB_ARRIVE(NB_OPEN, 416); }
template <int J> __device__ __forceinline__ void tok_idle() { tok_wait<J>(); tok_next<J, false>(); tok_pass(); }

constexpr uint64_t CHK = 1152;

__device__ __forceinline__ float warp_sumsq(const uint32_t (&q)[4]) {
  const uint32_t t = bf_add(bf_add(q[0], q[1]), bf_add(q[2], q[3]));
  float f = bf_lo(t) + bf_hi(t);
#pragma unroll
  for (int o = 16; o; o >>= 1) f += __shfl_xor_sync(0xffffffffu, f, o);
  return f;
}
__device__ __forceinline__ int norm_exp(float f) { return (((int)(__float_as_uint(f * 1.5f) >> 23) - 127) >> 1) + 1; }
__device__ __forceinline__ int scale_exp(int e1, int e2) { return min(11 - e1 - e2, 14 - e2); }

__device__ __forceinline__ void convert_tile(int t, int k, const uint4* w1, const uint4* w2, uint32_t st, Scratch* scr) {
  const int lane = threadIdx.x & 31, k7 = lane & 7;
  const int j = t / 6, ks = t % 6, e = ks % 3, t4 = k7 >> 1;
  const uint4* src = t < 24 ? w1 + ((e < 2 ? 64 * (ks / 3) + 8 * t4 + 4 * e : 32 + 16 * (ks / 3) + 4 * t4) + (k7 & 1)) * 48 + j * 12 + (lane >> 3)
                            : w2 + (t - 24) * 192 + (lane >> 2) * 12 + (lane & 3);
  src += (k / 3) * 96 + (k % 3) * 4;
  if (k >= 6) src = (k == 6 ? w1 : w2) + lane * 145;
  const uint4 v = __ldg(src);
  const uint32_t w[4] = {v.x, v.y, v.z, v.w};
  const uint32_t q[4] = {bf_mul(v.x, v.x), bf_mul(v.y, v.y), bf_mul(v.z, v.z), bf_mul(v.w, v.w)};
  asm volatile("st.shared.f32 [%0], %1;" ::"r"(st + 3088 + 4 * k), "f"(warp_sumsq(q)) : "memory");
  NB_SYNC(NB_PREP, 256);
  uint32_t a[4], b[4], o[4];
  lds128(a, st + 3088);
  lds128(b, st + 3104);
  const int s = max(-64, min(64, scale_exp(norm_exp(144.f * __uint_as_float(b[2])), norm_exp(144.f * __uint_as_float(b[3]))) - 3));
  const uint32_t dst = st + k7 * 16 + (lane >> 3) * 256 + (k / 3) * 128 + (k % 3) * 1024;
  if (k >= 6) {
    const float f = ((__uint_as_float(a[0]) + __uint_as_float(a[1])) + (__uint_as_float(a[2]) + __uint_as_float(a[3]))) +
                    (__uint_as_float(b[0]) + __uint_as_float(b[1]));
    asm volatile("st.shared.v2.b32 [%0], {%1,%2};" ::"r"(st + 3072), "r"(__float_as_uint(f)), "r"(s) : "memory");
  } else if (t < 24) {
#pragma unroll
    for (int i = 0; i < 4; i++) o[i] = pack_f16(bf_lo(w[i]), bf_hi(w[i]));
    asm volatile("st.shared.v4.b32 [%0], {%1,%2,%3,%4};" ::"r"(dst), "r"(o[0]), "r"(o[1]), "r"(o[2]), "r"(o[3]) : "memory");
  } else {
    constexpr float F = 0.5f / GELU_A, FHI = 1.515625f;
    const float p2 = __uint_as_float((uint32_t)(127 + s - 56) << 23);
    const uint32_t hi = pack_bf16(FHI * 0x1p-56f, FHI * 0x1p-56f), lo = pack_bf16((F - FHI) * 0x1p-56f, (F - FHI) * 0x1p-56f);
    const uint32_t pw = pack_bf16(p2, p2);
#pragma unroll
    for (int i = 0; i < 4; i++) {
      const uint32_t ws = bf_mul(w[i], pw), u = bf_fma(ws, hi, bf_mul(ws, lo));
      o[i] = (u & 0x7fff7fffu) * 7u + u;
    }
    asm volatile("stmatrix.sync.aligned.m8n8.x4.shared.b16 [%0], {%1,%2,%3,%4};" ::"r"(dst), "r"(o[0]), "r"(o[1]), "r"(o[2]), "r"(o[3])
                 : "memory");
  }
  asm volatile("fence.proxy.async.shared::cta;" ::: "memory");
  NB_SYNC(NB_PREP, 256);
  if (k == 0 && elect_one()) {
    asm volatile("cp.async.bulk.global.shared::cta.bulk_group [%0], [%1], 3072;" ::"l"(scr->w + t * 192), "r"(st) : "memory");
    asm volatile("cp.async.bulk.global.shared::cta.bulk_group [%0], [%1], 16;" ::"l"(scr->nrm + t), "r"(st + 3072) : "memory");
    asm volatile("cp.async.bulk.commit_group;" ::: "memory");
    asm volatile("cp.async.bulk.wait_group 0;" ::: "memory");
    asm volatile("red.relaxed.gpu.global.add.u32 [%0], 1;" ::"l"(&scr->done) : "memory");
  }
}

__device__ __forceinline__ uint32_t mlp_role(const MlpCtx& m0) {
  MlpCtx m = m0;
  uint32_t bad = 0;
  asm volatile("barrier.cluster.wait.aligned;" ::: "memory");
  if ((m.sb & 0x3FFFF) != 1024) bad = 0xffffu;
  constexpr uint64_t dW1 = (uint64_t)((1024 + OFF_W1) >> 4) | ((uint64_t)8 << 16) | ((uint64_t)16 << 32);
  constexpr uint64_t dW2 = dW1 + (OFF_W2 >> 4);
  uint32_t A1[24], g[24], d[24], cn[24], D2[24];
  float st[8];
  if (m.wg & m.rank) tok_idle<3>();
  else if (m.wg) tok_idle<0>();
  else if (m.rank) tok_idle<1>();
  ln_wait(m, 0);
  ln_load(m, cn);
  ln_sums(cn, st);
  ln_shfl(st, 1);
  ln_release(m);
  ln_fold(st);
  ln_shfl(st, 2);
  ln_restat(ln_stats(st), cn, st, bad, 1, m.zero);
  ln_apply(A1, cn, st);
  {
    const int lane = threadIdx.x & 31;
    mbar_wait(m.sb + BAR_W, 0);
    float n1, n2;
    int s;
    asm volatile("ld.shared.b32 %0, [%1];" : "=r"(s) : "r"(m.sb + OFF_NRM + 4) : "memory");
    asm volatile("ld.shared.f32 %0, [%1];" : "=f"(n1) : "r"(m.sb + OFF_NRM + 16 * min(lane, 23)) : "memory");
    asm volatile("ld.shared.f32 %0, [%1];" : "=f"(n2) : "r"(m.sb + OFF_NRM + 384 + 16 * min(lane, 23)) : "memory");
    if (lane >= 24) n1 = n2 = 0.f;
#pragma unroll
    for (int o = 16; o; o >>= 1) {
      n1 += __shfl_xor_sync(0xffffffffu, n1, o);
      n2 += __shfl_xor_sync(0xffffffffu, n2, o);
    }
    const int e1 = norm_exp(n1), e2 = norm_exp(n2), smax = scale_exp(e1, e2);
    if (e1 > 12 || e1 < -5 || e2 > 50 || e2 < -50 || s > smax || s < smax - 7) bad = 0xffffu;
    m.unscale = __shfl_sync(0xffffffffu, ((uint32_t)(127 - s) << 7) * 0x10001u, 0);
  }
  if (m.wg & m.rank) tok_idle<0>();
  if (m.wg) tok_idle<1>();
  {
    uint32_t d0[24];
    WG_FENCE();
    tok_wait<2>();
    tok_next<2>();
    gemm6<true, 192>(d0, A1, dW1);
    tok_pass(); PIN();
    WG_WAIT0(); rfence(d0);
    WG_FENCE();
    tok_wait<3>();
    tok_next<3>();
    gemm6<true, 192>(d, A1, dW1 + CHK);
    tok_pass(); PIN();
    gelu<0, 24>(g, d0);
    PIN();
    mbar_wait(m.sb + BAR_W + 8, 0);
    ln_wait(m, 1);
    WG_WAIT0(); rfence(d);
  }
#define G2(INIT, a, j)                      \
  WG_FENCE();                               \
  tok_wait<j>();                            \
  gemm6<INIT, 192>(D2, a, dW2 + (j) * CHK); \
  tok_next<j>(); PIN();
#define G1(dst, j, P)                       \
  P(); WG_WAIT0(); rfence(D2);              \
  WG_FENCE();                               \
  gemm6<true, 192>(dst, A1, dW1 + (j) * CHK); \
  tok_pass(); P();
#define ROUND_END(dst, j)                   \
  PIN(); WG_WAIT0(); rfence(dst);
#define GA 9
#define GB 12
#define GC 13
#define GD 11
#pragma unroll 1
  for (int i = 0;; i++) {
    uint32_t g1[24], d2[24], g2[24], d3[24], g3[24], d0[24];
    ln_load(m, cn);
    PIN();
    G2(true, g, 0)
    gelu<0, GA>(g1, d);
    G1(d2, 2, PIN)
    ln_sums(cn, st);
    gelu<GA, 24>(g1, d);
    PIN();
    ln_shfl(st, 1);
    ROUND_END(d2, 0)

    G2(false, g1, 1)
    ln_fold(st);
    gelu<0, GB>(g2, d2);
    PIN();
    ln_shfl(st, 2);
    G1(d3, 3, PIN)
    const bool ok = ln_stats(st);
    gelu<GB, 24>(g2, d2);
    PIN();
    ln_restat(ok, cn, st, bad, 2u << i, m.zero);
    ROUND_END(d3, 1)

    if (i == 15) {
      G2(false, g2, 2)
      tok_pass();
      gelu<0, 24>(g3, d3);
      PIN();
      x_load(m, cn);
      ROUND_END(D2, 2)
      G2(false, g3, 3)
      tok_pass();
      WG_WAIT0(); rfence(D2);
      epilogue<0, 6>(m, D2, cn);
      break;
    }
    G2(false, g2, 2)
    ln_apply(A1, cn, st);
    PIN();
    gelu<0, GC>(g3, d3);
    G1(d0, 0, PIN)
    gelu<GC, 24>(g3, d3);
    PIN();
    x_load(m, cn);
    ROUND_END(d0, 2)

    G2(false, g3, 3)
    gelu<0, GD>(g, d0);
    G1(d, 1, PIN)
    epilogue<0, 6>(m, D2, cn);
    gelu<GD, 24>(g, d0);
    PIN();
    asm volatile("fence.proxy.async.shared::cta;" ::: "memory");
    ROUND_END(d, 3)
  }
  out_store(m, 15);
  if (m.wg == 0) { tok_idle<0>(); tok_idle<1>(); }
  asm volatile("cp.async.bulk.wait_group.read 0;" ::: "memory");
  return __reduce_or_sync(0xffffffffu, bad & 0xffffu);
}

struct ConvCtx {
  uint32_t sb;
  uint32_t a0, a_c;
  uint32_t peer_off;
  int rank, v, c0, r0, zero;
  const CUtensorMap* tm;
  Scratch* scr;
  const uint8_t* xsrc;
  uint8_t* optr;
};

__device__ __forceinline__ void raw_refill(const ConvCtx& c, int s) {
  if (s + 4 < NSTEP && elect_one())
    tma_raw(c.sb + OFF_RAW + (s & 3) * RAW_BYTES, c.tm, c.rank, c.c0 / 2 - 2, c.r0 - 3 + 2 * (s + 4), c.sb + BAR_RAW + 8 * (s & 3));
}
__device__ __forceinline__ void step_ready(const ConvCtx& c, int s) {
  const int nx = (s + 1) & 3, par = ((s + 1) >> 2) & 1;
  if (s + 1 < NSTEP) mbar_wait(c.sb + BAR_RAW + 8 * nx, par);
  if (s >= 7 && s < NSTEP) mbar_wait(c.sb + BAR_CEMPTY + 8 * (2 * (nx & 1) + (nx >> 1)), par);
}

__device__ __forceinline__ void c_release(const ConvCtx& c, uint32_t w) {
  const uint32_t e = c.sb + BAR_CEMPTY + 8 * (2 * c.rank + w);
  asm volatile(
      "{\n.reg .pred p;\nelect.sync _|p, 0xffffffff;\n"
      "@p mbarrier.arrive.expect_tx.shared::cta.b64 _, [%0], %3;\n"
      "@p mbarrier.arrive.shared::cluster.b64 _, [%1], 4;\n"
      "@p mbarrier.arrive.shared::cluster.b64 _, [%2], 4;\n}\n" ::"r"(c.sb + BAR_CFULL + 8 * w),
      "r"(e), "r"(e + c.peer_off), "n"(CTX)
      : "memory");
}

__device__ __forceinline__ void prod_rows(const ConvCtx& c) {
#pragma unroll 1
  for (int s = 0; s < NROUND + SIGMA + c.rank; s++) {
    const int r = s - SIGMA - c.rank;
    const int u = (r & 1) ? (r >> 1) - 1 : (r >> 1) + 2;
    step_ready(c, s);
    if (s < 16) TP(c.scr, 100 + s);
    if (u >= ((r & 1) ? 0 : 4) && u < 32) mbar_wait(c.sb + ((r & 1) ? BAR_XFULL : BAR_CFULL) + 8 * (u & 1), (u >> 1) & 1);
    if (s < SIGMA) NB_SYNC(NB_PLAN, 160);
    else NB_SYNC(NB_OPEN, 416);
    TP(c.scr, s);
    if (r == 3) TC(c.scr, 1);
    if (r == 55) TC(c.scr, 2);
    raw_refill(c, s);
  }
}
__device__ __forceinline__ void prod_tiles(const ConvCtx& c) {
  asm volatile("barrier.cluster.wait.aligned;" ::: "memory");
#pragma unroll 1
  for (int n = 1; n < 33; n++) {
    const uint32_t w = (n + 1) & 1;
    const uint32_t buf = c.sb + OFF_XRES + w * 12288;
    NB_SYNC(NB_PROD, 160);
    if (n < 29) c_release(c, w);
    if (n >= 3) {
      uint8_t* dst = c.optr + (size_t)(n - 3) * (4 * IMG * CH * 2);
      if (elect_one()) {
        asm volatile("cp.async.bulk.global.shared::cta.bulk_group [%0], [%1], 6144;" ::"l"(dst), "r"(buf) : "memory");
        asm volatile("cp.async.bulk.global.shared::cta.bulk_group [%0], [%1], 6144;" ::"l"(dst + IMG * CH * 2), "r"(buf + 6144) : "memory");
        asm volatile("cp.async.bulk.commit_group;" ::: "memory");
        asm volatile("cp.async.bulk.wait_group.read 0;" ::: "memory");
      }
      __syncwarp();
    }
    {
      const uint8_t* src = c.xsrc + (size_t)(n - 1) * (4 * IMG * CH * 2);
      if (elect_one()) {
        mbar_expect(c.sb + BAR_XFULL + 8 * w, 12288);
        bulk_load_last(buf, src, 6144, c.sb + BAR_XFULL + 8 * w);
        bulk_load_last(buf + 6144, src + IMG * CH * 2, 6144, c.sb + BAR_XFULL + 8 * w);
      }
    }
  }
  asm volatile("cp.async.bulk.wait_group 0;" ::: "memory");
}

template <int LO, int HI>
__device__ __forceinline__ void conv_ld8(uint32_t a0, uint32_t (&r)[6][6]) {
  const uint32_t a2 = a0 ^ (16 | ((a0 >> 2) & 32));
  const uint32_t a[3] = {a0, (a0 & 64) ? a2 : a0, a2};
#pragma unroll
  for (int j = LO; j < HI; j++)
    asm volatile("ld.shared.v4.b32 {%0,%1,%2,%3}, [%4];"
                 : "=r"(r[j][0]), "=r"(r[j][1]), "=r"(r[j][2]), "=r"(r[j][3])
                 : "r"(a[j >> 1] + (j >> 1) * 64 + (j & 1) * RAW_PA)
                 : "memory");
}
__device__ __forceinline__ void conv_ld4(uint32_t a0, uint32_t stage, int v, uint32_t (&r)[6][6]) {
  const uint32_t ab = ((a0 >> 1) & ~31u) + (stage / 2 + 2 * RAW_PA + 8 * v);
#pragma unroll
  for (int j = 0; j < 6; j++) {
    uint32_t a = ab + (j >> 1) * 32;
    asm volatile("ld.shared.v2.b32 {%0,%1}, [%2];" : "=r"(r[j][4]), "=r"(r[j][5]) : "r"(a + (j & 1) * RAW_PB) : "memory");
  }
}
template <int LO, int HI>
__device__ __forceinline__ void conv_frags(uint32_t zero, const uint32_t (&r)[6][6], uint32_t (&A)[12][4]) {
#pragma unroll
  for (int ch = LO; ch < HI; ch++) {
    const uint32_t sel = (ch & 1) ? 0x7632 : 0x5410;
    A[ch][0] = __byte_perm(r[0][ch >> 1], r[1][ch >> 1], sel);
    A[ch][1] = __byte_perm(r[2][ch >> 1], r[3][ch >> 1], sel);
    A[ch][2] = A[ch][1] ^ zero;
    A[ch][3] = __byte_perm(r[4][ch >> 1], r[5][ch >> 1], sel);
    rfence(A[ch]);
  }
}
__device__ __forceinline__ void hmma_acc(uint32_t (&v)[4], const uint32_t (&a)[4], const uint32_t* b) {
  asm volatile("mma.sync.aligned.m16n8k16.row.col.f32.bf16.bf16.f32 {%0,%1,%2,%3}, {%4,%5,%6,%7}, {%8,%9}, {%0,%1,%2,%3};"
               : "+r"(v[0]), "+r"(v[1]), "+r"(v[2]), "+r"(v[3])
               : "r"(a[0]), "r"(a[1]), "r"(a[2]), "r"(a[3]), "r"(b[0]), "r"(b[1]));
}
__device__ __forceinline__ void hmma_new(uint32_t (&a)[4], const uint32_t* b) {
  asm volatile("mma.sync.aligned.m16n8k16.row.col.f32.bf16.bf16.f32 {%0,%1,%2,%3}, {%0,%1,%2,%3}, {%4,%5}, {%6,%6,%6,%6};"
               : "+r"(a[0]), "+r"(a[1]), "+r"(a[2]), "+r"(a[3])
               : "r"(b[0]), "r"(b[1]), "f"(0.f));
}

#define EARLY 5
__device__ __forceinline__ void conv_send(bool local, const uint32_t (&pk)[12], uint32_t dst, uint32_t bar) {
  if (local) {
#pragma unroll
    for (int q = 0; q < 3; q++)
      asm volatile("st.shared.v4.b32 [%0], {%1,%2,%3,%4};" ::"r"(dst + q * 2048), "r"(pk[4 * q]), "r"(pk[4 * q + 1]), "r"(pk[4 * q + 2]), "r"(pk[4 * q + 3])
                   : "memory");
    asm volatile("{\n.reg .pred p;\nelect.sync _|p, 0xffffffff;\n@p mbarrier.arrive.shared::cta.b64 _, [%0];\n}\n" ::"r"(bar) : "memory");
  } else {
#pragma unroll
    for (int q = 0; q < 3; q++)
      asm volatile("st.async.weak.shared::cluster.mbarrier::complete_tx::bytes.v4.b32 [%0], {%1,%2,%3,%4}, [%5];" ::"r"(dst + q * 2048),
                   "r"(pk[4 * q]), "r"(pk[4 * q + 1]), "r"(pk[4 * q + 2]), "r"(pk[4 * q + 3]), "r"(bar)
                   : "memory");
  }
}
template <int S2, bool GATED>
__device__ __forceinline__ void conv_step(const ConvCtx& c, int s, uint32_t (&K)[12], uint32_t (&V)[12][4], const uint32_t (&B)[12][4],
                                          uint32_t (&A)[12][4]) {
  const int nx = ((s + 1) & 2) | (S2 ^ 1);
  uint32_t r[6][6], pk[12];
  const uint32_t a0 = c.a0 + nx * RAW_BYTES;
  if (GATED) NB_SYNC(NB_OPEN, 416);
  else NB_SYNC(NB_PLAN, 160);
  conv_ld4(a0, c.sb + OFF_RAW + nx * RAW_BYTES, c.v, r);
  if (GATED) PIN();
#pragma unroll
  for (int ch = 0; ch < 12; ch++) hmma_acc(V[11 - ch], A[11 - ch], &B[11 - ch][2]);
#pragma unroll
  for (int ch = 0; ch < 12 - EARLY; ch++) hmma_new(A[ch], &B[ch][0]);
  const uint32_t zero = GATED ? c.zero & clock_pin() : c.zero;
  if (GATED) NB_ARRIVE(NB_CLOSE, 256);
#pragma unroll
  for (int ch = 12 - EARLY; ch < 12; ch++) hmma_new(A[ch], &B[ch][0]);
  if (GATED) PIN();
  const bool local = (S2 ^ 1) == c.rank;
  const uint32_t off = local ? 0u : c.peer_off;
  const uint32_t dst = c.a_c + off + (nx >> 1) * C_BYTES;
  const uint32_t bar = c.sb + off + BAR_CFULL + 8 * (nx >> 1);
#pragma unroll
  for (int q = 0; q < 12; q++) {
    const int ch = q & ~1, h = 2 * (q & 1);
    pk[q] = h_add(K[q], pack_f16(__uint_as_float(V[ch][h + 1]), __uint_as_float(V[ch + 1][h])));
  }
#pragma unroll
  for (int q = 0; q < 12; q++) {
    const int ch = q & ~1, h = 2 * (q & 1);
    K[q] = pack_f16(__uint_as_float(V[ch][h]), __uint_as_float(V[ch + 1][h + 1]));
  }
  rfence(K);
  rfence(pk);
  PIN();
  conv_ld8<0, 4>(a0, r);
  if (GATED || s >= 3) conv_send(local, pk, dst, bar);
  conv_frags<8, 12>(zero, r, V);
  PIN();
  conv_ld8<4, 6>(a0, r);
  conv_frags<0, 8>(zero, r, V);
  PIN();
}

__device__ __forceinline__ void conv_role(ConvCtx c) {
  const int lane = laneid(), g = lane >> 2, t = lane & 3;
  const int u = (t >> 1) * 19 + 2 * (g + (t & 1));
  c.a0 = c.sb + OFF_RAW + u * 64 + ((c.v ^ (u >> 1)) & 3) * 16;
  c.a_c = c.sb + OFF_C + 6144 * c.rank + 512 * c.v + ((lane + 2 * c.v) & 31) * 16;
  uint32_t B[12][4];
  {
    const int dc = (g >> 1) & 1, ro = g >> 2, rk = t >> 1;
    const int i0 = 4 * (g & 1) + rk - ro, j0 = 4 * (t & 1) - dc;
    const uint32_t base = c.sb + OFF_XRES + (i0 * 7 + j0) * 192;
    asm volatile("barrier.cluster.wait.aligned;" ::: "memory");
    mbar_wait(c.sb + BAR_W + 48, 0);
#pragma unroll
    for (int b = 0; b < 2; b++) {
      uint32_t w[4][6];
#pragma unroll
      for (int k = 0; k < 4; k++) {
        const int ok = (unsigned)(i0 + 2 * b) < 7u && (unsigned)(j0 + k) < 7u;
#pragma unroll
        for (int q = 0; q < 6; q++) w[k][q] = 0;
        asm volatile(
            "{\n.reg .pred p;\nsetp.ne.s32 p, %8, 0;\n@p ld.shared.v4.b32 {%0,%1,%2,%3}, [%6];\n@p ld.shared.v2.b32 {%4,%5}, [%7];\n}\n"
            : "+r"(w[k][0]), "+r"(w[k][1]), "+r"(w[k][2]), "+r"(w[k][3]), "+r"(w[k][4]), "+r"(w[k][5])
            : "r"(base + (b * 14 + k) * 192 + 128 * c.rank + 16 * c.v), "r"(base + (b * 14 + k) * 192 + 64 + 32 * c.rank + 8 * c.v), "r"(ok)
            : "memory");
      }
#pragma unroll
      for (int q = 0; q < 6; q++) {
        B[2 * q][2 * b] = __byte_perm(w[0][q], w[1][q], 0x5410);
        B[2 * q][2 * b + 1] = __byte_perm(w[2][q], w[3][q], 0x5410);
        B[2 * q + 1][2 * b] = __shfl_xor_sync(0xffffffffu, __byte_perm(w[0][q], w[1][q], 0x7632), 4);
        B[2 * q + 1][2 * b + 1] = __shfl_xor_sync(0xffffffffu, __byte_perm(w[2][q], w[3][q], 0x7632), 4);
      }
    }
  }
  uint32_t K1[12], K2[12], V[12][4];
#pragma unroll
  for (int ch = 0; ch < 12; ch++)
    asm volatile("" : "=r"(K1[ch]), "=r"(K2[ch]), "=r"(V[ch][0]), "=r"(V[ch][1]), "=r"(V[ch][2]), "=r"(V[ch][3]));
  uint32_t A[12][4], r[6][6];
  mbar_wait(c.sb + BAR_RAW, 0);
  conv_ld8<0, 6>(c.a0, r);
  conv_ld4(c.a0, c.sb + OFF_RAW, c.v, r);
  conv_frags<0, 12>(c.zero, r, A);
  PIN();
  NB_ARRIVE(NB_CLOSE, 256);
#pragma unroll 1
  for (int s = 0; s < SIGMA; s += 2) {
    conv_step<0, false>(c, s, K1, V, B, A);
    conv_step<1, false>(c, s + 1, K2, A, B, V);
  }
#pragma unroll 1
  for (int s = SIGMA;; s += 2) {
    conv_step<0, true>(c, s, K1, V, B, A);
    if (s == NSTEP - 1) break;
    conv_step<1, true>(c, s + 1, K2, A, B, V);
  }
#pragma unroll 1
  for (int r = NSTEP - SIGMA - c.rank; r < NROUND - 1; r++) {
    NB_SYNC(NB_OPEN, 416);
    NB_ARRIVE(NB_CLOSE, 256);
  }
  NB_SYNC(NB_OPEN, 416);
}

struct TMaps { CUtensorMap m[2]; };

__global__ void __cluster_dims__(2, 1, 1) __launch_bounds__(512, 1)
convnext_kernel(const __grid_constant__ TMaps tms, const __nv_bfloat16* __restrict__ x, const __nv_bfloat16* __restrict__ dw,
                const __nv_bfloat16* __restrict__ w1, const __nv_bfloat16* __restrict__ w2, __nv_bfloat16* __restrict__ out,
                Scratch* scr, int zero) {
  extern __shared__ __align__(1024) uint8_t smem[];
  const uint32_t sb = (uint32_t)__cvta_generic_to_shared(smem);
  const int tid = threadIdx.x, lane = tid & 31;
  const int wid = __shfl_sync(0xffffffffu, tid >> 5, 0);
  const int rank = blockIdx.x & 1, cl = blockIdx.x >> 1;
  const int c0 = (cl & 15) * 32, r0 = (cl >> 4) * 128;
  const uint32_t peer_off = mapa(sb, rank ^ 1) - sb;

  if (wid == 12 && elect_one()) {
    mbar_init(sb + BAR_W + 48, 1);
#pragma unroll
    for (int i = 0; i < 4; i++) mbar_init(sb + BAR_RAW + 8 * i, 1);
    asm volatile("fence.mbarrier_init.release.cluster;" ::: "memory");
    mbar_expect(sb + BAR_W + 48, 49 * CH * 2);
    bulk_load(sb + OFF_XRES, dw, 49 * CH * 2, sb + BAR_W + 48);
#pragma unroll
    for (int i = 0; i < E0; i++) tma_raw(sb + OFF_RAW + i * RAW_BYTES, tms.m, rank, c0 / 2 - 2, r0 - 3 + 2 * i, sb + BAR_RAW + 8 * i);
  }
  if (wid == 14 && elect_one()) {
    asm volatile("prefetch.tensormap [%0];" ::"l"(&tms.m[1]) : "memory");
#pragma unroll
    for (int i = 0; i < 3; i++) mbar_init(sb + BAR_W + 8 * i, 1);
#pragma unroll
    for (int i = 0; i < 2; i++) mbar_init(sb + BAR_CFULL + 8 * i, CCNT);
#pragma unroll
    for (int i = 0; i < 4; i++) mbar_init(sb + BAR_CEMPTY + 8 * i, 4);
#pragma unroll
    for (int i = 0; i < 2; i++) mbar_init(sb + BAR_XFULL + 8 * i, 1);
#pragma unroll
    for (int i = 0; i < 2; i++) mbar_expect(sb + BAR_CFULL + 8 * i, CTX);
    asm volatile("fence.mbarrier_init.release.cluster;" ::: "memory");
  }
  __syncwarp();
  asm volatile("barrier.cluster.arrive.relaxed.aligned;" ::: "memory");

  if (wid < 8) {
    if (blockIdx.x < 48) convert_tile(blockIdx.x, wid, reinterpret_cast<const uint4*>(w1), reinterpret_cast<const uint4*>(w2), sb, scr);
    MlpCtx m;
    m.sb = sb; m.wg = wid >> 2; m.warp = wid & 3; m.rank = rank; m.peer_off = peer_off; m.zero = zero;
    m.optr = reinterpret_cast<uint8_t*>(out) + ((size_t)(r0 + 4 * m.wg + 2 * rank) * IMG + c0 + 8 * m.warp) * (CH * 2);
    m.caddr = sb + OFF_C + m.wg * C_BYTES + (lane & 3) * 512 + ((m.warp * 8 + (lane >> 2) + 2 * (lane & 3)) & 31) * 16;
    m.xaddr = sb + OFF_XRES + m.wg * 12288 + m.warp * 1536 + ((lane >> 3) & 1) * 6144 + ((lane >> 4) * 4 + ((lane >> 2) & 1)) * 192 + (lane & 3) * 16;
    m.unscale = 0;
    asm volatile("setmaxnreg.inc.sync.aligned.u32 %0;" ::"n"(REG_MLP));
    const uint32_t bad = mlp_role(m);
    TC(scr, 3);
    if (bad) {
      asm volatile("cp.async.bulk.wait_group 0;" ::: "memory");
      mbar_wait(sb + BAR_W + 16, 0);
      __syncwarp();
      asm volatile("fence.proxy.async;" ::: "memory");
#pragma unroll 1
      for (int i = 0; i < 16; i++)
        if (bad >> i & 1)
          slow_tile(x, dw, w1, w2, out, r0 + 8 * i + 4 * m.wg + 2 * rank, c0 + 8 * m.warp,
                    reinterpret_cast<float*>(smem + OFF_RAW + wid * 2048));
    }
  } else {
    ConvCtx c;
    c.sb = sb; c.rank = rank; c.v = wid - 8; c.c0 = c0; c.r0 = r0; c.zero = zero; c.tm = tms.m; c.scr = scr;
    c.peer_off = peer_off;
    c.xsrc = reinterpret_cast<const uint8_t*>(x) + ((size_t)(r0 + 2 * rank) * IMG + c0) * (CH * 2);
    c.optr = reinterpret_cast<uint8_t*>(out) + ((size_t)(r0 + 2 * rank) * IMG + c0) * (CH * 2);
    if (wid < 12) {
      asm volatile("setmaxnreg.inc.sync.aligned.u32 %0;" ::"n"(REG_CONV));
      conv_role(c);
    } else {
      asm volatile("setmaxnreg.dec.sync.aligned.u32 24;");
      if (wid == 15) TC(scr, 0);
      if (wid == 12) {
#pragma unroll 1
        for (int h = E0 - 4; h < 0; h++) raw_refill(c, h);
        asm volatile("barrier.cluster.wait.aligned;" ::: "memory");
        prod_rows(c);
      } else if (wid == 14) {
#pragma unroll 1
        for (int n = 0; n < (1 << 20); n++) {
          unsigned v;
          __nanosleep(n ? PSL : PS0);
          asm volatile("ld.acquire.gpu.global.u32 %0, [%1];" : "=r"(v) : "l"(&scr->done) : "memory");
          if (__shfl_sync(0xffffffffu, v, 0) >= 48) break;
        }
        TP(scr, 90);
        asm volatile("barrier.cluster.wait.aligned;" ::: "memory");
        asm volatile("fence.proxy.async.global;" ::: "memory");
        if (elect_one()) {
          mbar_expect(sb + BAR_W, 36864 + 768);
          mbar_expect(sb + BAR_W + 8, 110592);
          bulk_load(sb + OFF_NRM, scr->nrm, 768, sb + BAR_W);
          if (atomicAdd(&scr->seen, 1u) == gridDim.x - 1) { scr->done = 0; scr->seen = 0; }
        }
        __syncwarp();
#pragma unroll 1
        for (int i = 0; i < 8; i++) {
          if (elect_one()) bulk_load(sb + i * 18432, reinterpret_cast<const uint8_t*>(scr->w) + i * 18432, 18432, sb + BAR_W + (i < 2 ? 0 : 8));
          __nanosleep(PACE);
        }
      } else if (wid == 13) {
        prod_tiles(c);
        __syncwarp();
        if (elect_one()) asm volatile("mbarrier.arrive.shared::cta.b64 _, [%0];" ::"r"(sb + BAR_W + 16) : "memory");
      }
    }
  }
}

typedef CUresult (*EncodeFn)(CUtensorMap*, CUtensorMapDataType, cuuint32_t, void*, const cuuint64_t*, const cuuint64_t*,
                             const cuuint32_t*, const cuuint32_t*, CUtensorMapInterleave, CUtensorMapSwizzle,
                             CUtensorMapL2promotion, CUtensorMapFloatOOBfill);

}

extern "C" void kernel_launch(void* const* d_in, const int* in_sizes, int n_in, void* d_out, int out_size) {
  const __nv_bfloat16* x = (const __nv_bfloat16*)d_in[0];
  const __nv_bfloat16* dw = (const __nv_bfloat16*)d_in[1];
  const __nv_bfloat16* w1 = (const __nv_bfloat16*)d_in[2];
  const __nv_bfloat16* w2 = (const __nv_bfloat16*)d_in[3];
  __nv_bfloat16* out = (__nv_bfloat16*)d_out;

  static EncodeFn encode = nullptr;
  static Scratch* scr = nullptr;
  if (!encode) {
    cudaDriverEntryPointQueryResult st;
    void* fn = nullptr;
    cudaGetDriverEntryPoint("cuTensorMapEncodeTiled", &fn, cudaEnableDefault, &st);
    encode = (EncodeFn)fn;
    cudaGetSymbolAddress((void**)&scr, g_scratch);
    cudaFuncSetAttribute(convnext_kernel, cudaFuncAttributeMaxDynamicSharedMemorySize, SMEM_BYTES);
  }
  TMaps tm;
  cuuint64_t dims[4] = {CH, IMG / 2, IMG, 2};
  cuuint64_t strides[3] = {CH * 4, (cuuint64_t)IMG * CH * 2, CH * 2};
  cuuint32_t es[4] = {1, 1, 1, 1};
  for (int i = 0; i < 2; i++) {
    cuuint32_t box[4] = {i ? 16u : 32u, 19, 2, 1};
    encode(&tm.m[i], CU_TENSOR_MAP_DATA_TYPE_BFLOAT16, 4, (void*)x, dims, strides, box, es, CU_TENSOR_MAP_INTERLEAVE_NONE,
           i ? CU_TENSOR_MAP_SWIZZLE_NONE : CU_TENSOR_MAP_SWIZZLE_64B, PROMO, CU_TENSOR_MAP_FLOAT_OOB_FILL_NONE);
  }
  convnext_kernel<<<128, 512, SMEM_BYTES>>>(tm, x, dw, w1, w2, out, scr, 0);
}
```

```cpp
#include <cuda_runtime.h>
#include <cuda_bf16.h>
#include <cuda.h>
#include <stdint.h>

#define PROMO CU_TENSOR_MAP_L2_PROMOTION_L2_128B
#define CTX 6144
#define CCNT 5
#define PSL 100
#define PS0 1000
#define E0 1
#define PACE 100
#define PFIRST 1
namespace {

constexpr int IMG = 512, CH = 96;
constexpr int NSTEP = 67;
constexpr int SIGMA = 8;
constexpr int NROUND = 68;

constexpr uint32_t OFF_W1 = 0;
constexpr uint32_t OFF_W2 = 73728;
constexpr uint32_t OFF_RAW = 147456;
constexpr uint32_t RAW_PA = 2560, RAW_PB = 1280;
constexpr uint32_t RAW_BYTES = 2 * RAW_PA + 2 * RAW_PB;
constexpr uint32_t RAW_TX = 2 * 38 * 96;
constexpr uint32_t OFF_XRES = OFF_RAW + 4 * RAW_BYTES;
constexpr uint32_t OFF_C = OFF_XRES + 2 * 12288;
constexpr uint32_t C_BYTES = 12288;
constexpr uint32_t OFF_BAR = OFF_C + 2 * C_BYTES;
constexpr uint32_t BAR_RAW = OFF_BAR;
constexpr uint32_t BAR_CFULL = OFF_BAR + 32;
constexpr uint32_t BAR_CEMPTY = OFF_BAR + 48;
constexpr uint32_t BAR_XFULL = OFF_BAR + 80;
constexpr uint32_t BAR_W = OFF_BAR + 96;
constexpr uint32_t OFF_NRM = OFF_XRES + 9472;
constexpr uint32_t SMEM_BYTES = OFF_BAR + 160;

struct Scratch {
  uint4 w[2 * 73728 / 16];
  uint4 nrm[48];
  unsigned done, seen;
};
__device__ Scratch g_scratch;

constexpr float GELU_A = 0.32918364f;
constexpr uint32_t GELU_K2 = 0x40d940d9u;

constexpr int NB_CLOSE = 1, NB_SEC = 6  , NB_OPEN = 3, NB_PROD = 2, NB_PLAN = 4, NB_PREP = 5, NB_WG = 8  ;
#define REG_MLP 144
constexpr int REG_CONV = 488 - 2 * REG_MLP;

#define WG_FENCE() asm volatile("wgmma.fence.sync.aligned;" ::: "memory")
#define WG_COMMIT() asm volatile("wgmma.commit_group.sync.aligned;" ::: "memory")
#define WG_WAIT0() asm volatile("wgmma.wait_group.sync.aligned 0;" ::: "memory")
#define WG_WAIT1() asm volatile("wgmma.wait_group.sync.aligned 1;" ::: "memory")
#define PIN() asm volatile("pmevent 0;" ::: "memory")
#define NB_SYNC(id, n) asm volatile("bar.sync %0, %1;" ::"n"(id), "n"(n) : "memory")
#define NB_ARRIVE(id, n) asm volatile("bar.arrive %0, %1;" ::"n"(id), "n"(n) : "memory")

#define TC(scr, k)
#define TP(scr, k)

#define R24(c, d)                                                                                        \
  c(d[0]), c(d[1]), c(d[2]), c(d[3]), c(d[4]), c(d[5]), c(d[6]), c(d[7]), c(d[8]), c(d[9]), c(d[10]),    \
      c(d[11]), c(d[12]), c(d[13]), c(d[14]), c(d[15]), c(d[16]), c(d[17]), c(d[18]), c(d[19]), c(d[20]), \
      c(d[21]), c(d[22]), c(d[23])
#define WG_TXT(sd)                                                                             \
  "wgmma.mma_async.sync.aligned.m64n96k16.f16.f16.f16 "                                        \
  "{%0,%1,%2,%3,%4,%5,%6,%7,%8,%9,%10,%11,%12,%13,%14,%15,%16,%17,%18,%19,%20,%21,%22,%23}, " \
  "{%24,%25,%26,%27}, %28, " sd ", 1, 1, 1;\n"

__device__ __forceinline__ void wg_acc(uint32_t (&d)[24], const uint32_t* a, uint64_t db) {
  asm volatile(WG_TXT("1") : R24("+r", d) : "r"(a[0]), "r"(a[1]), "r"(a[2]), "r"(a[3]), "l"(db));
}
__device__ __forceinline__ void wg_init(uint32_t (&d)[24], const uint32_t* a, uint64_t db) {
  asm volatile(WG_TXT("0") : R24("=r", d) : "r"(a[0]), "r"(a[1]), "r"(a[2]), "r"(a[3]), "l"(db));
}
template <int N>
__device__ __forceinline__ void rfence(uint32_t (&d)[N]) {
#pragma unroll
  for (int i = 0; i < N; i++) asm volatile("" : "+r"(d[i])::"memory");
}
template <bool INIT, int KSTRIDE>
__device__ __forceinline__ void gemm6(uint32_t (&d)[24], const uint32_t (&a)[24], uint64_t db) {
#pragma unroll
  for (int k = 0; k < 6; k++) {
    if (INIT && k == 0) wg_init(d, &a[0], db);
    else wg_acc(d, &a[4 * k], db + k * KSTRIDE);
  }
  WG_COMMIT();
}

__device__ __forceinline__ void mbar_init(uint32_t bar, uint32_t cnt) {
  asm volatile("mbarrier.init.shared::cta.b64 [%0], %1;" ::"r"(bar), "r"(cnt) : "memory");
}
__device__ __forceinline__ void mbar_expect(uint32_t bar, uint32_t bytes) {
  asm volatile("mbarrier.arrive.expect_tx.shared::cta.b64 _, [%0], %1;" ::"r"(bar), "r"(bytes) : "memory");
}
__device__ __forceinline__ void mbar_arrive_cluster(uint32_t bar) {
  asm volatile("mbarrier.arrive.shared::cluster.b64 _, [%0];" ::"r"(bar) : "memory");
}
__device__ __forceinline__ bool mbar_try(uint32_t bar, uint32_t parity) {
  uint32_t ok;
  asm volatile(
      "{\n.reg .pred p;\nmbarrier.try_wait.parity.shared::cta.b64 p, [%1], %2;\nselp.u32 %0, 1, 0, p;\n}\n"
      : "=r"(ok)
      : "r"(bar), "r"(parity)
      : "memory");
  return ok;
}
__device__ __forceinline__ bool mbar_test(uint32_t bar, uint32_t parity) {
  uint32_t ok;
  asm volatile(
      "{\n.reg .pred p;\nmbarrier.test_wait.parity.shared::cta.b64 p, [%1], %2;\nselp.u32 %0, 1, 0, p;\n}\n"
      : "=r"(ok)
      : "r"(bar), "r"(parity)
      : "memory");
  return ok;
}
__device__ __forceinline__ void mbar_wait(uint32_t bar, uint32_t parity) {
  if (__builtin_expect(mbar_try(bar, parity), 1)) return;
#pragma unroll 1
  for (uint32_t n = 0; n < (1u << 16) && !mbar_try(bar, parity); n++) {}
}
__device__ __forceinline__ uint32_t mapa(uint32_t addr, uint32_t rank) {
  uint32_t r;
  asm("mapa.shared::cluster.u32 %0, %1, %2;" : "=r"(r) : "r"(addr), "r"(rank));
  return r;
}
__device__ __forceinline__ void tma_raw(uint32_t dst, const CUtensorMap* tm, int rank, int w2, int h, uint32_t bar) {
  mbar_expect(bar, RAW_TX);
#pragma unroll
  for (int k = 0; k < 4; k++) {
    const int e = k & 1;
    asm volatile(
        "cp.async.bulk.tensor.4d.shared::cluster.global.mbarrier::complete_tx::bytes [%0], [%1, {%2, %3, %4, %5}], [%6];"
        ::"r"(dst + (k < 2 ? e * RAW_PA : 2 * RAW_PA + e * RAW_PB)), "l"(tm + (k >> 1)), "r"(k < 2 ? 64 * rank : 32 + 16 * rank), "r"(w2 + e),
        "r"(h), "r"(1 - e), "r"(bar)
        : "memory");
  }
}
__device__ __forceinline__ void bulk_load(uint32_t dst, const void* src, uint32_t bytes, uint32_t bar) {
  asm volatile("cp.async.bulk.shared::cluster.global.mbarrier::complete_tx::bytes [%0], [%1], %2, [%3];" ::"r"(dst),
               "l"(src), "r"(bytes), "r"(bar)
               : "memory");
}
__device__ __forceinline__ void bulk_load_last(uint32_t dst, const void* src, uint32_t bytes, uint32_t bar) {
  asm volatile(
      "{\n.reg .b64 pol;\ncreatepolicy.fractional.L2::evict_first.b64 pol, 1.0;\n"
      "cp.async.bulk.shared::cluster.global.mbarrier::complete_tx::bytes.L2::cache_hint [%0], [%1], %2, [%3], pol;\n}\n" ::"r"(dst),
      "l"(src), "r"(bytes), "r"(bar)
      : "memory");
}
__device__ __forceinline__ uint32_t pack_bf16(float lo, float hi) {
  uint32_t r;
  asm("cvt.rn.bf16x2.f32 %0, %1, %2;" : "=r"(r) : "f"(hi), "f"(lo));
  return r;
}
__device__ __forceinline__ uint32_t pack_f16(float lo, float hi) {
  uint32_t r;
  asm("cvt.rn.f16x2.f32 %0, %1, %2;" : "=r"(r) : "f"(hi), "f"(lo));
  return r;
}
__device__ __forceinline__ float bf_lo(uint32_t v) { return __uint_as_float(v << 16); }
__device__ __forceinline__ float bf_hi(uint32_t v) { return __uint_as_float(v & 0xffff0000u); }
__device__ __forceinline__ uint32_t bf_add(uint32_t a, uint32_t b) {
  uint32_t r;
  asm("add.rn.bf16x2 %0, %1, %2;" : "=r"(r) : "r"(a), "r"(b));
  return r;
}
__device__ __forceinline__ uint32_t bf_mul(uint32_t a, uint32_t b) {
  uint32_t r;
  asm("mul.rn.bf16x2 %0, %1, %2;" : "=r"(r) : "r"(a), "r"(b));
  return r;
}
__device__ __forceinline__ uint32_t bf_fma(uint32_t a, uint32_t b, uint32_t c) {
  uint32_t r;
  asm("fma.rn.bf16x2 %0, %1, %2, %3;" : "=r"(r) : "r"(a), "r"(b), "r"(c));
  return r;
}

__device__ __forceinline__ uint32_t h_add(uint32_t a, uint32_t b) {
  uint32_t r;
  asm("add.rn.f16x2 %0, %1, %2;" : "=r"(r) : "r"(a), "r"(b));
  return r;
}
__device__ __forceinline__ uint32_t h_mul(uint32_t a, uint32_t b) {
  uint32_t r;
  asm("mul.rn.f16x2 %0, %1, %2;" : "=r"(r) : "r"(a), "r"(b));
  return r;
}
__device__ __forceinline__ uint32_t h_fma(uint32_t a, uint32_t b, uint32_t c) {
  uint32_t r;
  asm("fma.rn.f16x2 %0, %1, %2, %3;" : "=r"(r) : "r"(a), "r"(b), "r"(c));
  return r;
}
__device__ __forceinline__ float h_sum(uint32_t v) {
  float lo, hi;
  asm("{\n.reg .b16 l, h;\nmov.b32 {l, h}, %2;\ncvt.f32.f16 %0, l;\ncvt.f32.f16 %1, h;\n}\n" : "=f"(lo), "=f"(hi) : "r"(v));
  return lo + hi;
}
__device__ __forceinline__ void lds128(uint32_t (&v)[4], uint32_t a) {
  asm volatile("ld.shared.v4.b32 {%0,%1,%2,%3}, [%4];" : "=r"(v[0]), "=r"(v[1]), "=r"(v[2]), "=r"(v[3]) : "r"(a) : "memory");
}

template <int LO, int HI>
__device__ __forceinline__ void gelu(uint32_t (&o)[24], const uint32_t (&d)[24]) {
#pragma unroll
  for (int qq = LO; qq < HI; qq++) {
    const int q = (qq + 4) % 24;
    uint32_t t, u;
    asm("fma.rn.f16x2 %0, %1, %1, %2;" : "=r"(t) : "r"(d[q]), "r"(GELU_K2));
    asm("mul.rn.f16x2 %0, %1, %2;" : "=r"(u) : "r"(d[q]), "r"(t));
    asm("tanh.approx.f16x2 %0, %1;" : "=r"(t) : "r"(u));
    asm("fma.rn.f16x2 %0, %1, %2, %1;" : "=r"(o[q]) : "r"(d[q]), "r"(t));
  }
}

__device__ __forceinline__ uint32_t laneid() {
  uint32_t l;
  asm volatile("mov.u32 %0, %%laneid;" : "=r"(l));
  return l;
}

__device__ __forceinline__ bool elect_one() {
  uint32_t p;
  asm volatile("{\n.reg .pred p;\nelect.sync _|p, 0xffffffff;\nselp.u32 %0, 1, 0, p;\n}\n" : "=r"(p));
  return p;
}

__device__ __forceinline__ uint32_t clock_pin() {
  uint32_t t;
  asm volatile("mov.u32 %0, %%clock;" : "=r"(t)::"memory");
  return t;
}

struct MlpCtx {
  uint32_t sb;
  uint32_t caddr;
  uint32_t xaddr;
  uint32_t unscale;
  uint32_t peer_off;
  int wg, warp, rank, zero;
  uint8_t* optr;
};

__device__ __forceinline__ void ln_wait(const MlpCtx& m, int i) { mbar_wait(m.sb + BAR_CFULL + 8 * m.wg, i & 1); }
__device__ __forceinline__ void ln_load(const MlpCtx& m, uint32_t (&c)[24]) {
#pragma unroll
  for (int p = 0; p < 6; p++)
    asm volatile("ld.shared.v4.b32 {%0,%1,%2,%3}, [%4];"
                 : "=r"(c[4 * p]), "=r"(c[4 * p + 1]), "=r"(c[4 * p + 2]), "=r"(c[4 * p + 3])
                 : "r"(m.caddr + p * 2048)
                 : "memory");
}
__device__ __forceinline__ void ln_shfl(float (&st)[8], int mask) {
#pragma unroll
  for (int k = 0; k < 4; k++) st[4 + k] = __shfl_xor_sync(0xffffffffu, st[k], mask);
}
__device__ __forceinline__ void ln_fold(float (&st)[8]) {
#pragma unroll
  for (int k = 0; k < 4; k++) st[k] += st[4 + k];
}
__device__ __forceinline__ void ln_sums(const uint32_t (&c)[24], float (&st)[8]) {
#pragma unroll
  for (int r = 0; r < 2; r++) {
    uint32_t s0 = h_add(c[r], c[r + 2]), s1 = h_add(c[r + 4], c[r + 6]), s2 = h_add(c[r + 8], c[r + 10]);
    uint32_t s3 = h_add(c[r + 12], c[r + 14]), s4 = h_add(c[r + 16], c[r + 18]), s5 = h_add(c[r + 20], c[r + 22]);
    s0 = h_add(s0, s1); s2 = h_add(s2, s3); s4 = h_add(s4, s5);
    st[r] = h_sum(h_add(h_add(s0, s2), s4));
    uint32_t q0 = h_mul(c[r], c[r]), q1 = h_mul(c[r + 2], c[r + 2]);
#pragma unroll
    for (int p = 2; p < 12; p += 2) {
      q0 = h_fma(c[2 * p + r], c[2 * p + r], q0);
      q1 = h_fma(c[2 * p + 2 + r], c[2 * p + 2 + r], q1);
    }
    st[2 + r] = h_sum(h_add(q0, q1));
  }
}
__device__ __forceinline__ void ln_release(const MlpCtx& m) {
  const uint32_t e = m.sb + BAR_CEMPTY + 8 * (2 * m.rank + m.wg);
  asm volatile(
      "{\n.reg .pred p, q;\nelect.sync _|p, 0xffffffff;\nsetp.eq.and.s32 q, %3, 0, p;\n"
      "@q mbarrier.arrive.expect_tx.shared::cta.b64 _, [%0], %4;\n"
      "@p mbarrier.arrive.shared::cluster.b64 _, [%1];\n"
      "@p mbarrier.arrive.shared::cluster.b64 _, [%2];\n}\n" ::"r"(m.sb + BAR_CFULL + 8 * m.wg),
      "r"(e), "r"(e + m.peer_off), "r"(m.warp), "n"(CTX)
      : "memory");
}
__device__ __forceinline__ bool ln_stats(float (&st)[8]) {
  bool ok = true;
#pragma unroll
  for (int r = 0; r < 2; r++) {
    const float nm = (st[r] + st[4 + r]) * (-1.0f / 96.0f);
    const float e2 = fmaf(st[2 + r] + st[6 + r], 1.0f / 96.0f, 1e-5f);
    float rs;
    asm("rsqrt.approx.ftz.f32 %0, %1;" : "=f"(rs) : "f"(fmaf(-nm, nm, e2)));
    ok = ok && (rs * rs * e2 <= 17.0f) && (e2 >= 1.001e-5f);
    const float rr = rs * GELU_A, dd = rr * nm;
    st[r] = __uint_as_float(pack_f16(rr, rr));
    st[2 + r] = __uint_as_float(pack_f16(dd, dd));
  }
  return ok;
}
__device__ __forceinline__ void ln_restat(bool ok, const uint32_t (&c)[24], float (&st)[8], uint32_t& bad, uint32_t bit,
                                          uint32_t zero) {
  if (__builtin_expect(__any_sync(0xffffffffu, !ok), 0)) {
#pragma unroll
    for (int r = 0; r < 2; r++) {
      float nm = 0.f, var = 0.f;
#pragma unroll
      for (int p = 0; p < 12; p++) {
        nm += h_sum(c[2 * p + r] ^ zero);
        if (p % 3 == 2) { asm volatile("" : "+f"(nm)); PIN(); }
      }
      nm += __shfl_xor_sync(0xffffffffu, nm, 1);
      nm += __shfl_xor_sync(0xffffffffu, nm, 2);
      nm *= -1.0f / 96.0f;
#pragma unroll
      for (int p = 0; p < 12; p++) {
        float lo, hi;
        asm volatile("{\n.reg .b16 l, h;\nmov.b32 {l, h}, %2;\ncvt.f32.f16 %0, l;\ncvt.f32.f16 %1, h;\n}\n" : "=f"(lo), "=f"(hi) : "r"(c[2 * p + r]));
        var = fmaf(lo + nm, lo + nm, fmaf(hi + nm, hi + nm, var));
        if (p % 3 == 2) { asm volatile("" : "+f"(var)); PIN(); }
      }
      var += __shfl_xor_sync(0xffffffffu, var, 1);
      var += __shfl_xor_sync(0xffffffffu, var, 2);
      const float rr = rsqrtf(fmaf(var, 1.0f / 96.0f, 1e-5f)) * GELU_A;
      st[r] = __uint_as_float(pack_f16(rr, rr));
      const float dd = 0.5f * h_sum(__float_as_uint(st[r])) * nm;
      st[2 + r] = __uint_as_float(pack_f16(dd, dd));
      if (!(rr >= 0x1p-14f && fabsf(dd) <= 16.0f && var >= 1e-8f)) bad |= bit;
    }
  }
}
__device__ __forceinline__ void ln_apply(uint32_t (&a)[24], const uint32_t (&c)[24], const float (&st)[8]) {
#pragma unroll
  for (int p = 0; p < 24; p++) {
    a[p] = h_fma(c[p], __float_as_uint(st[p & 1]), __float_as_uint(st[2 + (p & 1)]));
  }
}

__device__ __noinline__ void slow_tile(const __nv_bfloat16* x, const __nv_bfloat16* dw, const __nv_bfloat16* w1,
                                       const __nv_bfloat16* w2, __nv_bfloat16* out, int row0, int col0, float* buf) {
  const int lane = threadIdx.x & 31;
  for (int px = 0; px < 16; px++) {
    const int row = row0 + (px >> 3), col = col0 + (px & 7);
    float c[3] = {0.f, 0.f, 0.f};
    for (int i = 0; i < 7; i++)
      for (int j = 0; j < 7; j++) {
        const int rr = row + i - 3, cc = col + j - 3;
        if (rr < 0 || rr >= IMG || cc < 0 || cc >= IMG) continue;
        for (int k = 0; k < 3; k++)
          c[k] = fmaf(__bfloat162float(x[((size_t)rr * IMG + cc) * CH + lane + 32 * k]), __bfloat162float(dw[(i * 7 + j) * CH + lane + 32 * k]), c[k]);
      }
    float mean = (c[0] + c[1] + c[2]) * (1.0f / 96.0f);
    for (int o = 16; o; o >>= 1) mean += __shfl_xor_sync(0xffffffffu, mean, o);
    float var = 0.f;
    for (int k = 0; k < 3; k++) { c[k] -= mean; var = fmaf(c[k] * (1.0f / 96.0f), c[k], var); }
    for (int o = 16; o; o >>= 1) var += __shfl_xor_sync(0xffffffffu, var, o);
    const float rs = 1.0f / sqrtf(var + 1e-5f);
    __syncwarp();
    for (int k = 0; k < 3; k++) buf[lane + 32 * k] = c[k] * rs;
    __syncwarp();
    for (int n = lane; n < 4 * CH; n += 32) {
      float y = 0.f;
      for (int k = 0; k < CH; k++) y = fmaf(buf[k], __bfloat162float(w1[k * 4 * CH + n]), y);
      buf[CH + n] = 0.5f * y * (1.0f + tanhf(0.7978845608f * (y + 0.044715f * y * y * y)));
    }
    __syncwarp();
    for (int n = lane; n < CH; n += 32) {
      float o = 0.f;
      for (int k = 0; k < 4 * CH; k++) o = fmaf(buf[CH + k], __bfloat162float(w2[k * CH + n]), o);
      const size_t idx = ((size_t)row * IMG + col) * CH + n;
      out[idx] = __float2bfloat16(__bfloat162float(x[idx]) + o);
    }
  }
}

__device__ __forceinline__ void x_load(const MlpCtx& m, uint32_t (&x)[24]) {
#pragma unroll
  for (int k = 0; k < 6; k++)
    asm volatile("ld.shared.v4.b32 {%0,%1,%2,%3}, [%4];"
                 : "=r"(x[4 * k]), "=r"(x[4 * k + 1]), "=r"(x[4 * k + 2]), "=r"(x[4 * k + 3])
                 : "r"(m.xaddr + (k / 3) * 384 + (k % 3) * 64)
                 : "memory");
}
template <int LO, int HI>
__device__ __forceinline__ void epilogue(const MlpCtx& m, const uint32_t (&d)[24], uint32_t (&x)[24]) {
#pragma unroll
  for (int k = LO; k < HI; k++) {
    const int r = k / 3, q = k % 3;
    uint32_t* y = &x[4 * k];
#pragma unroll
    for (int j = 0; j < 4; j++) {
      uint32_t v = d[2 * (4 * q + j) + r];
      float lo, hi;
      asm("{\n.reg .b16 l, h;\nmov.b32 {l, h}, %2;\ncvt.f32.f16 %0, l;\ncvt.f32.f16 %1, h;\n}\n" : "=f"(lo), "=f"(hi) : "r"(v));
      asm("fma.rn.bf16x2 %0, %1, %2, %0;" : "+r"(y[j]) : "r"(pack_bf16(lo, hi)), "r"(m.unscale));
    }
    asm volatile("st.shared.v4.b32 [%0], {%1,%2,%3,%4};" ::"r"(m.xaddr + r * 384 + q * 64), "r"(y[0]), "r"(y[1]), "r"(y[2]), "r"(y[3])
                 : "memory");
  }
}
__device__ __forceinline__ void out_store(const MlpCtx& m, int i) {
  asm volatile("fence.proxy.async.shared::cta;" ::: "memory");
  __syncwarp();
  if (elect_one()) {
    const uint32_t src = m.sb + OFF_XRES + m.wg * 12288 + m.warp * 1536;
    uint8_t* dst = m.optr + (size_t)i * (8 * IMG * CH * 2);
    asm volatile("cp.async.bulk.global.shared::cta.bulk_group [%0], [%1], 1536;" ::"l"(dst), "r"(src) : "memory");
    asm volatile("cp.async.bulk.global.shared::cta.bulk_group [%0], [%1], 1536;" ::"l"(dst + IMG * CH * 2), "r"(src + 6144) : "memory");
    asm volatile("cp.async.bulk.commit_group;" ::: "memory");
  }
}

#define FSET 3
template <int J> constexpr bool goes_first = J == FSET || J == ((FSET + 1) & 3);
template <int J> __device__ __forceinline__ void tok_wait() {
  if (goes_first<J>) NB_SYNC(NB_CLOSE, 256);
  else NB_SYNC(NB_SEC + (J & 1), 256);
}
template <int J, bool PROD = true> __device__ __forceinline__ void tok_next() {
  if (goes_first<J>) NB_ARRIVE(NB_SEC + (J & 1), 256);
  if (J == 0 && PROD) NB_ARRIVE(NB_PROD, 160);
}
__device__ __forceinline__ void tok_pass() { NB_ARRIVE(NB_OPEN, 448); }
template <int J> __device__ __forceinline__ void tok_idle() { tok_wait<J>(); tok_next<J, false>(); tok_pass(); }

constexpr uint64_t CHK = 1152;

__device__ __forceinline__ float warp_sumsq(const uint32_t (&q)[4]) {
  const uint32_t t = bf_add(bf_add(q[0], q[1]), bf_add(q[2], q[3]));
  float f = bf_lo(t) + bf_hi(t);
#pragma unroll
  for (int o = 16; o; o >>= 1) f += __shfl_xor_sync(0xffffffffu, f, o);
  return f;
}
__device__ __forceinline__ int norm_exp(float f) { return (((int)(__float_as_uint(f * 1.5f) >> 23) - 127) >> 1) + 1; }
__device__ __forceinline__ int scale_exp(int e1, int e2) { return min(11 - e1 - e2, 14 - e2); }

__device__ __forceinline__ void convert_tile(int t, int k, const uint4* w1, const uint4* w2, uint32_t st, Scratch* scr) {
  const int lane = threadIdx.x & 31, k7 = lane & 7;
  const int j = t / 6, ks = t % 6, e = ks % 3, t4 = k7 >> 1;
  const uint4* src = t < 24 ? w1 + ((e < 2 ? 64 * (ks / 3) + 8 * t4 + 4 * e : 32 + 16 * (ks / 3) + 4 * t4) + (k7 & 1)) * 48 + j * 12 + (lane >> 3)
                            : w2 + (t - 24) * 192 + (lane >> 2) * 12 + (lane & 3);
  src += (k / 3) * 96 + (k % 3) * 4;
  if (k >= 6) src = (k == 6 ? w1 : w2) + lane * 145;
  const uint4 v = __ldg(src);
  const uint32_t w[4] = {v.x, v.y, v.z, v.w};
  const uint32_t q[4] = {bf_mul(v.x, v.x), bf_mul(v.y, v.y), bf_mul(v.z, v.z), bf_mul(v.w, v.w)};
  asm volatile("st.shared.f32 [%0], %1;" ::"r"(st + 3088 + 4 * k), "f"(warp_sumsq(q)) : "memory");
  NB_SYNC(NB_PREP, 256);
  uint32_t a[4], b[4], o[4];
  lds128(a, st + 3088);
  lds128(b, st + 3104);
  const int s = max(-64, min(64, scale_exp(norm_exp(144.f * __uint_as_float(b[2])), norm_exp(144.f * __uint_as_float(b[3]))) - 3));
  const uint32_t dst = st + k7 * 16 + (lane >> 3) * 256 + (k / 3) * 128 + (k % 3) * 1024;
  if (k >= 6) {
    const float f = ((__uint_as_float(a[0]) + __uint_as_float(a[1])) + (__uint_as_float(a[2]) + __uint_as_float(a[3]))) +
                    (__uint_as_float(b[0]) + __uint_as_float(b[1]));
    asm volatile("st.shared.v2.b32 [%0], {%1,%2};" ::"r"(st + 3072), "r"(__float_as_uint(f)), "r"(s) : "memory");
  } else if (t < 24) {
#pragma unroll
    for (int i = 0; i < 4; i++) o[i] = pack_f16(bf_lo(w[i]), bf_hi(w[i]));
    asm volatile("st.shared.v4.b32 [%0], {%1,%2,%3,%4};" ::"r"(dst), "r"(o[0]), "r"(o[1]), "r"(o[2]), "r"(o[3]) : "memory");
  } else {
    constexpr float F = 0.5f / GELU_A, FHI = 1.515625f;
    const float p2 = __uint_as_float((uint32_t)(127 + s - 56) << 23);
    const uint32_t hi = pack_bf16(FHI * 0x1p-56f, FHI * 0x1p-56f), lo = pack_bf16((F - FHI) * 0x1p-56f, (F - FHI) * 0x1p-56f);
    const uint32_t pw = pack_bf16(p2, p2);
#pragma unroll
    for (int i = 0; i < 4; i++) {
      const uint32_t ws = bf_mul(w[i], pw), u = bf_fma(ws, hi, bf_mul(ws, lo));
      o[i] = (u & 0x7fff7fffu) * 7u + u;
    }
    asm volatile("stmatrix.sync.aligned.m8n8.x4.shared.b16 [%0], {%1,%2,%3,%4};" ::"r"(dst), "r"(o[0]), "r"(o[1]), "r"(o[2]), "r"(o[3])
                 : "memory");
  }
  asm volatile("fence.proxy.async.shared::cta;" ::: "memory");
  NB_SYNC(NB_PREP, 256);
  if (k == 0 && elect_one()) {
    asm volatile("cp.async.bulk.global.shared::cta.bulk_group [%0], [%1], 3072;" ::"l"(scr->w + t * 192), "r"(st) : "memory");
    asm volatile("cp.async.bulk.global.shared::cta.bulk_group [%0], [%1], 16;" ::"l"(scr->nrm + t), "r"(st + 3072) : "memory");
    asm volatile("cp.async.bulk.commit_group;" ::: "memory");
    asm volatile("cp.async.bulk.wait_group 0;" ::: "memory");
    asm volatile("red.relaxed.gpu.global.add.u32 [%0], 1;" ::"l"(&scr->done) : "memory");
  }
}

__device__ __forceinline__ uint32_t mlp_role(const MlpCtx& m0) {
  MlpCtx m = m0;
  uint32_t bad = 0;
  asm volatile("barrier.cluster.wait.aligned;" ::: "memory");
  if ((m.sb & 0x3FFFF) != 1024) bad = 0xffffu;
  constexpr uint64_t dW1 = (uint64_t)((1024 + OFF_W1) >> 4) | ((uint64_t)8 << 16) | ((uint64_t)16 << 32);
  constexpr uint64_t dW2 = dW1 + (OFF_W2 >> 4);
  uint32_t A1[24], g[24], d[24], cn[24], D2[24];
  float st[8];
  if (m.wg & m.rank) tok_idle<3>();
  else if (m.wg) tok_idle<0>();
  else if (m.rank) tok_idle<1>();
  ln_wait(m, 0);
  ln_load(m, cn);
  ln_sums(cn, st);
  ln_shfl(st, 1);
  ln_release(m);
  ln_fold(st);
  ln_shfl(st, 2);
  ln_restat(ln_stats(st), cn, st, bad, 1, m.zero);
  ln_apply(A1, cn, st);
  {
    const int lane = threadIdx.x & 31;
    mbar_wait(m.sb + BAR_W, 0);
    float n1, n2;
    int s;
    asm volatile("ld.shared.b32 %0, [%1];" : "=r"(s) : "r"(m.sb + OFF_NRM + 4) : "memory");
    asm volatile("ld.shared.f32 %0, [%1];" : "=f"(n1) : "r"(m.sb + OFF_NRM + 16 * min(lane, 23)) : "memory");
    asm volatile("ld.shared.f32 %0, [%1];" : "=f"(n2) : "r"(m.sb + OFF_NRM + 384 + 16 * min(lane, 23)) : "memory");
    if (lane >= 24) n1 = n2 = 0.f;
#pragma unroll
    for (int o = 16; o; o >>= 1) {
      n1 += __shfl_xor_sync(0xffffffffu, n1, o);
      n2 += __shfl_xor_sync(0xffffffffu, n2, o);
    }
    const int e1 = norm_exp(n1), e2 = norm_exp(n2), smax = scale_exp(e1, e2);
    if (e1 > 12 || e1 < -5 || e2 > 50 || e2 < -50 || s > smax || s < smax - 7) bad = 0xffffu;
    m.unscale = __shfl_sync(0xffffffffu, ((uint32_t)(127 - s) << 7) * 0x10001u, 0);
  }
  if (m.wg & m.rank) tok_idle<0>();
  if (m.wg) tok_idle<1>();
  {
    uint32_t d0[24];
    WG_FENCE();
    tok_wait<2>();
    tok_next<2>();
    gemm6<true, 192>(d0, A1, dW1);
    tok_pass(); PIN();
    WG_WAIT0(); rfence(d0);
    WG_FENCE();
    tok_wait<3>();
    tok_next<3>();
    gemm6<true, 192>(d, A1, dW1 + CHK);
    tok_pass(); PIN();
    gelu<0, 24>(g, d0);
    PIN();
    mbar_wait(m.sb + BAR_W + 8, 0);
    ln_wait(m, 1);
    WG_WAIT0(); rfence(d);
  }
#define G2(INIT, a, j)                      \
  WG_FENCE();                               \
  tok_wait<j>();                            \
  gemm6<INIT, 192>(D2, a, dW2 + (j) * CHK); \
  tok_next<j>(); PIN();
#define G1(dst, j, P)                       \
  P(); WG_WAIT0(); rfence(D2);              \
  WG_FENCE();                               \
  gemm6<true, 192>(dst, A1, dW1 + (j) * CHK); \
  tok_pass(); P();
#define ROUND_END(dst, j)                   \
  PIN(); WG_WAIT0(); rfence(dst);
#define GA 9
#define GB 12
#define GC 13
#define GD 11
#pragma unroll 1
  for (int i = 0;; i++) {
    uint32_t g1[24], d2[24], g2[24], d3[24], g3[24], d0[24];
    ln_load(m, cn);
    PIN();
    G2(true, g, 0)
    gelu<0, GA>(g1, d);
    G1(d2, 2, PIN)
    ln_sums(cn, st);
    gelu<GA, 24>(g1, d);
    PIN();
    ln_shfl(st, 1);
    ROUND_END(d2, 0)

    G2(false, g1, 1)
    ln_fold(st);
    gelu<0, GB>(g2, d2);
    PIN();
    ln_shfl(st, 2);
    G1(d3, 3, PIN)
    const bool ok = ln_stats(st);
    gelu<GB, 24>(g2, d2);
    PIN();
    ln_restat(ok, cn, st, bad, 2u << i, m.zero);
    ROUND_END(d3, 1)

    if (i == 15) {
      G2(false, g2, 2)
      tok_pass();
      gelu<0, 24>(g3, d3);
      PIN();
      x_load(m, cn);
      ROUND_END(D2, 2)
      G2(false, g3, 3)
      tok_pass();
      WG_WAIT0(); rfence(D2);
      epilogue<0, 6>(m, D2, cn);
      break;
    }
    G2(false, g2, 2)
    ln_apply(A1, cn, st);
    PIN();
    gelu<0, GC>(g3, d3);
    G1(d0, 0, PIN)
    gelu<GC, 24>(g3, d3);
    PIN();
    x_load(m, cn);
    ROUND_END(d0, 2)

    G2(false, g3, 3)
    gelu<0, GD>(g, d0);
    G1(d, 1, PIN)
    epilogue<0, 6>(m, D2, cn);
    gelu<GD, 24>(g, d0);
    PIN();
    asm volatile("fence.proxy.async.shared::cta;" ::: "memory");
    ROUND_END(d, 3)
  }
  out_store(m, 15);
  if (m.wg == 0) { tok_idle<0>(); tok_idle<1>(); }
  asm volatile("cp.async.bulk.wait_group.read 0;" ::: "memory");
  return __reduce_or_sync(0xffffffffu, bad & 0xffffu);
}

struct ConvCtx {
  uint32_t sb;
  uint32_t a0, a_c;
  uint32_t peer_off;
  int rank, v, c0, r0, zero;
  const CUtensorMap* tm;
  Scratch* scr;
  const uint8_t* xsrc;
  uint8_t* optr;
};

__device__ __forceinline__ void raw_refill(const ConvCtx& c, int s) {
  if (s + 4 < NSTEP && elect_one())
    tma_raw(c.sb + OFF_RAW + (s & 3) * RAW_BYTES, c.tm, c.rank, c.c0 / 2 - 2, c.r0 - 3 + 2 * (s + 4), c.sb + BAR_RAW + 8 * (s & 3));
}
__device__ __forceinline__ void step_ready(const ConvCtx& c, int s) {
  const int nx = (s + 1) & 3, par = ((s + 1) >> 2) & 1;
  if (s + 1 < NSTEP) mbar_wait(c.sb + BAR_RAW + 8 * nx, par);
  if (s >= 7 && s < NSTEP) mbar_wait(c.sb + BAR_CEMPTY + 8 * (2 * (nx & 1) + (nx >> 1)), par);
}

__device__ __forceinline__ void c_release(const ConvCtx& c, uint32_t w) {
  const uint32_t e = c.sb + BAR_CEMPTY + 8 * (2 * c.rank + w);
  asm volatile(
      "{\n.reg .pred p;\nelect.sync _|p, 0xffffffff;\n"
      "@p mbarrier.arrive.expect_tx.shared::cta.b64 _, [%0], %3;\n"
      "@p mbarrier.arrive.shared::cluster.b64 _, [%1], 4;\n"
      "@p mbarrier.arrive.shared::cluster.b64 _, [%2], 4;\n}\n" ::"r"(c.sb + BAR_CFULL + 8 * w),
      "r"(e), "r"(e + c.peer_off), "n"(CTX)
      : "memory");
}

__device__ __forceinline__ void prod_rows(const ConvCtx& c) {
#pragma unroll 1
  for (int s = 0; s < NROUND + SIGMA + c.rank; s++) {
    if (s < SIGMA) NB_SYNC(NB_PLAN, 192);
    else NB_SYNC(NB_OPEN, 448);
    raw_refill(c, s);
  }
}
__device__ __forceinline__ void prod_checks(const ConvCtx& c) {
  asm volatile("barrier.cluster.wait.aligned;" ::: "memory");
#pragma unroll 1
  for (int s = 0; s < NROUND + SIGMA + c.rank; s++) {
    const int r = s - SIGMA - c.rank;
    const int u = (r & 1) ? (r >> 1) - 1 : (r >> 1) + 2;
    step_ready(c, s);
    if (s < 16) TP(c.scr, 100 + s);
    if (u >= ((r & 1) ? 0 : 4) && u < 32) mbar_wait(c.sb + ((r & 1) ? BAR_XFULL : BAR_CFULL) + 8 * (u & 1), (u >> 1) & 1);
    if (s < SIGMA) NB_SYNC(NB_PLAN, 192);
    else NB_SYNC(NB_OPEN, 448);
    TP(c.scr, s);
    if (r == 3) TC(c.scr, 1);
    if (r == 55) TC(c.scr, 2);
  }
}
__device__ __forceinline__ void prod_tiles(const ConvCtx& c) {
  asm volatile("barrier.cluster.wait.aligned;" ::: "memory");
#pragma unroll 1
  for (int n = 1; n < 33; n++) {
    const uint32_t w = (n + 1) & 1;
    const uint32_t buf = c.sb + OFF_XRES + w * 12288;
    NB_SYNC(NB_PROD, 160);
    if (n < 29) c_release(c, w);
    if (n >= 3) {
      uint8_t* dst = c.optr + (size_t)(n - 3) * (4 * IMG * CH * 2);
      if (elect_one()) {
        asm volatile("cp.async.bulk.global.shared::cta.bulk_group [%0], [%1], 6144;" ::"l"(dst), "r"(buf) : "memory");
        asm volatile("cp.async.bulk.global.shared::cta.bulk_group [%0], [%1], 6144;" ::"l"(dst + IMG * CH * 2), "r"(buf + 6144) : "memory");
        asm volatile("cp.async.bulk.commit_group;" ::: "memory");
        asm volatile("cp.async.bulk.wait_group.read 0;" ::: "memory");
      }
      __syncwarp();
    }
    {
      const uint8_t* src = c.xsrc + (size_t)(n - 1) * (4 * IMG * CH * 2);
      if (elect_one()) {
        mbar_expect(c.sb + BAR_XFULL + 8 * w, 12288);
        bulk_load_last(buf, src, 6144, c.sb + BAR_XFULL + 8 * w);
        bulk_load_last(buf + 6144, src + IMG * CH * 2, 6144, c.sb + BAR_XFULL + 8 * w);
      }
    }
  }
  asm volatile("cp.async.bulk.wait_group 0;" ::: "memory");
}

template <int LO, int HI>
__device__ __forceinline__ void conv_ld8(uint32_t a0, uint32_t (&r)[6][6]) {
  const uint32_t a2 = a0 ^ (16 | ((a0 >> 2) & 32));
  const uint32_t a[3] = {a0, (a0 & 64) ? a2 : a0, a2};
#pragma unroll
  for (int j = LO; j < HI; j++)
    asm volatile("ld.shared.v4.b32 {%0,%1,%2,%3}, [%4];"
                 : "=r"(r[j][0]), "=r"(r[j][1]), "=r"(r[j][2]), "=r"(r[j][3])
                 : "r"(a[j >> 1] + (j >> 1) * 64 + (j & 1) * RAW_PA)
                 : "memory");
}
__device__ __forceinline__ void conv_ld4(uint32_t a0, uint32_t stage, int v, uint32_t (&r)[6][6]) {
  const uint32_t ab = ((a0 >> 1) & ~31u) + (stage / 2 + 2 * RAW_PA + 8 * v);
#pragma unroll
  for (int j = 0; j < 6; j++) {
    uint32_t a = ab + (j >> 1) * 32;
    asm volatile("ld.shared.v2.b32 {%0,%1}, [%2];" : "=r"(r[j][4]), "=r"(r[j][5]) : "r"(a + (j & 1) * RAW_PB) : "memory");
  }
}
template <int LO, int HI>
__device__ __forceinline__ void conv_frags(uint32_t zero, const uint32_t (&r)[6][6], uint32_t (&A)[12][4]) {
#pragma unroll
  for (int ch = LO; ch < HI; ch++) {
    const uint32_t sel = (ch & 1) ? 0x7632 : 0x5410;
    A[ch][0] = __byte_perm(r[0][ch >> 1], r[1][ch >> 1], sel);
    A[ch][1] = __byte_perm(r[2][ch >> 1], r[3][ch >> 1], sel);
    A[ch][2] = A[ch][1] ^ zero;
    A[ch][3] = __byte_perm(r[4][ch >> 1], r[5][ch >> 1], sel);
    rfence(A[ch]);
  }
}
__device__ __forceinline__ void hmma_acc(uint32_t (&v)[4], const uint32_t (&a)[4], const uint32_t* b) {
  asm volatile("mma.sync.aligned.m16n8k16.row.col.f32.bf16.bf16.f32 {%0,%1,%2,%3}, {%4,%5,%6,%7}, {%8,%9}, {%0,%1,%2,%3};"
               : "+r"(v[0]), "+r"(v[1]), "+r"(v[2]), "+r"(v[3])
               : "r"(a[0]), "r"(a[1]), "r"(a[2]), "r"(a[3]), "r"(b[0]), "r"(b[1]));
}
__device__ __forceinline__ void hmma_new(uint32_t (&a)[4], const uint32_t* b) {
  asm volatile("mma.sync.aligned.m16n8k16.row.col.f32.bf16.bf16.f32 {%0,%1,%2,%3}, {%0,%1,%2,%3}, {%4,%5}, {%6,%6,%6,%6};"
               : "+r"(a[0]), "+r"(a[1]), "+r"(a[2]), "+r"(a[3])
               : "r"(b[0]), "r"(b[1]), "f"(0.f));
}

#define EARLY 5
__device__ __forceinline__ void conv_send(bool local, const uint32_t (&pk)[12], uint32_t dst, uint32_t bar) {
  if (local) {
#pragma unroll
    for (int q = 0; q < 3; q++)
      asm volatile("st.shared.v4.b32 [%0], {%1,%2,%3,%4};" ::"r"(dst + q * 2048), "r"(pk[4 * q]), "r"(pk[4 * q + 1]), "r"(pk[4 * q + 2]), "r"(pk[4 * q + 3])
                   : "memory");
    asm volatile("{\n.reg .pred p;\nelect.sync _|p, 0xffffffff;\n@p mbarrier.arrive.shared::cta.b64 _, [%0];\n}\n" ::"r"(bar) : "memory");
  } else {
#pragma unroll
    for (int q = 0; q < 3; q++)
      asm volatile("st.async.weak.shared::cluster.mbarrier::complete_tx::bytes.v4.b32 [%0], {%1,%2,%3,%4}, [%5];" ::"r"(dst + q * 2048),
                   "r"(pk[4 * q]), "r"(pk[4 * q + 1]), "r"(pk[4 * q + 2]), "r"(pk[4 * q + 3]), "r"(bar)
                   : "memory");
  }
}
template <int S2, bool GATED>
__device__ __forceinline__ void conv_step(const ConvCtx& c, int s, uint32_t (&K)[12], uint32_t (&V)[12][4], const uint32_t (&B)[12][4],
                                          uint32_t (&A)[12][4]) {
  const int nx = ((s + 1) & 2) | (S2 ^ 1);
  uint32_t r[6][6], pk[12];
  const uint32_t a0 = c.a0 + nx * RAW_BYTES;
  if (GATED) NB_SYNC(NB_OPEN, 448);
  else NB_SYNC(NB_PLAN, 192);
  conv_ld4(a0, c.sb + OFF_RAW + nx * RAW_BYTES, c.v, r);
  if (GATED) PIN();
#pragma unroll
  for (int ch = 0; ch < 12; ch++) hmma_acc(V[11 - ch], A[11 - ch], &B[11 - ch][2]);
#pragma unroll
  for (int ch = 0; ch < 12 - EARLY; ch++) hmma_new(A[ch], &B[ch][0]);
  const uint32_t zero = GATED ? c.zero & clock_pin() : c.zero;
  if (GATED) NB_ARRIVE(NB_CLOSE, 256);
#pragma unroll
  for (int ch = 12 - EARLY; ch < 12; ch++) hmma_new(A[ch], &B[ch][0]);
  if (GATED) PIN();
  const bool local = (S2 ^ 1) == c.rank;
  const uint32_t off = local ? 0u : c.peer_off;
  const uint32_t dst = c.a_c + off + (nx >> 1) * C_BYTES;
  const uint32_t bar = c.sb + off + BAR_CFULL + 8 * (nx >> 1);
#pragma unroll
  for (int q = 0; q < 12; q++) {
    const int ch = q & ~1, h = 2 * (q & 1);
    pk[q] = h_add(K[q], pack_f16(__uint_as_float(V[ch][h + 1]), __uint_as_float(V[ch + 1][h])));
  }
#pragma unroll
  for (int q = 0; q < 12; q++) {
    const int ch = q & ~1, h = 2 * (q & 1);
    K[q] = pack_f16(__uint_as_float(V[ch][h]), __uint_as_float(V[ch + 1][h + 1]));
  }
  rfence(K);
  rfence(pk);
  PIN();
  conv_ld8<0, 4>(a0, r);
  if (GATED || s >= 3) conv_send(local, pk, dst, bar);
  conv_frags<8, 12>(zero, r, V);
  PIN();
  conv_ld8<4, 6>(a0, r);
  conv_frags<0, 8>(zero, r, V);
  PIN();
}

__device__ __forceinline__ void conv_role(ConvCtx c) {
  const int lane = laneid(), g = lane >> 2, t = lane & 3;
  const int u = (t >> 1) * 19 + 2 * (g + (t & 1));
  c.a0 = c.sb + OFF_RAW + u * 64 + ((c.v ^ (u >> 1)) & 3) * 16;
  c.a_c = c.sb + OFF_C + 6144 * c.rank + 512 * c.v + ((lane + 2 * c.v) & 31) * 16;
  uint32_t B[12][4];
  {
    const int dc = (g >> 1) & 1, ro = g >> 2, rk = t >> 1;
    const int i0 = 4 * (g & 1) + rk - ro, j0 = 4 * (t & 1) - dc;
    const uint32_t base = c.sb + OFF_XRES + (i0 * 7 + j0) * 192;
    asm volatile("barrier.cluster.wait.aligned;" ::: "memory");
    mbar_wait(c.sb + BAR_W + 48, 0);
#pragma unroll
    for (int b = 0; b < 2; b++) {
      uint32_t w[4][6];
#pragma unroll
      for (int k = 0; k < 4; k++) {
        const int ok = (unsigned)(i0 + 2 * b) < 7u && (unsigned)(j0 + k) < 7u;
#pragma unroll
        for (int q = 0; q < 6; q++) w[k][q] = 0;
        asm volatile(
            "{\n.reg .pred p;\nsetp.ne.s32 p, %8, 0;\n@p ld.shared.v4.b32 {%0,%1,%2,%3}, [%6];\n@p ld.shared.v2.b32 {%4,%5}, [%7];\n}\n"
            : "+r"(w[k][0]), "+r"(w[k][1]), "+r"(w[k][2]), "+r"(w[k][3]), "+r"(w[k][4]), "+r"(w[k][5])
            : "r"(base + (b * 14 + k) * 192 + 128 * c.rank + 16 * c.v), "r"(base + (b * 14 + k) * 192 + 64 + 32 * c.rank + 8 * c.v), "r"(ok)
            : "memory");
      }
#pragma unroll
      for (int q = 0; q < 6; q++) {
        B[2 * q][2 * b] = __byte_perm(w[0][q], w[1][q], 0x5410);
        B[2 * q][2 * b + 1] = __byte_perm(w[2][q], w[3][q], 0x5410);
        B[2 * q + 1][2 * b] = __shfl_xor_sync(0xffffffffu, __byte_perm(w[0][q], w[1][q], 0x7632), 4);
        B[2 * q + 1][2 * b + 1] = __shfl_xor_sync(0xffffffffu, __byte_perm(w[2][q], w[3][q], 0x7632), 4);
      }
    }
  }
  uint32_t K1[12], K2[12], V[12][4];
#pragma unroll
  for (int ch = 0; ch < 12; ch++)
    asm volatile("" : "=r"(K1[ch]), "=r"(K2[ch]), "=r"(V[ch][0]), "=r"(V[ch][1]), "=r"(V[ch][2]), "=r"(V[ch][3]));
  uint32_t A[12][4], r[6][6];
  mbar_wait(c.sb + BAR_RAW, 0);
  conv_ld8<0, 6>(c.a0, r);
  conv_ld4(c.a0, c.sb + OFF_RAW, c.v, r);
  conv_frags<0, 12>(c.zero, r, A);
  PIN();
  NB_ARRIVE(NB_CLOSE, 256);
#pragma unroll 1
  for (int s = 0; s < SIGMA; s += 2) {
    conv_step<0, false>(c, s, K1, V, B, A);
    conv_step<1, false>(c, s + 1, K2, A, B, V);
  }
#pragma unroll 1
  for (int s = SIGMA;; s += 2) {
    conv_step<0, true>(c, s, K1, V, B, A);
    if (s == NSTEP - 1) break;
    conv_step<1, true>(c, s + 1, K2, A, B, V);
  }
#pragma unroll 1
  for (int r = NSTEP - SIGMA - c.rank; r < NROUND - 1; r++) {
    NB_SYNC(NB_OPEN, 448);
    NB_ARRIVE(NB_CLOSE, 256);
  }
  NB_SYNC(NB_OPEN, 448);
}

struct TMaps { CUtensorMap m[2]; };

__global__ void __cluster_dims__(2, 1, 1) __launch_bounds__(512, 1)
convnext_kernel(const __grid_constant__ TMaps tms, const __nv_bfloat16* __restrict__ x, const __nv_bfloat16* __restrict__ dw,
                const __nv_bfloat16* __restrict__ w1, const __nv_bfloat16* __restrict__ w2, __nv_bfloat16* __restrict__ out,
                Scratch* scr, int zero) {
  extern __shared__ __align__(1024) uint8_t smem[];
  const uint32_t sb = (uint32_t)__cvta_generic_to_shared(smem);
  const int tid = threadIdx.x, lane = tid & 31;
  const int wid = __shfl_sync(0xffffffffu, tid >> 5, 0);
  const int rank = blockIdx.x & 1, cl = blockIdx.x >> 1;
  const int c0 = (cl & 15) * 32, r0 = (cl >> 4) * 128;
  const uint32_t peer_off = mapa(sb, rank ^ 1) - sb;

  if (wid == 12 && elect_one()) {
    mbar_init(sb + BAR_W + 48, 1);
#pragma unroll
    for (int i = 0; i < 4; i++) mbar_init(sb + BAR_RAW + 8 * i, 1);
    asm volatile("fence.mbarrier_init.release.cluster;" ::: "memory");
    mbar_expect(sb + BAR_W + 48, 49 * CH * 2);
    bulk_load(sb + OFF_XRES, dw, 49 * CH * 2, sb + BAR_W + 48);
#pragma unroll
    for (int i = 0; i < E0; i++) tma_raw(sb + OFF_RAW + i * RAW_BYTES, tms.m, rank, c0 / 2 - 2, r0 - 3 + 2 * i, sb + BAR_RAW + 8 * i);
  }
  if (wid == 14 && elect_one()) {
    asm volatile("cp.async.bulk.prefetch.L2.global [%0], 1152;" ::"l"(reinterpret_cast<const uint8_t*>(rank ? w2 : w1) + cl * 1152) : "memory");
    asm volatile("prefetch.tensormap [%0];" ::"l"(&tms.m[1]) : "memory");
#pragma unroll
    for (int i = 0; i < 3; i++) mbar_init(sb + BAR_W + 8 * i, 1);
#pragma unroll
    for (int i = 0; i < 2; i++) mbar_init(sb + BAR_CFULL + 8 * i, CCNT);
#pragma unroll
    for (int i = 0; i < 4; i++) mbar_init(sb + BAR_CEMPTY + 8 * i, 4);
#pragma unroll
    for (int i = 0; i < 2; i++) mbar_init(sb + BAR_XFULL + 8 * i, 1);
#pragma unroll
    for (int i = 0; i < 2; i++) mbar_expect(sb + BAR_CFULL + 8 * i, CTX);
    asm volatile("fence.mbarrier_init.release.cluster;" ::: "memory");
  }
  __syncwarp();
  asm volatile("barrier.cluster.arrive.relaxed.aligned;" ::: "memory");

  if (wid < 8) {
    if (blockIdx.x < 48) convert_tile(blockIdx.x, wid, reinterpret_cast<const uint4*>(w1), reinterpret_cast<const uint4*>(w2), sb, scr);
    MlpCtx m;
    m.sb = sb; m.wg = wid >> 2; m.warp = wid & 3; m.rank = rank; m.peer_off = peer_off; m.zero = zero;
    m.optr = reinterpret_cast<uint8_t*>(out) + ((size_t)(r0 + 4 * m.wg + 2 * rank) * IMG + c0 + 8 * m.warp) * (CH * 2);
    m.caddr = sb + OFF_C + m.wg * C_BYTES + (lane & 3) * 512 + ((m.warp * 8 + (lane >> 2) + 2 * (lane & 3)) & 31) * 16;
    m.xaddr = sb + OFF_XRES + m.wg * 12288 + m.warp * 1536 + ((lane >> 3) & 1) * 6144 + ((lane >> 4) * 4 + ((lane >> 2) & 1)) * 192 + (lane & 3) * 16;
    m.unscale = 0;
    asm volatile("setmaxnreg.inc.sync.aligned.u32 %0;" ::"n"(REG_MLP));
    const uint32_t bad = mlp_role(m);
    TC(scr, 3);
    if (bad) {
      asm volatile("cp.async.bulk.wait_group 0;" ::: "memory");
      mbar_wait(sb + BAR_W + 16, 0);
      __syncwarp();
      asm volatile("fence.proxy.async;" ::: "memory");
#pragma unroll 1
      for (int i = 0; i < 16; i++)
        if (bad >> i & 1)
          slow_tile(x, dw, w1, w2, out, r0 + 8 * i + 4 * m.wg + 2 * rank, c0 + 8 * m.warp,
                    reinterpret_cast<float*>(smem + OFF_RAW + wid * 2048));
    }
  } else {
    ConvCtx c;
    c.sb = sb; c.rank = rank; c.v = wid - 8; c.c0 = c0; c.r0 = r0; c.zero = zero; c.tm = tms.m; c.scr = scr;
    c.peer_off = peer_off;
    c.xsrc = reinterpret_cast<const uint8_t*>(x) + ((size_t)(r0 + 2 * rank) * IMG + c0) * (CH * 2);
    c.optr = reinterpret_cast<uint8_t*>(out) + ((size_t)(r0 + 2 * rank) * IMG + c0) * (CH * 2);
    if (wid < 12) {
      asm volatile("setmaxnreg.inc.sync.aligned.u32 %0;" ::"n"(REG_CONV));
      conv_role(c);
    } else {
      asm volatile("setmaxnreg.dec.sync.aligned.u32 24;");
      if (wid == 15) TC(scr, 0);
      if (wid == 12) {
#pragma unroll 1
        for (int h = E0 - 4; h < 0; h++) raw_refill(c, h);
        prod_rows(c);
      } else if (wid == 15) {
        prod_checks(c);
      } else if (wid == 14) {
#pragma unroll 1
        for (int n = 0; n < (1 << 20); n++) {
          unsigned v;
          __nanosleep(n ? PSL : PS0);
          asm volatile("ld.acquire.gpu.global.u32 %0, [%1];" : "=r"(v) : "l"(&scr->done) : "memory");
          if (__shfl_sync(0xffffffffu, v, 0) >= 48) break;
        }
        TP(scr, 90);
        asm volatile("barrier.cluster.wait.aligned;" ::: "memory");
        asm volatile("fence.proxy.async.global;" ::: "memory");
        if (elect_one()) {
          mbar_expect(sb + BAR_W, 36864 + 768);
          mbar_expect(sb + BAR_W + 8, 110592);
          bulk_load(sb + OFF_NRM, scr->nrm, 768, sb + BAR_W);
        }
        __syncwarp();
#pragma unroll 1
        for (int i = 0; i < 8; i++) {
          if (elect_one()) bulk_load(sb + i * 18432, reinterpret_cast<const uint8_t*>(scr->w) + i * 18432, 18432, sb + BAR_W + (i < 2 ? 0 : 8));
          if (i >= PFIRST) __nanosleep(PACE);
        }
        if (elect_one() && atomicAdd(&scr->seen, 1u) == gridDim.x - 1) { scr->done = 0; scr->seen = 0; }
      } else if (wid == 13) {
        prod_tiles(c);
        __syncwarp();
        if (elect_one()) asm volatile("mbarrier.arrive.shared::cta.b64 _, [%0];" ::"r"(sb + BAR_W + 16) : "memory");
      }
    }
  }
}

typedef CUresult (*EncodeFn)(CUtensorMap*, CUtensorMapDataType, cuuint32_t, void*, const cuuint64_t*, const cuuint64_t*,
                             const cuuint32_t*, const cuuint32_t*, CUtensorMapInterleave, CUtensorMapSwizzle,
                             CUtensorMapL2promotion, CUtensorMapFloatOOBfill);

}

extern "C" void kernel_launch(void* const* d_in, const int* in_sizes, int n_in, void* d_out, int out_size) {
  const __nv_bfloat16* x = (const __nv_bfloat16*)d_in[0];
  const __nv_bfloat16* dw = (const __nv_bfloat16*)d_in[1];
  const __nv_bfloat16* w1 = (const __nv_bfloat16*)d_in[2];
  const __nv_bfloat16* w2 = (const __nv_bfloat16*)d_in[3];
  __nv_bfloat16* out = (__nv_bfloat16*)d_out;

  static EncodeFn encode = nullptr;
  static Scratch* scr = nullptr;
  if (!encode) {
    cudaDriverEntryPointQueryResult st;
    void* fn = nullptr;
    cudaGetDriverEntryPoint("cuTensorMapEncodeTiled", &fn, cudaEnableDefault, &st);
    encode = (EncodeFn)fn;
    cudaGetSymbolAddress((void**)&scr, g_scratch);
    cudaFuncSetAttribute(convnext_kernel, cudaFuncAttributeMaxDynamicSharedMemorySize, SMEM_BYTES);
  }
  TMaps tm;
  cuuint64_t dims[4] = {CH, IMG / 2, IMG, 2};
  cuuint64_t strides[3] = {CH * 4, (cuuint64_t)IMG * CH * 2, CH * 2};
  cuuint32_t es[4] = {1, 1, 1, 1};
  for (int i = 0; i < 2; i++) {
    cuuint32_t box[4] = {i ? 16u : 32u, 19, 2, 1};
    encode(&tm.m[i], CU_TENSOR_MAP_DATA_TYPE_BFLOAT16, 4, (void*)x, dims, strides, box, es, CU_TENSOR_MAP_INTERLEAVE_NONE,
           i ? CU_TENSOR_MAP_SWIZZLE_NONE : CU_TENSOR_MAP_SWIZZLE_64B, PROMO, CU_TENSOR_MAP_FLOAT_OOB_FILL_NONE);
  }
  convnext_kernel<<<128, 512, SMEM_BYTES>>>(tm, x, dw, w1, w2, out, scr, 0);
}
```

```cpp
#include <cuda_runtime.h>
#include <cuda_bf16.h>
#include <cuda.h>
#include <stdint.h>

#define PROMO CU_TENSOR_MAP_L2_PROMOTION_L2_128B
#define CTX 6144
#define CCNT 5
#define PSL 100
#define PS0 1000
#define E0 1
#define PACE 100
#define PFIRST 1
namespace {

constexpr int IMG = 512, CH = 96;
constexpr int NSTEP = 67;
constexpr int SIGMA = 8;
constexpr int NROUND = 68;

constexpr uint32_t OFF_W1 = 0;
constexpr uint32_t OFF_W2 = 73728;
constexpr uint32_t OFF_RAW = 147456;
constexpr uint32_t RAW_PA = 2560, RAW_PB = 1280;
constexpr uint32_t RAW_BYTES = 2 * RAW_PA + 2 * RAW_PB;
constexpr uint32_t RAW_TX = 2 * 38 * 96;
constexpr uint32_t OFF_XRES = OFF_RAW + 4 * RAW_BYTES;
constexpr uint32_t OFF_C = OFF_XRES + 2 * 12288;
constexpr uint32_t C_BYTES = 12288;
constexpr uint32_t OFF_BAR = OFF_C + 2 * C_BYTES;
constexpr uint32_t BAR_RAW = OFF_BAR;
constexpr uint32_t BAR_CFULL = OFF_BAR + 32;
constexpr uint32_t BAR_CEMPTY = OFF_BAR + 48;
constexpr uint32_t BAR_XFULL = OFF_BAR + 80;
constexpr uint32_t BAR_W = OFF_BAR + 96;
constexpr uint32_t OFF_NRM = OFF_XRES + 9472;
constexpr uint32_t SMEM_BYTES = OFF_BAR + 160;

struct Scratch {
  uint4 w[2 * 73728 / 16];
  uint4 nrm[48];
  unsigned done, seen;
};
__device__ Scratch g_scratch;

constexpr float GELU_A = 0.32918364f;
constexpr uint32_t GELU_K2 = 0x40d940d9u;

constexpr int NB_CLOSE = 1, NB_SEC = 6  , NB_OPEN = 3, NB_PROD = 2, NB_PLAN = 4, NB_PREP = 5, NB_WG = 8  ;
#define REG_MLP 144
constexpr int REG_CONV = 488 - 2 * REG_MLP;

#define WG_FENCE() asm volatile("wgmma.fence.sync.aligned;" ::: "memory")
#define WG_COMMIT() asm volatile("wgmma.commit_group.sync.aligned;" ::: "memory")
#define WG_WAIT0() asm volatile("wgmma.wait_group.sync.aligned 0;" ::: "memory")
#define WG_WAIT1() asm volatile("wgmma.wait_group.sync.aligned 1;" ::: "memory")
#define PIN() asm volatile("pmevent 0;" ::: "memory")
#define NB_SYNC(id, n) asm volatile("bar.sync %0, %1;" ::"n"(id), "n"(n) : "memory")
#define NB_ARRIVE(id, n) asm volatile("bar.arrive %0, %1;" ::"n"(id), "n"(n) : "memory")

#define TC(scr, k)
#define TP(scr, k)

#define R24(c, d)                                                                                        \
  c(d[0]), c(d[1]), c(d[2]), c(d[3]), c(d[4]), c(d[5]), c(d[6]), c(d[7]), c(d[8]), c(d[9]), c(d[10]),    \
      c(d[11]), c(d[12]), c(d[13]), c(d[14]), c(d[15]), c(d[16]), c(d[17]), c(d[18]), c(d[19]), c(d[20]), \
      c(d[21]), c(d[22]), c(d[23])
#define WG_TXT(sd)                                                                             \
  "wgmma.mma_async.sync.aligned.m64n96k16.f16.f16.f16 "                                        \
  "{%0,%1,%2,%3,%4,%5,%6,%7,%8,%9,%10,%11,%12,%13,%14,%15,%16,%17,%18,%19,%20,%21,%22,%23}, " \
  "{%24,%25,%26,%27}, %28, " sd ", 1, 1, 1;\n"

__device__ __forceinline__ void wg_acc(uint32_t (&d)[24], const uint32_t* a, uint64_t db) {
  asm volatile(WG_TXT("1") : R24("+r", d) : "r"(a[0]), "r"(a[1]), "r"(a[2]), "r"(a[3]), "l"(db));
}
__device__ __forceinline__ void wg_init(uint32_t (&d)[24], const uint32_t* a, uint64_t db) {
  asm volatile(WG_TXT("0") : R24("=r", d) : "r"(a[0]), "r"(a[1]), "r"(a[2]), "r"(a[3]), "l"(db));
}
template <int N>
__device__ __forceinline__ void rfence(uint32_t (&d)[N]) {
#pragma unroll
  for (int i = 0; i < N; i++) asm volatile("" : "+r"(d[i])::"memory");
}
template <bool INIT, int KSTRIDE>
__device__ __forceinline__ void gemm6(uint32_t (&d)[24], const uint32_t (&a)[24], uint64_t db) {
#pragma unroll
  for (int k = 0; k < 6; k++) {
    if (INIT && k == 0) wg_init(d, &a[0], db);
    else wg_acc(d, &a[4 * k], db + k * KSTRIDE);
  }
  WG_COMMIT();
}

__device__ __forceinline__ void mbar_init(uint32_t bar, uint32_t cnt) {
  asm volatile("mbarrier.init.shared::cta.b64 [%0], %1;" ::"r"(bar), "r"(cnt) : "memory");
}
__device__ __forceinline__ void mbar_expect(uint32_t bar, uint32_t bytes) {
  asm volatile("mbarrier.arrive.expect_tx.shared::cta.b64 _, [%0], %1;" ::"r"(bar), "r"(bytes) : "memory");
}
__device__ __forceinline__ void mbar_arrive_cluster(uint32_t bar) {
  asm volatile("mbarrier.arrive.shared::cluster.b64 _, [%0];" ::"r"(bar) : "memory");
}
__device__ __forceinline__ bool mbar_try(uint32_t bar, uint32_t parity) {
  uint32_t ok;
  asm volatile(
      "{\n.reg .pred p;\nmbarrier.try_wait.parity.shared::cta.b64 p, [%1], %2;\nselp.u32 %0, 1, 0, p;\n}\n"
      : "=r"(ok)
      : "r"(bar), "r"(parity)
      : "memory");
  return ok;
}
__device__ __forceinline__ bool mbar_test(uint32_t bar, uint32_t parity) {
  uint32_t ok;
  asm volatile(
      "{\n.reg .pred p;\nmbarrier.test_wait.parity.shared::cta.b64 p, [%1], %2;\nselp.u32 %0, 1, 0, p;\n}\n"
      : "=r"(ok)
      : "r"(bar), "r"(parity)
      : "memory");
  return ok;
}
__device__ __forceinline__ void mbar_wait(uint32_t bar, uint32_t parity) {
  if (__builtin_expect(mbar_try(bar, parity), 1)) return;
#pragma unroll 1
  for (uint32_t n = 0; n < (1u << 16) && !mbar_try(bar, parity); n++) {}
}
__device__ __forceinline__ uint32_t mapa(uint32_t addr, uint32_t rank) {
  uint32_t r;
  asm("mapa.shared::cluster.u32 %0, %1, %2;" : "=r"(r) : "r"(addr), "r"(rank));
  return r;
}
__device__ __forceinline__ void tma_raw(uint32_t dst, const CUtensorMap* tm, int rank, int w2, int h, uint32_t bar) {
  mbar_expect(bar, RAW_TX);
#pragma unroll
  for (int k = 0; k < 4; k++) {
    const int e = k & 1;
    asm volatile(
        "cp.async.bulk.tensor.4d.shared::cluster.global.mbarrier::complete_tx::bytes [%0], [%1, {%2, %3, %4, %5}], [%6];"
        ::"r"(dst + (k < 2 ? e * RAW_PA : 2 * RAW_PA + e * RAW_PB)), "l"(tm + (k >> 1)), "r"(k < 2 ? 64 * rank : 32 + 16 * rank), "r"(w2 + e),
        "r"(h), "r"(1 - e), "r"(bar)
        : "memory");
  }
}
__device__ __forceinline__ void bulk_load(uint32_t dst, const void* src, uint32_t bytes, uint32_t bar) {
  asm volatile("cp.async.bulk.shared::cluster.global.mbarrier::complete_tx::bytes [%0], [%1], %2, [%3];" ::"r"(dst),
               "l"(src), "r"(bytes), "r"(bar)
               : "memory");
}
__device__ __forceinline__ void bulk_load_last(uint32_t dst, const void* src, uint32_t bytes, uint32_t bar) {
  asm volatile(
      "{\n.reg .b64 pol;\ncreatepolicy.fractional.L2::evict_first.b64 pol, 1.0;\n"
      "cp.async.bulk.shared::cluster.global.mbarrier::complete_tx::bytes.L2::cache_hint [%0], [%1], %2, [%3], pol;\n}\n" ::"r"(dst),
      "l"(src), "r"(bytes), "r"(bar)
      : "memory");
}
__device__ __forceinline__ uint32_t pack_bf16(float lo, float hi) {
  uint32_t r;
  asm("cvt.rn.bf16x2.f32 %0, %1, %2;" : "=r"(r) : "f"(hi), "f"(lo));
  return r;
}
__device__ __forceinline__ uint32_t pack_f16(float lo, float hi) {
  uint32_t r;
  asm("cvt.rn.f16x2.f32 %0, %1, %2;" : "=r"(r) : "f"(hi), "f"(lo));
  return r;
}
__device__ __forceinline__ float bf_lo(uint32_t v) { return __uint_as_float(v << 16); }
__device__ __forceinline__ float bf_hi(uint32_t v) { return __uint_as_float(v & 0xffff0000u); }
__device__ __forceinline__ uint32_t bf_add(uint32_t a, uint32_t b) {
  uint32_t r;
  asm("add.rn.bf16x2 %0, %1, %2;" : "=r"(r) : "r"(a), "r"(b));
  return r;
}
__device__ __forceinline__ uint32_t bf_mul(uint32_t a, uint32_t b) {
  uint32_t r;
  asm("mul.rn.bf16x2 %0, %1, %2;" : "=r"(r) : "r"(a), "r"(b));
  return r;
}
__device__ __forceinline__ uint32_t bf_fma(uint32_t a, uint32_t b, uint32_t c) {
  uint32_t r;
  asm("fma.rn.bf16x2 %0, %1, %2, %3;" : "=r"(r) : "r"(a), "r"(b), "r"(c));
  return r;
}

__device__ __forceinline__ uint32_t h_add(uint32_t a, uint32_t b) {
  uint32_t r;
  asm("add.rn.f16x2 %0, %1, %2;" : "=r"(r) : "r"(a), "r"(b));
  return r;
}
__device__ __forceinline__ uint32_t h_mul(uint32_t a, uint32_t b) {
  uint32_t r;
  asm("mul.rn.f16x2 %0, %1, %2;" : "=r"(r) : "r"(a), "r"(b));
  return r;
}
__device__ __forceinline__ uint32_t h_fma(uint32_t a, uint32_t b, uint32_t c) {
  uint32_t r;
  asm("fma.rn.f16x2 %0, %1, %2, %3;" : "=r"(r) : "r"(a), "r"(b), "r"(c));
  return r;
}
__device__ __forceinline__ float h_sum(uint32_t v) {
  float lo, hi;
  asm("{\n.reg .b16 l, h;\nmov.b32 {l, h}, %2;\ncvt.f32.f16 %0, l;\ncvt.f32.f16 %1, h;\n}\n" : "=f"(lo), "=f"(hi) : "r"(v));
  return lo + hi;
}
__device__ __forceinline__ void lds128(uint32_t (&v)[4], uint32_t a) {
  asm volatile("ld.shared.v4.b32 {%0,%1,%2,%3}, [%4];" : "=r"(v[0]), "=r"(v[1]), "=r"(v[2]), "=r"(v[3]) : "r"(a) : "memory");
}

template <int LO, int HI>
__device__ __forceinline__ void gelu(uint32_t (&o)[24], const uint32_t (&d)[24]) {
#pragma unroll
  for (int qq = LO; qq < HI; qq++) {
    const int q = (qq + 4) % 24;
    uint32_t t, u;
    asm("fma.rn.f16x2 %0, %1, %1, %2;" : "=r"(t) : "r"(d[q]), "r"(GELU_K2));
    asm("mul.rn.f16x2 %0, %1, %2;" : "=r"(u) : "r"(d[q]), "r"(t));
    asm("tanh.approx.f16x2 %0, %1;" : "=r"(t) : "r"(u));
    asm("fma.rn.f16x2 %0, %1, %2, %1;" : "=r"(o[q]) : "r"(d[q]), "r"(t));
  }
}

__device__ __forceinline__ uint32_t laneid() {
  uint32_t l;
  asm volatile("mov.u32 %0, %%laneid;" : "=r"(l));
  return l;
}

__device__ __forceinline__ bool elect_one() {
  uint32_t p;
  asm volatile("{\n.reg .pred p;\nelect.sync _|p, 0xffffffff;\nselp.u32 %0, 1, 0, p;\n}\n" : "=r"(p));
  return p;
}

__device__ __forceinline__ uint32_t clock_pin() {
  uint32_t t;
  asm volatile("mov.u32 %0, %%clock;" : "=r"(t)::"memory");
  return t;
}

struct MlpCtx {
  uint32_t sb;
  uint32_t caddr;
  uint32_t xaddr;
  uint32_t unscale;
  uint32_t peer_off;
  int wg, warp, rank, zero;
  uint8_t* optr;
};

__device__ __forceinline__ void ln_wait(const MlpCtx& m, int i) { mbar_wait(m.sb + BAR_CFULL + 8 * m.wg, i & 1); }
__device__ __forceinline__ void ln_load(const MlpCtx& m, uint32_t (&c)[24]) {
#pragma unroll
  for (int p = 0; p < 6; p++)
    asm volatile("ld.shared.v4.b32 {%0,%1,%2,%3}, [%4];"
                 : "=r"(c[4 * p]), "=r"(c[4 * p + 1]), "=r"(c[4 * p + 2]), "=r"(c[4 * p + 3])
                 : "r"(m.caddr + p * 2048)
                 : "memory");
}
__device__ __forceinline__ void ln_shfl(float (&st)[8], int mask) {
#pragma unroll
  for (int k = 0; k < 4; k++) st[4 + k] = __shfl_xor_sync(0xffffffffu, st[k], mask);
}
__device__ __forceinline__ void ln_fold(float (&st)[8]) {
#pragma unroll
  for (int k = 0; k < 4; k++) st[k] += st[4 + k];
}
__device__ __forceinline__ void ln_sums(const uint32_t (&c)[24], float (&st)[8]) {
#pragma unroll
  for (int r = 0; r < 2; r++) {
    uint32_t s0 = h_add(c[r], c[r + 2]), s1 = h_add(c[r + 4], c[r + 6]), s2 = h_add(c[r + 8], c[r + 10]);
    uint32_t s3 = h_add(c[r + 12], c[r + 14]), s4 = h_add(c[r + 16], c[r + 18]), s5 = h_add(c[r + 20], c[r + 22]);
    s0 = h_add(s0, s1); s2 = h_add(s2, s3); s4 = h_add(s4, s5);
    st[r] = h_sum(h_add(h_add(s0, s2), s4));
    uint32_t q0 = h_mul(c[r], c[r]), q1 = h_mul(c[r + 2], c[r + 2]);
#pragma unroll
    for (int p = 2; p < 12; p += 2) {
      q0 = h_fma(c[2 * p + r], c[2 * p + r], q0);
      q1 = h_fma(c[2 * p + 2 + r], c[2 * p + 2 + r], q1);
    }
    st[2 + r] = h_sum(h_add(q0, q1));
  }
}
__device__ __forceinline__ void ln_release(const MlpCtx& m) {
  const uint32_t e = m.sb + BAR_CEMPTY + 8 * (2 * m.rank + m.wg);
  asm volatile(
      "{\n.reg .pred p, q;\nelect.sync _|p, 0xffffffff;\nsetp.eq.and.s32 q, %3, 0, p;\n"
      "@q mbarrier.arrive.expect_tx.shared::cta.b64 _, [%0], %4;\n"
      "@p mbarrier.arrive.shared::cluster.b64 _, [%1];\n"
      "@p mbarrier.arrive.shared::cluster.b64 _, [%2];\n}\n" ::"r"(m.sb + BAR_CFULL + 8 * m.wg),
      "r"(e), "r"(e + m.peer_off), "r"(m.warp), "n"(CTX)
      : "memory");
}
__device__ __forceinline__ bool ln_stats(float (&st)[8]) {
  bool ok = true;
#pragma unroll
  for (int r = 0; r < 2; r++) {
    const float nm = (st[r] + st[4 + r]) * (-1.0f / 96.0f);
    const float e2 = fmaf(st[2 + r] + st[6 + r], 1.0f / 96.0f, 1e-5f);
    float rs;
    asm("rsqrt.approx.ftz.f32 %0, %1;" : "=f"(rs) : "f"(fmaf(-nm, nm, e2)));
    ok = ok && (rs * rs * e2 <= 17.0f) && (e2 >= 1.001e-5f);
    const float rr = rs * GELU_A, dd = rr * nm;
    st[r] = __uint_as_float(pack_f16(rr, rr));
    st[2 + r] = __uint_as_float(pack_f16(dd, dd));
  }
  return ok;
}
__device__ __forceinline__ void ln_restat(bool ok, const uint32_t (&c)[24], float (&st)[8], uint32_t& bad, uint32_t bit,
                                          uint32_t zero) {
  if (__builtin_expect(__any_sync(0xffffffffu, !ok), 0)) {
#pragma unroll
    for (int r = 0; r < 2; r++) {
      float nm = 0.f, var = 0.f;
#pragma unroll
      for (int p = 0; p < 12; p++) {
        nm += h_sum(c[2 * p + r] ^ zero);
        if (p % 3 == 2) { asm volatile("" : "+f"(nm)); PIN(); }
      }
      nm += __shfl_xor_sync(0xffffffffu, nm, 1);
      nm += __shfl_xor_sync(0xffffffffu, nm, 2);
      nm *= -1.0f / 96.0f;
#pragma unroll
      for (int p = 0; p < 12; p++) {
        float lo, hi;
        asm volatile("{\n.reg .b16 l, h;\nmov.b32 {l, h}, %2;\ncvt.f32.f16 %0, l;\ncvt.f32.f16 %1, h;\n}\n" : "=f"(lo), "=f"(hi) : "r"(c[2 * p + r]));
        var = fmaf(lo + nm, lo + nm, fmaf(hi + nm, hi + nm, var));
        if (p % 3 == 2) { asm volatile("" : "+f"(var)); PIN(); }
      }
      var += __shfl_xor_sync(0xffffffffu, var, 1);
      var += __shfl_xor_sync(0xffffffffu, var, 2);
      const float rr = rsqrtf(fmaf(var, 1.0f / 96.0f, 1e-5f)) * GELU_A;
      st[r] = __uint_as_float(pack_f16(rr, rr));
      const float dd = 0.5f * h_sum(__float_as_uint(st[r])) * nm;
      st[2 + r] = __uint_as_float(pack_f16(dd, dd));
      if (!(rr >= 0x1p-14f && fabsf(dd) <= 16.0f && var >= 1e-8f)) bad |= bit;
    }
  }
}
__device__ __forceinline__ void ln_apply(uint32_t (&a)[24], const uint32_t (&c)[24], const float (&st)[8]) {
#pragma unroll
  for (int p = 0; p < 24; p++) {
    a[p] = h_fma(c[p], __float_as_uint(st[p & 1]), __float_as_uint(st[2 + (p & 1)]));
  }
}

__device__ __noinline__ void slow_tile(const __nv_bfloat16* x, const __nv_bfloat16* dw, const __nv_bfloat16* w1,
                                       const __nv_bfloat16* w2, __nv_bfloat16* out, int row0, int col0, float* buf) {
  const int lane = threadIdx.x & 31;
  for (int px = 0; px < 16; px++) {
    const int row = row0 + (px >> 3), col = col0 + (px & 7);
    float c[3] = {0.f, 0.f, 0.f};
    for (int i = 0; i < 7; i++)
      for (int j = 0; j < 7; j++) {
        const int rr = row + i - 3, cc = col + j - 3;
        if (rr < 0 || rr >= IMG || cc < 0 || cc >= IMG) continue;
        for (int k = 0; k < 3; k++)
          c[k] = fmaf(__bfloat162float(x[((size_t)rr * IMG + cc) * CH + lane + 32 * k]), __bfloat162float(dw[(i * 7 + j) * CH + lane + 32 * k]), c[k]);
      }
    float mean = (c[0] + c[1] + c[2]) * (1.0f / 96.0f);
    for (int o = 16; o; o >>= 1) mean += __shfl_xor_sync(0xffffffffu, mean, o);
    float var = 0.f;
    for (int k = 0; k < 3; k++) { c[k] -= mean; var = fmaf(c[k] * (1.0f / 96.0f), c[k], var); }
    for (int o = 16; o; o >>= 1) var += __shfl_xor_sync(0xffffffffu, var, o);
    const float rs = 1.0f / sqrtf(var + 1e-5f);
    __syncwarp();
    for (int k = 0; k < 3; k++) buf[lane + 32 * k] = c[k] * rs;
    __syncwarp();
    for (int n = lane; n < 4 * CH; n += 32) {
      float y = 0.f;
      for (int k = 0; k < CH; k++) y = fmaf(buf[k], __bfloat162float(w1[k * 4 * CH + n]), y);
      buf[CH + n] = 0.5f * y * (1.0f + tanhf(0.7978845608f * (y + 0.044715f * y * y * y)));
    }
    __syncwarp();
    for (int n = lane; n < CH; n += 32) {
      float o = 0.f;
      for (int k = 0; k < 4 * CH; k++) o = fmaf(buf[CH + k], __bfloat162float(w2[k * CH + n]), o);
      const size_t idx = ((size_t)row * IMG + col) * CH + n;
      out[idx] = __float2bfloat16(__bfloat162float(x[idx]) + o);
    }
  }
}

__device__ __forceinline__ void x_load(const MlpCtx& m, uint32_t (&x)[24]) {
#pragma unroll
  for (int k = 0; k < 6; k++)
    asm volatile("ld.shared.v4.b32 {%0,%1,%2,%3}, [%4];"
                 : "=r"(x[4 * k]), "=r"(x[4 * k + 1]), "=r"(x[4 * k + 2]), "=r"(x[4 * k + 3])
                 : "r"(m.xaddr + (k / 3) * 384 + (k % 3) * 64)
                 : "memory");
}
template <int LO, int HI>
__device__ __forceinline__ void epilogue(const MlpCtx& m, const uint32_t (&d)[24], uint32_t (&x)[24]) {
#pragma unroll
  for (int k = LO; k < HI; k++) {
    const int r = k / 3, q = k % 3;
    uint32_t* y = &x[4 * k];
#pragma unroll
    for (int j = 0; j < 4; j++) {
      uint32_t v = d[2 * (4 * q + j) + r];
      float lo, hi;
      asm("{\n.reg .b16 l, h;\nmov.b32 {l, h}, %2;\ncvt.f32.f16 %0, l;\ncvt.f32.f16 %1, h;\n}\n" : "=f"(lo), "=f"(hi) : "r"(v));
      asm("fma.rn.bf16x2 %0, %1, %2, %0;" : "+r"(y[j]) : "r"(pack_bf16(lo, hi)), "r"(m.unscale));
    }
    asm volatile("st.shared.v4.b32 [%0], {%1,%2,%3,%4};" ::"r"(m.xaddr + r * 384 + q * 64), "r"(y[0]), "r"(y[1]), "r"(y[2]), "r"(y[3])
                 : "memory");
  }
}
__device__ __forceinline__ void out_store_last(const MlpCtx& m) {
  asm volatile("fence.proxy.async.shared::cta;" ::: "memory");
  __syncwarp();
  if (elect_one()) {
    const uint32_t src = m.sb + OFF_XRES + m.wg * 12288 + m.warp * 1536;
    uint8_t* dst = m.optr;
    asm volatile("cp.async.bulk.global.shared::cta.bulk_group [%0], [%1], 1536;" ::"l"(dst), "r"(src) : "memory");
    asm volatile("cp.async.bulk.global.shared::cta.bulk_group [%0], [%1], 1536;" ::"l"(dst + IMG * CH * 2), "r"(src + 6144) : "memory");
    asm volatile("cp.async.bulk.commit_group;" ::: "memory");
  }
}

#define FSET 3
template <int J> constexpr bool goes_first = J == FSET || J == ((FSET + 1) & 3);
template <int J> __device__ __forceinline__ void tok_wait() {
  if (goes_first<J>) NB_SYNC(NB_CLOSE, 256);
  else NB_SYNC(NB_SEC + (J & 1), 256);
}
template <int J, bool PROD = true> __device__ __forceinline__ void tok_next() {
  if (goes_first<J>) NB_ARRIVE(NB_SEC + (J & 1), 256);
  if (J == 0 && PROD) NB_ARRIVE(NB_PROD, 160);
}
__device__ __forceinline__ void tok_pass() { NB_ARRIVE(NB_OPEN, 448); }
template <int J> __device__ __forceinline__ void tok_idle() { tok_wait<J>(); tok_next<J, false>(); tok_pass(); }

constexpr uint64_t CHK = 1152;

__device__ __forceinline__ float warp_sumsq(const uint32_t (&q)[4]) {
  const uint32_t t = bf_add(bf_add(q[0], q[1]), bf_add(q[2], q[3]));
  float f = bf_lo(t) + bf_hi(t);
#pragma unroll
  for (int o = 16; o; o >>= 1) f += __shfl_xor_sync(0xffffffffu, f, o);
  return f;
}
__device__ __forceinline__ int norm_exp(float f) { return (((int)(__float_as_uint(f * 1.5f) >> 23) - 127) >> 1) + 1; }
__device__ __forceinline__ int scale_exp(int e1, int e2) { return min(11 - e1 - e2, 14 - e2); }

__device__ __forceinline__ void convert_tile(int t, int k, const uint4* w1, const uint4* w2, uint32_t st, Scratch* scr) {
  const int lane = threadIdx.x & 31, k7 = lane & 7;
  const int j = t / 6, ks = t % 6, e = ks % 3, t4 = k7 >> 1;
  const uint4* src = t < 24 ? w1 + ((e < 2 ? 64 * (ks / 3) + 8 * t4 + 4 * e : 32 + 16 * (ks / 3) + 4 * t4) + (k7 & 1)) * 48 + j * 12 + (lane >> 3)
                            : w2 + (t - 24) * 192 + (lane >> 2) * 12 + (lane & 3);
  src += (k / 3) * 96 + (k % 3) * 4;
  if (k >= 6) src = (k == 6 ? w1 : w2) + lane * 145;
  const uint4 v = __ldg(src);
  const uint32_t w[4] = {v.x, v.y, v.z, v.w};
  const uint32_t q[4] = {bf_mul(v.x, v.x), bf_mul(v.y, v.y), bf_mul(v.z, v.z), bf_mul(v.w, v.w)};
  asm volatile("st.shared.f32 [%0], %1;" ::"r"(st + 3088 + 4 * k), "f"(warp_sumsq(q)) : "memory");
  NB_SYNC(NB_PREP, 256);
  uint32_t a[4], b[4], o[4];
  lds128(a, st + 3088);
  lds128(b, st + 3104);
  const int s = max(-64, min(64, scale_exp(norm_exp(144.f * __uint_as_float(b[2])), norm_exp(144.f * __uint_as_float(b[3]))) - 3));
  const uint32_t dst = st + k7 * 16 + (lane >> 3) * 256 + (k / 3) * 128 + (k % 3) * 1024;
  if (k >= 6) {
    const float f = ((__uint_as_float(a[0]) + __uint_as_float(a[1])) + (__uint_as_float(a[2]) + __uint_as_float(a[3]))) +
                    (__uint_as_float(b[0]) + __uint_as_float(b[1]));
    asm volatile("st.shared.v2.b32 [%0], {%1,%2};" ::"r"(st + 3072), "r"(__float_as_uint(f)), "r"(s) : "memory");
  } else if (t < 24) {
#pragma unroll
    for (int i = 0; i < 4; i++) o[i] = pack_f16(bf_lo(w[i]), bf_hi(w[i]));
    asm volatile("st.shared.v4.b32 [%0], {%1,%2,%3,%4};" ::"r"(dst), "r"(o[0]), "r"(o[1]), "r"(o[2]), "r"(o[3]) : "memory");
  } else {
    constexpr float F = 0.5f / GELU_A, FHI = 1.515625f;
    const float p2 = __uint_as_float((uint32_t)(127 + s - 56) << 23);
    const uint32_t hi = pack_bf16(FHI * 0x1p-56f, FHI * 0x1p-56f), lo = pack_bf16((F - FHI) * 0x1p-56f, (F - FHI) * 0x1p-56f);
    const uint32_t pw = pack_bf16(p2, p2);
#pragma unroll
    for (int i = 0; i < 4; i++) {
      const uint32_t ws = bf_mul(w[i], pw), u = bf_fma(ws, hi, bf_mul(ws, lo));
      o[i] = (u & 0x7fff7fffu) * 7u + u;
    }
    asm volatile("stmatrix.sync.aligned.m8n8.x4.shared.b16 [%0], {%1,%2,%3,%4};" ::"r"(dst), "r"(o[0]), "r"(o[1]), "r"(o[2]), "r"(o[3])
                 : "memory");
  }
  asm volatile("fence.proxy.async.shared::cta;" ::: "memory");
  NB_SYNC(NB_PREP, 256);
  if (k == 0 && elect_one()) {
    asm volatile("cp.async.bulk.global.shared::cta.bulk_group [%0], [%1], 3072;" ::"l"(scr->w + t * 192), "r"(st) : "memory");
    asm volatile("cp.async.bulk.global.shared::cta.bulk_group [%0], [%1], 16;" ::"l"(scr->nrm + t), "r"(st + 3072) : "memory");
    asm volatile("cp.async.bulk.commit_group;" ::: "memory");
    asm volatile("cp.async.bulk.wait_group 0;" ::: "memory");
    asm volatile("red.relaxed.gpu.global.add.u32 [%0], 1;" ::"l"(&scr->done) : "memory");
  }
}

__device__ __forceinline__ uint32_t mlp_role(const MlpCtx& m0) {
  MlpCtx m = m0;
  uint32_t bad = 0;
  asm volatile("barrier.cluster.wait.aligned;" ::: "memory");
  if ((m.sb & 0x3FFFF) != 1024) bad = 0xffffu;
  constexpr uint64_t dW1 = (uint64_t)((1024 + OFF_W1) >> 4) | ((uint64_t)8 << 16) | ((uint64_t)16 << 32);
  constexpr uint64_t dW2 = dW1 + (OFF_W2 >> 4);
  uint32_t A1[24], g[24], d[24], cn[24], D2[24];
  float st[8];
  if (m.wg & m.rank) tok_idle<3>();
  else if (m.wg) tok_idle<0>();
  else if (m.rank) tok_idle<1>();
  ln_wait(m, 0);
  ln_load(m, cn);
  ln_sums(cn, st);
  ln_shfl(st, 1);
  ln_release(m);
  ln_fold(st);
  ln_shfl(st, 2);
  ln_restat(ln_stats(st), cn, st, bad, 1, m.zero);
  ln_apply(A1, cn, st);
  {
    const int lane = threadIdx.x & 31;
    mbar_wait(m.sb + BAR_W, 0);
    float n1, n2;
    int s;
    asm volatile("ld.shared.b32 %0, [%1];" : "=r"(s) : "r"(m.sb + OFF_NRM + 4) : "memory");
    asm volatile("ld.shared.f32 %0, [%1];" : "=f"(n1) : "r"(m.sb + OFF_NRM + 16 * min(lane, 23)) : "memory");
    asm volatile("ld.shared.f32 %0, [%1];" : "=f"(n2) : "r"(m.sb + OFF_NRM + 384 + 16 * min(lane, 23)) : "memory");
    if (lane >= 24) n1 = n2 = 0.f;
#pragma unroll
    for (int o = 16; o; o >>= 1) {
      n1 += __shfl_xor_sync(0xffffffffu, n1, o);
      n2 += __shfl_xor_sync(0xffffffffu, n2, o);
    }
    const int e1 = norm_exp(n1), e2 = norm_exp(n2), smax = scale_exp(e1, e2);
    if (e1 > 12 || e1 < -5 || e2 > 50 || e2 < -50 || s > smax || s < smax - 7) bad = 0xffffu;
    m.unscale = __shfl_sync(0xffffffffu, ((uint32_t)(127 - s) << 7) * 0x10001u, 0);
  }
  if (m.wg & m.rank) tok_idle<0>();
  if (m.wg) tok_idle<1>();
  {
    uint32_t d0[24];
    WG_FENCE();
    tok_wait<2>();
    tok_next<2>();
    gemm6<true, 192>(d0, A1, dW1);
    tok_pass(); PIN();
    WG_WAIT0(); rfence(d0);
    WG_FENCE();
    tok_wait<3>();
    tok_next<3>();
    gemm6<true, 192>(d, A1, dW1 + CHK);
    tok_pass(); PIN();
    gelu<0, 24>(g, d0);
    PIN();
    mbar_wait(m.sb + BAR_W + 8, 0);
    ln_wait(m, 1);
    WG_WAIT0(); rfence(d);
  }
#define G2(INIT, a, j)                      \
  WG_FENCE();                               \
  tok_wait<j>();                            \
  gemm6<INIT, 192>(D2, a, dW2 + (j) * CHK); \
  tok_next<j>(); PIN();
#define G1(dst, j, P)                       \
  P(); WG_WAIT0(); rfence(D2);              \
  WG_FENCE();                               \
  gemm6<true, 192>(dst, A1, dW1 + (j) * CHK); \
  tok_pass(); P();
#define ROUND_END(dst, j)                   \
  PIN(); WG_WAIT0(); rfence(dst);
#define GA 9
#define GB 12
#define GC 13
#define GD 11
#pragma unroll 1
  for (int i = 0;; i++) {
    uint32_t g1[24], d2[24], g2[24], d3[24], g3[24], d0[24];
    ln_load(m, cn);
    PIN();
    G2(true, g, 0)
    gelu<0, GA>(g1, d);
    G1(d2, 2, PIN)
    ln_sums(cn, st);
    gelu<GA, 24>(g1, d);
    PIN();
    ln_shfl(st, 1);
    ROUND_END(d2, 0)

    G2(false, g1, 1)
    ln_fold(st);
    gelu<0, GB>(g2, d2);
    PIN();
    ln_shfl(st, 2);
    G1(d3, 3, PIN)
    const bool ok = ln_stats(st);
    gelu<GB, 24>(g2, d2);
    PIN();
    ln_restat(ok, cn, st, bad, 2u << i, m.zero);
    ROUND_END(d3, 1)

    if (i == 15) {
      G2(false, g2, 2)
      tok_pass();
      gelu<0, 24>(g3, d3);
      PIN();
      x_load(m, cn);
      ROUND_END(D2, 2)
      G2(false, g3, 3)
      tok_pass();
      WG_WAIT0(); rfence(D2);
      epilogue<0, 6>(m, D2, cn);
      break;
    }
    G2(false, g2, 2)
    ln_apply(A1, cn, st);
    PIN();
    gelu<0, GC>(g3, d3);
    G1(d0, 0, PIN)
    gelu<GC, 24>(g3, d3);
    PIN();
    x_load(m, cn);
    ROUND_END(d0, 2)

    G2(false, g3, 3)
    gelu<0, GD>(g, d0);
    G1(d, 1, PIN)
    epilogue<0, 6>(m, D2, cn);
    gelu<GD, 24>(g, d0);
    PIN();
    asm volatile("fence.proxy.async.shared::cta;" ::: "memory");
    ROUND_END(d, 3)
  }
  out_store_last(m);
  if (m.wg == 0) { tok_idle<0>(); tok_idle<1>(); }
  asm volatile("cp.async.bulk.wait_group.read 0;" ::: "memory");
  return __reduce_or_sync(0xffffffffu, bad & 0xffffu);
}

struct ConvCtx {
  uint32_t sb;
  uint32_t a0, a_c;
  uint32_t peer_off;
  int rank, v, c0, r0, dir, zero;
  const CUtensorMap* tm;
  Scratch* scr;
  const uint8_t* xsrc;
  uint8_t* optr;
};

__device__ __forceinline__ void raw_refill(const ConvCtx& c, int s) {
  if (s + 4 < NSTEP && elect_one())
    tma_raw(c.sb + OFF_RAW + (s & 3) * RAW_BYTES, c.tm, c.rank, c.c0 / 2 - 2, c.r0 + c.dir * (2 * s + 5), c.sb + BAR_RAW + 8 * (s & 3));
}
__device__ __forceinline__ void step_ready(const ConvCtx& c, int s) {
  const int nx = (s + 1) & 3, par = ((s + 1) >> 2) & 1;
  if (s + 1 < NSTEP) mbar_wait(c.sb + BAR_RAW + 8 * nx, par);
  if (s >= 7 && s < NSTEP) mbar_wait(c.sb + BAR_CEMPTY + 8 * (2 * (nx & 1) + (nx >> 1)), par);
}

__device__ __forceinline__ void c_release(const ConvCtx& c, uint32_t w) {
  const uint32_t e = c.sb + BAR_CEMPTY + 8 * (2 * c.rank + w);
  asm volatile(
      "{\n.reg .pred p;\nelect.sync _|p, 0xffffffff;\n"
      "@p mbarrier.arrive.expect_tx.shared::cta.b64 _, [%0], %3;\n"
      "@p mbarrier.arrive.shared::cluster.b64 _, [%1], 4;\n"
      "@p mbarrier.arrive.shared::cluster.b64 _, [%2], 4;\n}\n" ::"r"(c.sb + BAR_CFULL + 8 * w),
      "r"(e), "r"(e + c.peer_off), "n"(CTX)
      : "memory");
}

__device__ __forceinline__ void prod_rows(const ConvCtx& c) {
#pragma unroll 1
  for (int s = 0; s < NROUND + SIGMA + c.rank; s++) {
    if (s < SIGMA) NB_SYNC(NB_PLAN, 192);
    else NB_SYNC(NB_OPEN, 448);
    raw_refill(c, s);
  }
}
__device__ __forceinline__ void prod_checks(const ConvCtx& c) {
  asm volatile("barrier.cluster.wait.aligned;" ::: "memory");
#pragma unroll 1
  for (int s = 0; s < NROUND + SIGMA + c.rank; s++) {
    const int r = s - SIGMA - c.rank;
    const int u = (r & 1) ? (r >> 1) - 1 : (r >> 1) + 2;
    step_ready(c, s);
    if (s < 16) TP(c.scr, 100 + s);
    if (u >= ((r & 1) ? 0 : 4) && u < 32) mbar_wait(c.sb + ((r & 1) ? BAR_XFULL : BAR_CFULL) + 8 * (u & 1), (u >> 1) & 1);
    if (s < SIGMA) NB_SYNC(NB_PLAN, 192);
    else NB_SYNC(NB_OPEN, 448);
    TP(c.scr, s);
    if (r == 3) TC(c.scr, 1);
    if (r == 55) TC(c.scr, 2);
  }
}
__device__ __forceinline__ void prod_tiles(const ConvCtx& c) {
  asm volatile("barrier.cluster.wait.aligned;" ::: "memory");
#pragma unroll 1
  for (int n = 1; n < 33; n++) {
    const uint32_t w = (n + 1) & 1;
    const uint32_t buf = c.sb + OFF_XRES + w * 12288;
    NB_SYNC(NB_PROD, 160);
    if (n < 29) c_release(c, w);
    if (n >= 3) {
      uint8_t* dst = c.optr + (n - 3) * c.dir * (4 * IMG * CH * 2);
      if (elect_one()) {
        asm volatile("cp.async.bulk.global.shared::cta.bulk_group [%0], [%1], 6144;" ::"l"(dst), "r"(buf) : "memory");
        asm volatile("cp.async.bulk.global.shared::cta.bulk_group [%0], [%1], 6144;" ::"l"(dst + IMG * CH * 2), "r"(buf + 6144) : "memory");
        asm volatile("cp.async.bulk.commit_group;" ::: "memory");
        asm volatile("cp.async.bulk.wait_group.read 0;" ::: "memory");
      }
      __syncwarp();
    }
    {
      const uint8_t* src = c.xsrc + (n - 1) * c.dir * (4 * IMG * CH * 2);
      if (elect_one()) {
        mbar_expect(c.sb + BAR_XFULL + 8 * w, 12288);
        bulk_load_last(buf, src, 6144, c.sb + BAR_XFULL + 8 * w);
        bulk_load_last(buf + 6144, src + IMG * CH * 2, 6144, c.sb + BAR_XFULL + 8 * w);
      }
    }
  }
  asm volatile("cp.async.bulk.wait_group 0;" ::: "memory");
}

template <int LO, int HI>
__device__ __forceinline__ void conv_ld8(uint32_t a0, uint32_t (&r)[6][6]) {
  const uint32_t a2 = a0 ^ (16 | ((a0 >> 2) & 32));
  const uint32_t a[3] = {a0, (a0 & 64) ? a2 : a0, a2};
#pragma unroll
  for (int j = LO; j < HI; j++)
    asm volatile("ld.shared.v4.b32 {%0,%1,%2,%3}, [%4];"
                 : "=r"(r[j][0]), "=r"(r[j][1]), "=r"(r[j][2]), "=r"(r[j][3])
                 : "r"(a[j >> 1] + (j >> 1) * 64 + (j & 1) * RAW_PA)
                 : "memory");
}
__device__ __forceinline__ void conv_ld4(uint32_t a0, uint32_t stage, int v, uint32_t (&r)[6][6]) {
  const uint32_t ab = ((a0 >> 1) & ~31u) + (stage / 2 + 2 * RAW_PA + 8 * v);
#pragma unroll
  for (int j = 0; j < 6; j++) {
    uint32_t a = ab + (j >> 1) * 32;
    asm volatile("ld.shared.v2.b32 {%0,%1}, [%2];" : "=r"(r[j][4]), "=r"(r[j][5]) : "r"(a + (j & 1) * RAW_PB) : "memory");
  }
}
template <int LO, int HI>
__device__ __forceinline__ void conv_frags(uint32_t zero, const uint32_t (&r)[6][6], uint32_t (&A)[12][4]) {
#pragma unroll
  for (int ch = LO; ch < HI; ch++) {
    const uint32_t sel = (ch & 1) ? 0x7632 : 0x5410;
    A[ch][0] = __byte_perm(r[0][ch >> 1], r[1][ch >> 1], sel);
    A[ch][1] = __byte_perm(r[2][ch >> 1], r[3][ch >> 1], sel);
    A[ch][2] = A[ch][1] ^ zero;
    A[ch][3] = __byte_perm(r[4][ch >> 1], r[5][ch >> 1], sel);
    rfence(A[ch]);
  }
}
__device__ __forceinline__ void hmma_acc(uint32_t (&v)[4], const uint32_t (&a)[4], const uint32_t* b) {
  asm volatile("mma.sync.aligned.m16n8k16.row.col.f32.bf16.bf16.f32 {%0,%1,%2,%3}, {%4,%5,%6,%7}, {%8,%9}, {%0,%1,%2,%3};"
               : "+r"(v[0]), "+r"(v[1]), "+r"(v[2]), "+r"(v[3])
               : "r"(a[0]), "r"(a[1]), "r"(a[2]), "r"(a[3]), "r"(b[0]), "r"(b[1]));
}
__device__ __forceinline__ void hmma_new(uint32_t (&a)[4], const uint32_t* b) {
  asm volatile("mma.sync.aligned.m16n8k16.row.col.f32.bf16.bf16.f32 {%0,%1,%2,%3}, {%0,%1,%2,%3}, {%4,%5}, {%6,%6,%6,%6};"
               : "+r"(a[0]), "+r"(a[1]), "+r"(a[2]), "+r"(a[3])
               : "r"(b[0]), "r"(b[1]), "f"(0.f));
}

#define EARLY 5
__device__ __forceinline__ void conv_send(bool local, const uint32_t (&pk)[12], uint32_t dst, uint32_t bar) {
  if (local) {
#pragma unroll
    for (int q = 0; q < 3; q++)
      asm volatile("st.shared.v4.b32 [%0], {%1,%2,%3,%4};" ::"r"(dst + q * 2048), "r"(pk[4 * q]), "r"(pk[4 * q + 1]), "r"(pk[4 * q + 2]), "r"(pk[4 * q + 3])
                   : "memory");
    asm volatile("{\n.reg .pred p;\nelect.sync _|p, 0xffffffff;\n@p mbarrier.arrive.shared::cta.b64 _, [%0];\n}\n" ::"r"(bar) : "memory");
  } else {
#pragma unroll
    for (int q = 0; q < 3; q++)
      asm volatile("st.async.weak.shared::cluster.mbarrier::complete_tx::bytes.v4.b32 [%0], {%1,%2,%3,%4}, [%5];" ::"r"(dst + q * 2048),
                   "r"(pk[4 * q]), "r"(pk[4 * q + 1]), "r"(pk[4 * q + 2]), "r"(pk[4 * q + 3]), "r"(bar)
                   : "memory");
  }
}
template <int S2, bool GATED>
__device__ __forceinline__ void conv_step(const ConvCtx& c, int s, uint32_t (&K)[12], uint32_t (&V)[12][4], const uint32_t (&B)[12][4],
                                          uint32_t (&A)[12][4]) {
  const int nx = ((s + 1) & 2) | (S2 ^ 1);
  uint32_t r[6][6], pk[12];
  const uint32_t a0 = c.a0 + nx * RAW_BYTES;
  if (GATED) NB_SYNC(NB_OPEN, 448);
  else NB_SYNC(NB_PLAN, 192);
  conv_ld4(a0, c.sb + OFF_RAW + nx * RAW_BYTES, c.v, r);
  if (GATED) PIN();
#pragma unroll
  for (int ch = 0; ch < 12; ch++) hmma_acc(V[11 - ch], A[11 - ch], &B[11 - ch][2]);
#pragma unroll
  for (int ch = 0; ch < 12 - EARLY; ch++) hmma_new(A[ch], &B[ch][0]);
  const uint32_t zero = GATED ? c.zero & clock_pin() : c.zero;
  if (GATED) NB_ARRIVE(NB_CLOSE, 256);
#pragma unroll
  for (int ch = 12 - EARLY; ch < 12; ch++) hmma_new(A[ch], &B[ch][0]);
  if (GATED) PIN();
  const bool local = (S2 ^ 1) == c.rank;
  const uint32_t off = local ? 0u : c.peer_off;
  const uint32_t dst = c.a_c + off + (nx >> 1) * C_BYTES;
  const uint32_t bar = c.sb + off + BAR_CFULL + 8 * (nx >> 1);
#pragma unroll
  for (int q = 0; q < 12; q++) {
    const int ch = q & ~1, h = 2 * (q & 1);
    pk[q] = h_add(K[q], pack_f16(__uint_as_float(V[ch][h + 1]), __uint_as_float(V[ch + 1][h])));
  }
#pragma unroll
  for (int q = 0; q < 12; q++) {
    const int ch = q & ~1, h = 2 * (q & 1);
    K[q] = pack_f16(__uint_as_float(V[ch][h]), __uint_as_float(V[ch + 1][h + 1]));
  }
  rfence(K);
  rfence(pk);
  PIN();
  conv_ld8<0, 4>(a0, r);
  if (GATED || s >= 3) conv_send(local, pk, dst, bar);
  conv_frags<8, 12>(zero, r, V);
  PIN();
  conv_ld8<4, 6>(a0, r);
  conv_frags<0, 8>(zero, r, V);
  PIN();
}

__device__ __forceinline__ void conv_role(ConvCtx c) {
  const int lane = laneid(), g = lane >> 2, t = lane & 3;
  const int u = (t >> 1) * 19 + 2 * (g + (t & 1));
  c.a0 = c.sb + OFF_RAW + u * 64 + ((c.v ^ (u >> 1)) & 3) * 16;
  c.a_c = c.sb + OFF_C + 6144 * c.rank + 512 * c.v + ((lane + 2 * c.v) & 31) * 16;
  uint32_t B[12][4];
  {
    const int dc = (g >> 1) & 1, ro = g >> 2, rk = t >> 1;
    const int i0 = (c.dir > 0 ? 4 * (g & 1) : 6 - 4 * (g & 1)) + rk - ro, j0 = 4 * (t & 1) - dc;
    const uint32_t base = c.sb + OFF_XRES + (i0 * 7 + j0) * 192;
    asm volatile("barrier.cluster.wait.aligned;" ::: "memory");
    mbar_wait(c.sb + BAR_W + 48, 0);
#pragma unroll
    for (int b = 0; b < 2; b++) {
      uint32_t w[4][6];
#pragma unroll
      for (int k = 0; k < 4; k++) {
        const int ok = (unsigned)(i0 + 2 * b * c.dir) < 7u && (unsigned)(j0 + k) < 7u;
#pragma unroll
        for (int q = 0; q < 6; q++) w[k][q] = 0;
        asm volatile(
            "{\n.reg .pred p;\nsetp.ne.s32 p, %8, 0;\n@p ld.shared.v4.b32 {%0,%1,%2,%3}, [%6];\n@p ld.shared.v2.b32 {%4,%5}, [%7];\n}\n"
            : "+r"(w[k][0]), "+r"(w[k][1]), "+r"(w[k][2]), "+r"(w[k][3]), "+r"(w[k][4]), "+r"(w[k][5])
            : "r"(base + (b * 14 * c.dir + k) * 192 + 128 * c.rank + 16 * c.v), "r"(base + (b * 14 * c.dir + k) * 192 + 64 + 32 * c.rank + 8 * c.v), "r"(ok)
            : "memory");
      }
#pragma unroll
      for (int q = 0; q < 6; q++) {
        B[2 * q][2 * b] = __byte_perm(w[0][q], w[1][q], 0x5410);
        B[2 * q][2 * b + 1] = __byte_perm(w[2][q], w[3][q], 0x5410);
        B[2 * q + 1][2 * b] = __shfl_xor_sync(0xffffffffu, __byte_perm(w[0][q], w[1][q], 0x7632), 4);
        B[2 * q + 1][2 * b + 1] = __shfl_xor_sync(0xffffffffu, __byte_perm(w[2][q], w[3][q], 0x7632), 4);
      }
    }
  }
  uint32_t K1[12], K2[12], V[12][4];
#pragma unroll
  for (int ch = 0; ch < 12; ch++)
    asm volatile("" : "=r"(K1[ch]), "=r"(K2[ch]), "=r"(V[ch][0]), "=r"(V[ch][1]), "=r"(V[ch][2]), "=r"(V[ch][3]));
  uint32_t A[12][4], r[6][6];
  mbar_wait(c.sb + BAR_RAW, 0);
  conv_ld8<0, 6>(c.a0, r);
  conv_ld4(c.a0, c.sb + OFF_RAW, c.v, r);
  conv_frags<0, 12>(c.zero, r, A);
  PIN();
  NB_ARRIVE(NB_CLOSE, 256);
#pragma unroll 1
  for (int s = 0; s < SIGMA; s += 2) {
    conv_step<0, false>(c, s, K1, V, B, A);
    conv_step<1, false>(c, s + 1, K2, A, B, V);
  }
#pragma unroll 1
  for (int s = SIGMA;; s += 2) {
    conv_step<0, true>(c, s, K1, V, B, A);
    if (s == NSTEP - 1) break;
    conv_step<1, true>(c, s + 1, K2, A, B, V);
  }
#pragma unroll 1
  for (int r = NSTEP - SIGMA - c.rank; r < NROUND - 1; r++) {
    NB_SYNC(NB_OPEN, 448);
    NB_ARRIVE(NB_CLOSE, 256);
  }
  NB_SYNC(NB_OPEN, 448);
}

struct TMaps { CUtensorMap m[2]; };

__global__ void __cluster_dims__(2, 1, 1) __launch_bounds__(512, 1)
convnext_kernel(const __grid_constant__ TMaps tms, const __nv_bfloat16* __restrict__ x, const __nv_bfloat16* __restrict__ dw,
                const __nv_bfloat16* __restrict__ w1, const __nv_bfloat16* __restrict__ w2, __nv_bfloat16* __restrict__ out,
                Scratch* scr, int zero) {
  extern __shared__ __align__(1024) uint8_t smem[];
  const uint32_t sb = (uint32_t)__cvta_generic_to_shared(smem);
  const int tid = threadIdx.x, lane = tid & 31;
  const int wid = __shfl_sync(0xffffffffu, tid >> 5, 0);
  const int rank = blockIdx.x & 1, cl = blockIdx.x >> 1;
  const int dir = (cl & 16) ? 1 : -1;
  const int c0 = (cl & 15) * 32, r0 = (cl >> 4) * 128 + (dir > 0 ? 0 : 126);
  const uint32_t peer_off = mapa(sb, rank ^ 1) - sb;

  if (wid == 12 && elect_one()) {
    mbar_init(sb + BAR_W + 48, 1);
#pragma unroll
    for (int i = 0; i < 4; i++) mbar_init(sb + BAR_RAW + 8 * i, 1);
    asm volatile("fence.mbarrier_init.release.cluster;" ::: "memory");
    mbar_expect(sb + BAR_W + 48, 49 * CH * 2);
    bulk_load(sb + OFF_XRES, dw, 49 * CH * 2, sb + BAR_W + 48);
#pragma unroll
    for (int i = 0; i < E0; i++) tma_raw(sb + OFF_RAW + i * RAW_BYTES, tms.m, rank, c0 / 2 - 2, r0 + dir * (2 * i - 3), sb + BAR_RAW + 8 * i);
  }
  if (wid == 14 && elect_one()) {
    asm volatile("cp.async.bulk.prefetch.L2.global [%0], 1152;" ::"l"(reinterpret_cast<const uint8_t*>(rank ? w2 : w1) + cl * 1152) : "memory");
    asm volatile("prefetch.tensormap [%0];" ::"l"(&tms.m[1]) : "memory");
#pragma unroll
    for (int i = 0; i < 3; i++) mbar_init(sb + BAR_W + 8 * i, 1);
#pragma unroll
    for (int i = 0; i < 2; i++) mbar_init(sb + BAR_CFULL + 8 * i, CCNT);
#pragma unroll
    for (int i = 0; i < 4; i++) mbar_init(sb + BAR_CEMPTY + 8 * i, 4);
#pragma unroll
    for (int i = 0; i < 2; i++) mbar_init(sb + BAR_XFULL + 8 * i, 1);
#pragma unroll
    for (int i = 0; i < 2; i++) mbar_expect(sb + BAR_CFULL + 8 * i, CTX);
    asm volatile("fence.mbarrier_init.release.cluster;" ::: "memory");
  }
  __syncwarp();
  asm volatile("barrier.cluster.arrive.relaxed.aligned;" ::: "memory");

  if (wid < 8) {
    if (blockIdx.x < 48) convert_tile(blockIdx.x, wid, reinterpret_cast<const uint4*>(w1), reinterpret_cast<const uint4*>(w2), sb, scr);
    MlpCtx m;
    m.sb = sb; m.wg = wid >> 2; m.warp = wid & 3; m.rank = rank; m.peer_off = peer_off; m.zero = zero;
    m.optr = reinterpret_cast<uint8_t*>(out) + ((size_t)(r0 + dir * (120 + 4 * m.wg + 2 * rank)) * IMG + c0 + 8 * m.warp) * (CH * 2);
    m.caddr = sb + OFF_C + m.wg * C_BYTES + (lane & 3) * 512 + ((m.warp * 8 + (lane >> 2) + 2 * (lane & 3)) & 31) * 16;
    m.xaddr = sb + OFF_XRES + m.wg * 12288 + m.warp * 1536 + ((lane >> 3) & 1) * 6144 + ((lane >> 4) * 4 + ((lane >> 2) & 1)) * 192 + (lane & 3) * 16;
    m.unscale = 0;
    asm volatile("setmaxnreg.inc.sync.aligned.u32 %0;" ::"n"(REG_MLP));
    const uint32_t bad = mlp_role(m);
    TC(scr, 3);
    if (bad) {
      asm volatile("cp.async.bulk.wait_group 0;" ::: "memory");
      mbar_wait(sb + BAR_W + 16, 0);
      __syncwarp();
      asm volatile("fence.proxy.async;" ::: "memory");
#pragma unroll 1
      for (int i = 0; i < 16; i++)
        if (bad >> i & 1)
          slow_tile(x, dw, w1, w2, out, r0 + dir * (8 * i + 4 * m.wg + 2 * rank), c0 + 8 * m.warp,
                    reinterpret_cast<float*>(smem + OFF_RAW + wid * 2048));
    }
  } else {
    ConvCtx c;
    c.sb = sb; c.rank = rank; c.v = wid - 8; c.c0 = c0; c.r0 = r0; c.dir = dir; c.zero = zero; c.tm = tms.m; c.scr = scr;
    c.peer_off = peer_off;
    c.xsrc = reinterpret_cast<const uint8_t*>(x) + ((size_t)(r0 + 2 * dir * rank) * IMG + c0) * (CH * 2);
    c.optr = reinterpret_cast<uint8_t*>(out) + ((size_t)(r0 + 2 * dir * rank) * IMG + c0) * (CH * 2);
    if (wid < 12) {
      asm volatile("setmaxnreg.inc.sync.aligned.u32 %0;" ::"n"(REG_CONV));
      conv_role(c);
    } else {
      asm volatile("setmaxnreg.dec.sync.aligned.u32 24;");
      if (wid == 15) TC(scr, 0);
      if (wid == 12) {
#pragma unroll 1
        for (int h = E0 - 4; h < 0; h++) raw_refill(c, h);
        prod_rows(c);
      } else if (wid == 15) {
        prod_checks(c);
      } else if (wid == 14) {
#pragma unroll 1
        for (int n = 0; n < (1 << 20); n++) {
          unsigned v;
          __nanosleep(n ? PSL : PS0);
          asm volatile("ld.acquire.gpu.global.u32 %0, [%1];" : "=r"(v) : "l"(&scr->done) : "memory");
          if (__shfl_sync(0xffffffffu, v, 0) >= 48) break;
        }
        TP(scr, 90);
        asm volatile("barrier.cluster.wait.aligned;" ::: "memory");
        asm volatile("fence.proxy.async.global;" ::: "memory");
        if (elect_one()) {
          mbar_expect(sb + BAR_W, 36864 + 768);
          mbar_expect(sb + BAR_W + 8, 110592);
          bulk_load(sb + OFF_NRM, scr->nrm, 768, sb + BAR_W);
        }
        __syncwarp();
#pragma unroll 1
        for (int i = 0; i < 8; i++) {
          if (elect_one()) bulk_load(sb + i * 18432, reinterpret_cast<const uint8_t*>(scr->w) + i * 18432, 18432, sb + BAR_W + (i < 2 ? 0 : 8));
          if (i >= PFIRST) __nanosleep(PACE);
        }
        if (elect_one() && atomicAdd(&scr->seen, 1u) == gridDim.x - 1) { scr->done = 0; scr->seen = 0; }
      } else if (wid == 13) {
        prod_tiles(c);
        __syncwarp();
        if (elect_one()) asm volatile("mbarrier.arrive.shared::cta.b64 _, [%0];" ::"r"(sb + BAR_W + 16) : "memory");
      }
    }
  }
}

typedef CUresult (*EncodeFn)(CUtensorMap*, CUtensorMapDataType, cuuint32_t, void*, const cuuint64_t*, const cuuint64_t*,
                             const cuuint32_t*, const cuuint32_t*, CUtensorMapInterleave, CUtensorMapSwizzle,
                             CUtensorMapL2promotion, CUtensorMapFloatOOBfill);

}

extern "C" void kernel_launch(void* const* d_in, const int* in_sizes, int n_in, void* d_out, int out_size) {
  const __nv_bfloat16* x = (const __nv_bfloat16*)d_in[0];
  const __nv_bfloat16* dw = (const __nv_bfloat16*)d_in[1];
  const __nv_bfloat16* w1 = (const __nv_bfloat16*)d_in[2];
  const __nv_bfloat16* w2 = (const __nv_bfloat16*)d_in[3];
  __nv_bfloat16* out = (__nv_bfloat16*)d_out;

  static EncodeFn encode = nullptr;
  static Scratch* scr = nullptr;
  if (!encode) {
    cudaDriverEntryPointQueryResult st;
    void* fn = nullptr;
    cudaGetDriverEntryPoint("cuTensorMapEncodeTiled", &fn, cudaEnableDefault, &st);
    encode = (EncodeFn)fn;
    cudaGetSymbolAddress((void**)&scr, g_scratch);
    cudaFuncSetAttribute(convnext_kernel, cudaFuncAttributeMaxDynamicSharedMemorySize, SMEM_BYTES);
  }
  TMaps tm;
  cuuint64_t dims[4] = {CH, IMG / 2, IMG, 2};
  cuuint64_t strides[3] = {CH * 4, (cuuint64_t)IMG * CH * 2, CH * 2};
  cuuint32_t es[4] = {1, 1, 1, 1};
  for (int i = 0; i < 2; i++) {
    cuuint32_t box[4] = {i ? 16u : 32u, 19, 2, 1};
    encode(&tm.m[i], CU_TENSOR_MAP_DATA_TYPE_BFLOAT16, 4, (void*)x, dims, strides, box, es, CU_TENSOR_MAP_INTERLEAVE_NONE,
           i ? CU_TENSOR_MAP_SWIZZLE_NONE : CU_TENSOR_MAP_SWIZZLE_64B, PROMO, CU_TENSOR_MAP_FLOAT_OOB_FILL_NONE);
  }
  convnext_kernel<<<128, 512, SMEM_BYTES>>>(tm, x, dw, w1, w2, out, scr, 0);
}
```

```cpp
#include <cuda_runtime.h>
#include <cuda_bf16.h>
#include <cuda.h>
#include <stdint.h>

#define PROMO CU_TENSOR_MAP_L2_PROMOTION_L2_128B
#define CTX 6144
#define CCNT 5
#define PSL 100
#define PS0 1000
#define E0 1
#define PACE 100
#define PFIRST 1
namespace {

constexpr int IMG = 512, CH = 96;
constexpr int NSTEP = 67;
constexpr int SIGMA = 8;
constexpr int NROUND = 68;

constexpr uint32_t OFF_W1 = 0;
constexpr uint32_t OFF_W2 = 73728;
constexpr uint32_t OFF_RAW = 147456;
constexpr uint32_t RAW_PA = 2560, RAW_PB = 1280;
constexpr uint32_t RAW_BYTES = 2 * RAW_PA + 2 * RAW_PB;
constexpr uint32_t RAW_TX = 2 * 38 * 96;
constexpr uint32_t OFF_XRES = OFF_RAW + 4 * RAW_BYTES;
constexpr uint32_t OFF_C = OFF_XRES + 2 * 12288;
constexpr uint32_t C_BYTES = 12288;
constexpr uint32_t OFF_BAR = OFF_C + 2 * C_BYTES;
constexpr uint32_t BAR_RAW = OFF_BAR;
constexpr uint32_t BAR_CFULL = OFF_BAR + 32;
constexpr uint32_t BAR_CEMPTY = OFF_BAR + 48;
constexpr uint32_t BAR_XFULL = OFF_BAR + 80;
constexpr uint32_t BAR_W = OFF_BAR + 96;
constexpr uint32_t OFF_NRM = OFF_XRES + 9472;
constexpr uint32_t SMEM_BYTES = OFF_BAR + 160;

struct Scratch {
  uint4 w[2 * 73728 / 16];
  uint4 nrm[48];
  unsigned done, seen;
};
__device__ Scratch g_scratch;

constexpr float GELU_A = 0.32918364f;
constexpr uint32_t GELU_K2 = 0x40d940d9u;

constexpr int NB_CLOSE = 1, NB_SEC = 6  , NB_OPEN = 3, NB_PROD = 2, NB_PLAN = 4, NB_PREP = 5, NB_WG = 8  ;
#define REG_MLP 144
constexpr int REG_CONV = 488 - 2 * REG_MLP;

#define WG_FENCE() asm volatile("wgmma.fence.sync.aligned;" ::: "memory")
#define WG_COMMIT() asm volatile("wgmma.commit_group.sync.aligned;" ::: "memory")
#define WG_WAIT0() asm volatile("wgmma.wait_group.sync.aligned 0;" ::: "memory")
#define WG_WAIT1() asm volatile("wgmma.wait_group.sync.aligned 1;" ::: "memory")
#define PIN() asm volatile("pmevent 0;" ::: "memory")
#define NB_SYNC(id, n) asm volatile("bar.sync %0, %1;" ::"n"(id), "n"(n) : "memory")
#define NB_ARRIVE(id, n) asm volatile("bar.arrive %0, %1;" ::"n"(id), "n"(n) : "memory")

#define TC(scr, k)
#define TP(scr, k)

#define R24(c, d)                                                                                        \
  c(d[0]), c(d[1]), c(d[2]), c(d[3]), c(d[4]), c(d[5]), c(d[6]), c(d[7]), c(d[8]), c(d[9]), c(d[10]),    \
      c(d[11]), c(d[12]), c(d[13]), c(d[14]), c(d[15]), c(d[16]), c(d[17]), c(d[18]), c(d[19]), c(d[20]), \
      c(d[21]), c(d[22]), c(d[23])
#define WG_TXT(sd)                                                                             \
  "wgmma.mma_async.sync.aligned.m64n96k16.f16.f16.f16 "                                        \
  "{%0,%1,%2,%3,%4,%5,%6,%7,%8,%9,%10,%11,%12,%13,%14,%15,%16,%17,%18,%19,%20,%21,%22,%23}, " \
  "{%24,%25,%26,%27}, %28, " sd ", 1, 1, 1;\n"

__device__ __forceinline__ void wg_acc(uint32_t (&d)[24], const uint32_t* a, uint64_t db) {
  asm volatile(WG_TXT("1") : R24("+r", d) : "r"(a[0]), "r"(a[1]), "r"(a[2]), "r"(a[3]), "l"(db));
}
__device__ __forceinline__ void wg_init(uint32_t (&d)[24], const uint32_t* a, uint64_t db) {
  asm volatile(WG_TXT("0") : R24("=r", d) : "r"(a[0]), "r"(a[1]), "r"(a[2]), "r"(a[3]), "l"(db));
}
template <int N>
__device__ __forceinline__ void rfence(uint32_t (&d)[N]) {
#pragma unroll
  for (int i = 0; i < N; i++) asm volatile("" : "+r"(d[i])::"memory");
}
template <bool INIT, int KSTRIDE>
__device__ __forceinline__ void gemm6(uint32_t (&d)[24], const uint32_t (&a)[24], uint64_t db) {
#pragma unroll
  for (int k = 0; k < 6; k++) {
    if (INIT && k == 0) wg_init(d, &a[0], db);
    else wg_acc(d, &a[4 * k], db + k * KSTRIDE);
  }
  WG_COMMIT();
}

__device__ __forceinline__ void mbar_init(uint32_t bar, uint32_t cnt) {
  asm volatile("mbarrier.init.shared::cta.b64 [%0], %1;" ::"r"(bar), "r"(cnt) : "memory");
}
__device__ __forceinline__ void mbar_expect(uint32_t bar, uint32_t bytes) {
  asm volatile("mbarrier.arrive.expect_tx.shared::cta.b64 _, [%0], %1;" ::"r"(bar), "r"(bytes) : "memory");
}
__device__ __forceinline__ void mbar_arrive_cluster(uint32_t bar) {
  asm volatile("mbarrier.arrive.shared::cluster.b64 _, [%0];" ::"r"(bar) : "memory");
}
__device__ __forceinline__ bool mbar_try(uint32_t bar, uint32_t parity) {
  uint32_t ok;
  asm volatile(
      "{\n.reg .pred p;\nmbarrier.try_wait.parity.shared::cta.b64 p, [%1], %2;\nselp.u32 %0, 1, 0, p;\n}\n"
      : "=r"(ok)
      : "r"(bar), "r"(parity)
      : "memory");
  return ok;
}
__device__ __forceinline__ bool mbar_test(uint32_t bar, uint32_t parity) {
  uint32_t ok;
  asm volatile(
      "{\n.reg .pred p;\nmbarrier.test_wait.parity.shared::cta.b64 p, [%1], %2;\nselp.u32 %0, 1, 0, p;\n}\n"
      : "=r"(ok)
      : "r"(bar), "r"(parity)
      : "memory");
  return ok;
}
__device__ __forceinline__ void mbar_wait(uint32_t bar, uint32_t parity) {
  if (__builtin_expect(mbar_try(bar, parity), 1)) return;
#pragma unroll 1
  for (uint32_t n = 0; n < (1u << 16) && !mbar_try(bar, parity); n++) {}
}
__device__ __forceinline__ uint32_t mapa(uint32_t addr, uint32_t rank) {
  uint32_t r;
  asm("mapa.shared::cluster.u32 %0, %1, %2;" : "=r"(r) : "r"(addr), "r"(rank));
  return r;
}
__device__ __forceinline__ void tma_raw(uint32_t dst, const CUtensorMap* tm, int rank, int w2, int h, uint32_t bar) {
  mbar_expect(bar, RAW_TX);
#pragma unroll
  for (int k = 0; k < 4; k++) {
    const int e = k & 1;
    asm volatile(
        "cp.async.bulk.tensor.4d.shared::cluster.global.mbarrier::complete_tx::bytes [%0], [%1, {%2, %3, %4, %5}], [%6];"
        ::"r"(dst + (k < 2 ? e * RAW_PA : 2 * RAW_PA + e * RAW_PB)), "l"(tm + (k >> 1)), "r"(k < 2 ? 64 * rank : 32 + 16 * rank), "r"(w2 + e),
        "r"(h), "r"(1 - e), "r"(bar)
        : "memory");
  }
}
__device__ __forceinline__ void bulk_load(uint32_t dst, const void* src, uint32_t bytes, uint32_t bar) {
  asm volatile("cp.async.bulk.shared::cluster.global.mbarrier::complete_tx::bytes [%0], [%1], %2, [%3];" ::"r"(dst),
               "l"(src), "r"(bytes), "r"(bar)
               : "memory");
}
__device__ __forceinline__ void bulk_load_last(uint32_t dst, const void* src, uint32_t bytes, uint32_t bar) {
  asm volatile(
      "{\n.reg .b64 pol;\ncreatepolicy.fractional.L2::evict_first.b64 pol, 1.0;\n"
      "cp.async.bulk.shared::cluster.global.mbarrier::complete_tx::bytes.L2::cache_hint [%0], [%1], %2, [%3], pol;\n}\n" ::"r"(dst),
      "l"(src), "r"(bytes), "r"(bar)
      : "memory");
}
__device__ __forceinline__ uint32_t pack_bf16(float lo, float hi) {
  uint32_t r;
  asm("cvt.rn.bf16x2.f32 %0, %1, %2;" : "=r"(r) : "f"(hi), "f"(lo));
  return r;
}
__device__ __forceinline__ uint32_t pack_f16(float lo, float hi) {
  uint32_t r;
  asm("cvt.rn.f16x2.f32 %0, %1, %2;" : "=r"(r) : "f"(hi), "f"(lo));
  return r;
}
__device__ __forceinline__ float bf_lo(uint32_t v) { return __uint_as_float(v << 16); }
__device__ __forceinline__ float bf_hi(uint32_t v) { return __uint_as_float(v & 0xffff0000u); }
__device__ __forceinline__ uint32_t bf_add(uint32_t a, uint32_t b) {
  uint32_t r;
  asm("add.rn.bf16x2 %0, %1, %2;" : "=r"(r) : "r"(a), "r"(b));
  return r;
}
__device__ __forceinline__ uint32_t bf_mul(uint32_t a, uint32_t b) {
  uint32_t r;
  asm("mul.rn.bf16x2 %0, %1, %2;" : "=r"(r) : "r"(a), "r"(b));
  return r;
}
__device__ __forceinline__ uint32_t bf_fma(uint32_t a, uint32_t b, uint32_t c) {
  uint32_t r;
  asm("fma.rn.bf16x2 %0, %1, %2, %3;" : "=r"(r) : "r"(a), "r"(b), "r"(c));
  return r;
}

__device__ __forceinline__ uint32_t h_add(uint32_t a, uint32_t b) {
  uint32_t r;
  asm("add.rn.f16x2 %0, %1, %2;" : "=r"(r) : "r"(a), "r"(b));
  return r;
}
__device__ __forceinline__ uint32_t h_mul(uint32_t a, uint32_t b) {
  uint32_t r;
  asm("mul.rn.f16x2 %0, %1, %2;" : "=r"(r) : "r"(a), "r"(b));
  return r;
}
__device__ __forceinline__ uint32_t h_fma(uint32_t a, uint32_t b, uint32_t c) {
  uint32_t r;
  asm("fma.rn.f16x2 %0, %1, %2, %3;" : "=r"(r) : "r"(a), "r"(b), "r"(c));
  return r;
}
__device__ __forceinline__ float h_sum(uint32_t v) {
  float lo, hi;
  asm("{\n.reg .b16 l, h;\nmov.b32 {l, h}, %2;\ncvt.f32.f16 %0, l;\ncvt.f32.f16 %1, h;\n}\n" : "=f"(lo), "=f"(hi) : "r"(v));
  return lo + hi;
}
__device__ __forceinline__ void lds128(uint32_t (&v)[4], uint32_t a) {
  asm volatile("ld.shared.v4.b32 {%0,%1,%2,%3}, [%4];" : "=r"(v[0]), "=r"(v[1]), "=r"(v[2]), "=r"(v[3]) : "r"(a) : "memory");
}

template <int LO, int HI>
__device__ __forceinline__ void gelu(uint32_t (&o)[24], const uint32_t (&d)[24]) {
#pragma unroll
  for (int qq = LO; qq < HI; qq++) {
    const int q = (qq + 4) % 24;
    uint32_t t, u;
    asm("fma.rn.f16x2 %0, %1, %1, %2;" : "=r"(t) : "r"(d[q]), "r"(GELU_K2));
    asm("mul.rn.f16x2 %0, %1, %2;" : "=r"(u) : "r"(d[q]), "r"(t));
    asm("tanh.approx.f16x2 %0, %1;" : "=r"(t) : "r"(u));
    asm("fma.rn.f16x2 %0, %1, %2, %1;" : "=r"(o[q]) : "r"(d[q]), "r"(t));
  }
}

__device__ __forceinline__ uint32_t laneid() {
  uint32_t l;
  asm volatile("mov.u32 %0, %%laneid;" : "=r"(l));
  return l;
}

__device__ __forceinline__ bool elect_one() {
  uint32_t p;
  asm volatile("{\n.reg .pred p;\nelect.sync _|p, 0xffffffff;\nselp.u32 %0, 1, 0, p;\n}\n" : "=r"(p));
  return p;
}

__device__ __forceinline__ uint32_t clock_pin() {
  uint32_t t;
  asm volatile("mov.u32 %0, %%clock;" : "=r"(t)::"memory");
  return t;
}

struct MlpCtx {
  uint32_t sb;
  uint32_t caddr;
  uint32_t xaddr;
  uint32_t unscale;
  uint32_t peer_off;
  int wg, warp, rank, zero;
  uint8_t* optr;
};

__device__ __forceinline__ void ln_wait(const MlpCtx& m, int i) { mbar_wait(m.sb + BAR_CFULL + 8 * m.wg, i & 1); }
__device__ __forceinline__ void ln_load(const MlpCtx& m, uint32_t (&c)[24]) {
#pragma unroll
  for (int p = 0; p < 6; p++)
    asm volatile("ld.shared.v4.b32 {%0,%1,%2,%3}, [%4];"
                 : "=r"(c[4 * p]), "=r"(c[4 * p + 1]), "=r"(c[4 * p + 2]), "=r"(c[4 * p + 3])
                 : "r"(m.caddr + p * 2048)
                 : "memory");
}
__device__ __forceinline__ void ln_shfl(float (&st)[8], int mask) {
#pragma unroll
  for (int k = 0; k < 4; k++) st[4 + k] = __shfl_xor_sync(0xffffffffu, st[k], mask);
}
__device__ __forceinline__ void ln_fold(float (&st)[8]) {
#pragma unroll
  for (int k = 0; k < 4; k++) st[k] += st[4 + k];
}
__device__ __forceinline__ void ln_sums(const uint32_t (&c)[24], float (&st)[8]) {
#pragma unroll
  for (int r = 0; r < 2; r++) {
    uint32_t s0 = h_add(c[r], c[r + 2]), s1 = h_add(c[r + 4], c[r + 6]), s2 = h_add(c[r + 8], c[r + 10]);
    uint32_t s3 = h_add(c[r + 12], c[r + 14]), s4 = h_add(c[r + 16], c[r + 18]), s5 = h_add(c[r + 20], c[r + 22]);
    s0 = h_add(s0, s1); s2 = h_add(s2, s3); s4 = h_add(s4, s5);
    st[r] = h_sum(h_add(h_add(s0, s2), s4));
    uint32_t q0 = h_mul(c[r], c[r]), q1 = h_mul(c[r + 2], c[r + 2]);
#pragma unroll
    for (int p = 2; p < 12; p += 2) {
      q0 = h_fma(c[2 * p + r], c[2 * p + r], q0);
      q1 = h_fma(c[2 * p + 2 + r], c[2 * p + 2 + r], q1);
    }
    st[2 + r] = h_sum(h_add(q0, q1));
  }
}
__device__ __forceinline__ void ln_release(const MlpCtx& m) {
  const uint32_t e = m.sb + BAR_CEMPTY + 8 * (2 * m.rank + m.wg);
  asm volatile(
      "{\n.reg .pred p, q;\nelect.sync _|p, 0xffffffff;\nsetp.eq.and.s32 q, %3, 0, p;\n"
      "@q mbarrier.arrive.expect_tx.shared::cta.b64 _, [%0], %4;\n"
      "@p mbarrier.arrive.shared::cluster.b64 _, [%1];\n"
      "@p mbarrier.arrive.shared::cluster.b64 _, [%2];\n}\n" ::"r"(m.sb + BAR_CFULL + 8 * m.wg),
      "r"(e), "r"(e + m.peer_off), "r"(m.warp), "n"(CTX)
      : "memory");
}
__device__ __forceinline__ bool ln_stats(float (&st)[8]) {
  bool ok = true;
#pragma unroll
  for (int r = 0; r < 2; r++) {
    const float nm = (st[r] + st[4 + r]) * (-1.0f / 96.0f);
    const float e2 = fmaf(st[2 + r] + st[6 + r], 1.0f / 96.0f, 1e-5f);
    float rs;
    asm("rsqrt.approx.ftz.f32 %0, %1;" : "=f"(rs) : "f"(fmaf(-nm, nm, e2)));
    ok = ok && (rs * rs * e2 <= 17.0f) && (e2 >= 1.001e-5f);
    const float rr = rs * GELU_A, dd = rr * nm;
    st[r] = __uint_as_float(pack_f16(rr, rr));
    st[2 + r] = __uint_as_float(pack_f16(dd, dd));
  }
  return ok;
}
__device__ __forceinline__ void ln_restat(bool ok, const uint32_t (&c)[24], float (&st)[8], uint32_t& bad, uint32_t bit,
                                          uint32_t zero) {
  if (__builtin_expect(__any_sync(0xffffffffu, !ok), 0)) {
#pragma unroll
    for (int r = 0; r < 2; r++) {
      float nm = 0.f, var = 0.f;
#pragma unroll
      for (int p = 0; p < 12; p++) {
        nm += h_sum(c[2 * p + r] ^ zero);
        if (p % 3 == 2) { asm volatile("" : "+f"(nm)); PIN(); }
      }
      nm += __shfl_xor_sync(0xffffffffu, nm, 1);
      nm += __shfl_xor_sync(0xffffffffu, nm, 2);
      nm *= -1.0f / 96.0f;
#pragma unroll
      for (int p = 0; p < 12; p++) {
        float lo, hi;
        asm volatile("{\n.reg .b16 l, h;\nmov.b32 {l, h}, %2;\ncvt.f32.f16 %0, l;\ncvt.f32.f16 %1, h;\n}\n" : "=f"(lo), "=f"(hi) : "r"(c[2 * p + r]));
        var = fmaf(lo + nm, lo + nm, fmaf(hi + nm, hi + nm, var));
        if (p % 3 == 2) { asm volatile("" : "+f"(var)); PIN(); }
      }
      var += __shfl_xor_sync(0xffffffffu, var, 1);
      var += __shfl_xor_sync(0xffffffffu, var, 2);
      const float rr = rsqrtf(fmaf(var, 1.0f / 96.0f, 1e-5f)) * GELU_A;
      st[r] = __uint_as_float(pack_f16(rr, rr));
      const float dd = 0.5f * h_sum(__float_as_uint(st[r])) * nm;
      st[2 + r] = __uint_as_float(pack_f16(dd, dd));
      if (!(rr >= 0x1p-14f && fabsf(dd) <= 16.0f && var >= 1e-8f)) bad |= bit;
    }
  }
}
__device__ __forceinline__ void ln_apply(uint32_t (&a)[24], const uint32_t (&c)[24], const float (&st)[8]) {
#pragma unroll
  for (int p = 0; p < 24; p++) {
    a[p] = h_fma(c[p], __float_as_uint(st[p & 1]), __float_as_uint(st[2 + (p & 1)]));
  }
}

__device__ __noinline__ void slow_tile(const __nv_bfloat16* x, const __nv_bfloat16* dw, const __nv_bfloat16* w1,
                                       const __nv_bfloat16* w2, __nv_bfloat16* out, int row0, int col0, float* buf) {
  const int lane = threadIdx.x & 31;
  for (int px = 0; px < 16; px++) {
    const int row = row0 + (px >> 3), col = col0 + (px & 7);
    float c[3] = {0.f, 0.f, 0.f};
    for (int i = 0; i < 7; i++)
      for (int j = 0; j < 7; j++) {
        const int rr = row + i - 3, cc = col + j - 3;
        if (rr < 0 || rr >= IMG || cc < 0 || cc >= IMG) continue;
        for (int k = 0; k < 3; k++)
          c[k] = fmaf(__bfloat162float(x[((size_t)rr * IMG + cc) * CH + lane + 32 * k]), __bfloat162float(dw[(i * 7 + j) * CH + lane + 32 * k]), c[k]);
      }
    float mean = (c[0] + c[1] + c[2]) * (1.0f / 96.0f);
    for (int o = 16; o; o >>= 1) mean += __shfl_xor_sync(0xffffffffu, mean, o);
    float var = 0.f;
    for (int k = 0; k < 3; k++) { c[k] -= mean; var = fmaf(c[k] * (1.0f / 96.0f), c[k], var); }
    for (int o = 16; o; o >>= 1) var += __shfl_xor_sync(0xffffffffu, var, o);
    const float rs = 1.0f / sqrtf(var + 1e-5f);
    __syncwarp();
    for (int k = 0; k < 3; k++) buf[lane + 32 * k] = c[k] * rs;
    __syncwarp();
    for (int n = lane; n < 4 * CH; n += 32) {
      float y = 0.f;
      for (int k = 0; k < CH; k++) y = fmaf(buf[k], __bfloat162float(w1[k * 4 * CH + n]), y);
      buf[CH + n] = 0.5f * y * (1.0f + tanhf(0.7978845608f * (y + 0.044715f * y * y * y)));
    }
    __syncwarp();
    for (int n = lane; n < CH; n += 32) {
      float o = 0.f;
      for (int k = 0; k < 4 * CH; k++) o = fmaf(buf[CH + k], __bfloat162float(w2[k * CH + n]), o);
      const size_t idx = ((size_t)row * IMG + col) * CH + n;
      out[idx] = __float2bfloat16(__bfloat162float(x[idx]) + o);
    }
  }
}

__device__ __forceinline__ void x_load(const MlpCtx& m, uint32_t (&x)[24]) {
#pragma unroll
  for (int k = 0; k < 6; k++)
    asm volatile("ld.shared.v4.b32 {%0,%1,%2,%3}, [%4];"
                 : "=r"(x[4 * k]), "=r"(x[4 * k + 1]), "=r"(x[4 * k + 2]), "=r"(x[4 * k + 3])
                 : "r"(m.xaddr + (k / 3) * 384 + (k % 3) * 64)
                 : "memory");
}
template <bool DIRECT>
__device__ __forceinline__ void epilogue(const MlpCtx& m, const uint32_t (&d)[24], uint32_t (&x)[24]) {
  uint8_t* o = nullptr;
  if (DIRECT) {
    const uint32_t lane = laneid();
    o = m.optr + ((lane >> 3) & 1) * (IMG * CH * 2) + ((lane >> 4) * 4 + ((lane >> 2) & 1)) * 192 + (lane & 3) * 16;
  }
#pragma unroll
  for (int k = 0; k < 6; k++) {
    const int r = k / 3, q = k % 3;
    uint32_t* y = &x[4 * k];
#pragma unroll
    for (int j = 0; j < 4; j++) {
      uint32_t v = d[2 * (4 * q + j) + r];
      float lo, hi;
      asm("{\n.reg .b16 l, h;\nmov.b32 {l, h}, %2;\ncvt.f32.f16 %0, l;\ncvt.f32.f16 %1, h;\n}\n" : "=f"(lo), "=f"(hi) : "r"(v));
      asm("fma.rn.bf16x2 %0, %1, %2, %0;" : "+r"(y[j]) : "r"(pack_bf16(lo, hi)), "r"(m.unscale));
    }
    if (DIRECT)
      asm volatile("st.global.v4.b32 [%0], {%1,%2,%3,%4};" ::"l"(o + r * 384 + q * 64), "r"(y[0]), "r"(y[1]), "r"(y[2]), "r"(y[3]) : "memory");
    else
      asm volatile("st.shared.v4.b32 [%0], {%1,%2,%3,%4};" ::"r"(m.xaddr + r * 384 + q * 64), "r"(y[0]), "r"(y[1]), "r"(y[2]), "r"(y[3])
                   : "memory");
  }
}

#define FSET 3
template <int J> constexpr bool goes_first = J == FSET || J == ((FSET + 1) & 3);
template <int J> __device__ __forceinline__ void tok_wait() {
  if (goes_first<J>) NB_SYNC(NB_CLOSE, 256);
  else NB_SYNC(NB_SEC + (J & 1), 256);
}
template <int J, bool PROD = true> __device__ __forceinline__ void tok_next() {
  if (goes_first<J>) NB_ARRIVE(NB_SEC + (J & 1), 256);
  if (J == 0 && PROD) NB_ARRIVE(NB_PROD, 160);
}
__device__ __forceinline__ void tok_pass() { NB_ARRIVE(NB_OPEN, 448); }
template <int J> __device__ __forceinline__ void tok_idle() { tok_wait<J>(); tok_next<J, false>(); tok_pass(); }

constexpr uint64_t CHK = 1152;

__device__ __forceinline__ float warp_sumsq(const uint32_t (&q)[4]) {
  const uint32_t t = bf_add(bf_add(q[0], q[1]), bf_add(q[2], q[3]));
  float f = bf_lo(t) + bf_hi(t);
#pragma unroll
  for (int o = 16; o; o >>= 1) f += __shfl_xor_sync(0xffffffffu, f, o);
  return f;
}
__device__ __forceinline__ int norm_exp(float f) { return (((int)(__float_as_uint(f * 1.5f) >> 23) - 127) >> 1) + 1; }
__device__ __forceinline__ int scale_exp(int e1, int e2) { return min(11 - e1 - e2, 14 - e2); }

__device__ __forceinline__ void convert_tile(int t, int k, const uint4* w1, const uint4* w2, uint32_t st, Scratch* scr) {
  const int lane = threadIdx.x & 31, k7 = lane & 7;
  const int j = t / 6, ks = t % 6, e = ks % 3, t4 = k7 >> 1;
  const uint4* src = t < 24 ? w1 + ((e < 2 ? 64 * (ks / 3) + 8 * t4 + 4 * e : 32 + 16 * (ks / 3) + 4 * t4) + (k7 & 1)) * 48 + j * 12 + (lane >> 3)
                            : w2 + (t - 24) * 192 + (lane >> 2) * 12 + (lane & 3);
  src += (k / 3) * 96 + (k % 3) * 4;
  if (k >= 6) src = (k == 6 ? w1 : w2) + lane * 145;
  const uint4 v = __ldg(src);
  const uint32_t w[4] = {v.x, v.y, v.z, v.w};
  const uint32_t q[4] = {bf_mul(v.x, v.x), bf_mul(v.y, v.y), bf_mul(v.z, v.z), bf_mul(v.w, v.w)};
  asm volatile("st.shared.f32 [%0], %1;" ::"r"(st + 3088 + 4 * k), "f"(warp_sumsq(q)) : "memory");
  NB_SYNC(NB_PREP, 256);
  uint32_t a[4], b[4], o[4];
  lds128(a, st + 3088);
  lds128(b, st + 3104);
  const int s = max(-64, min(64, scale_exp(norm_exp(144.f * __uint_as_float(b[2])), norm_exp(144.f * __uint_as_float(b[3]))) - 3));
  const uint32_t dst = st + k7 * 16 + (lane >> 3) * 256 + (k / 3) * 128 + (k % 3) * 1024;
  if (k >= 6) {
    const float f = ((__uint_as_float(a[0]) + __uint_as_float(a[1])) + (__uint_as_float(a[2]) + __uint_as_float(a[3]))) +
                    (__uint_as_float(b[0]) + __uint_as_float(b[1]));
    asm volatile("st.shared.v2.b32 [%0], {%1,%2};" ::"r"(st + 3072), "r"(__float_as_uint(f)), "r"(s) : "memory");
  } else if (t < 24) {
#pragma unroll
    for (int i = 0; i < 4; i++) o[i] = pack_f16(bf_lo(w[i]), bf_hi(w[i]));
    asm volatile("st.shared.v4.b32 [%0], {%1,%2,%3,%4};" ::"r"(dst), "r"(o[0]), "r"(o[1]), "r"(o[2]), "r"(o[3]) : "memory");
  } else {
    constexpr float F = 0.5f / GELU_A, FHI = 1.515625f;
    const float p2 = __uint_as_float((uint32_t)(127 + s - 56) << 23);
    const uint32_t hi = pack_bf16(FHI * 0x1p-56f, FHI * 0x1p-56f), lo = pack_bf16((F - FHI) * 0x1p-56f, (F - FHI) * 0x1p-56f);
    const uint32_t pw = pack_bf16(p2, p2);
#pragma unroll
    for (int i = 0; i < 4; i++) {
      const uint32_t ws = bf_mul(w[i], pw), u = bf_fma(ws, hi, bf_mul(ws, lo));
      o[i] = (u & 0x7fff7fffu) * 7u + u;
    }
    asm volatile("stmatrix.sync.aligned.m8n8.x4.shared.b16 [%0], {%1,%2,%3,%4};" ::"r"(dst), "r"(o[0]), "r"(o[1]), "r"(o[2]), "r"(o[3])
                 : "memory");
  }
  asm volatile("fence.proxy.async.shared::cta;" ::: "memory");
  NB_SYNC(NB_PREP, 256);
  if (k == 0 && elect_one()) {
    asm volatile("cp.async.bulk.global.shared::cta.bulk_group [%0], [%1], 3072;" ::"l"(scr->w + t * 192), "r"(st) : "memory");
    asm volatile("cp.async.bulk.global.shared::cta.bulk_group [%0], [%1], 16;" ::"l"(scr->nrm + t), "r"(st + 3072) : "memory");
    asm volatile("cp.async.bulk.commit_group;" ::: "memory");
    asm volatile("cp.async.bulk.wait_group 0;" ::: "memory");
    asm volatile("red.relaxed.gpu.global.add.u32 [%0], 1;" ::"l"(&scr->done) : "memory");
  }
}

__device__ __forceinline__ uint32_t mlp_role(const MlpCtx& m0) {
  MlpCtx m = m0;
  uint32_t bad = 0;
  asm volatile("barrier.cluster.wait.aligned;" ::: "memory");
  if ((m.sb & 0x3FFFF) != 1024) bad = 0xffffu;
  constexpr uint64_t dW1 = (uint64_t)((1024 + OFF_W1) >> 4) | ((uint64_t)8 << 16) | ((uint64_t)16 << 32);
  constexpr uint64_t dW2 = dW1 + (OFF_W2 >> 4);
  uint32_t A1[24], g[24], d[24], cn[24], D2[24];
  float st[8];
  if (m.wg & m.rank) tok_idle<3>();
  else if (m.wg) tok_idle<0>();
  else if (m.rank) tok_idle<1>();
  ln_wait(m, 0);
  ln_load(m, cn);
  ln_sums(cn, st);
  ln_shfl(st, 1);
  ln_release(m);
  ln_fold(st);
  ln_shfl(st, 2);
  ln_restat(ln_stats(st), cn, st, bad, 1, m.zero);
  ln_apply(A1, cn, st);
  {
    const int lane = threadIdx.x & 31;
    mbar_wait(m.sb + BAR_W, 0);
    float n1, n2;
    int s;
    asm volatile("ld.shared.b32 %0, [%1];" : "=r"(s) : "r"(m.sb + OFF_NRM + 4) : "memory");
    asm volatile("ld.shared.f32 %0, [%1];" : "=f"(n1) : "r"(m.sb + OFF_NRM + 16 * min(lane, 23)) : "memory");
    asm volatile("ld.shared.f32 %0, [%1];" : "=f"(n2) : "r"(m.sb + OFF_NRM + 384 + 16 * min(lane, 23)) : "memory");
    if (lane >= 24) n1 = n2 = 0.f;
#pragma unroll
    for (int o = 16; o; o >>= 1) {
      n1 += __shfl_xor_sync(0xffffffffu, n1, o);
      n2 += __shfl_xor_sync(0xffffffffu, n2, o);
    }
    const int e1 = norm_exp(n1), e2 = norm_exp(n2), smax = scale_exp(e1, e2);
    if (e1 > 12 || e1 < -5 || e2 > 50 || e2 < -50 || s > smax || s < smax - 7) bad = 0xffffu;
    m.unscale = __shfl_sync(0xffffffffu, ((uint32_t)(127 - s) << 7) * 0x10001u, 0);
  }
  if (m.wg & m.rank) tok_idle<0>();
  if (m.wg) tok_idle<1>();
  {
    uint32_t d0[24];
    WG_FENCE();
    tok_wait<2>();
    tok_next<2>();
    gemm6<true, 192>(d0, A1, dW1);
    tok_pass(); PIN();
    WG_WAIT0(); rfence(d0);
    WG_FENCE();
    tok_wait<3>();
    tok_next<3>();
    gemm6<true, 192>(d, A1, dW1 + CHK);
    tok_pass(); PIN();
    gelu<0, 24>(g, d0);
    PIN();
    mbar_wait(m.sb + BAR_W + 8, 0);
    ln_wait(m, 1);
    WG_WAIT0(); rfence(d);
  }
#define G2(INIT, a, j)                      \
  WG_FENCE();                               \
  tok_wait<j>();                            \
  gemm6<INIT, 192>(D2, a, dW2 + (j) * CHK); \
  tok_next<j>(); PIN();
#define G1(dst, j, P)                       \
  P(); WG_WAIT0(); rfence(D2);              \
  WG_FENCE();                               \
  gemm6<true, 192>(dst, A1, dW1 + (j) * CHK); \
  tok_pass(); P();
#define ROUND_END(dst, j)                   \
  PIN(); WG_WAIT0(); rfence(dst);
#define GA 11
#define GB 12
#define GC 13
#define GD 11
#pragma unroll 1
  for (int i = 0;; i++) {
    uint32_t g1[24], d2[24], g2[24], d3[24], g3[24], d0[24];
    ln_load(m, cn);
    PIN();
    G2(true, g, 0)
    gelu<0, GA>(g1, d);
    G1(d2, 2, PIN)
    ln_sums(cn, st);
    gelu<GA, 24>(g1, d);
    PIN();
    ln_shfl(st, 1);
    ROUND_END(d2, 0)

    G2(false, g1, 1)
    ln_fold(st);
    gelu<0, GB>(g2, d2);
    PIN();
    ln_shfl(st, 2);
    G1(d3, 3, PIN)
    const bool ok = ln_stats(st);
    gelu<GB, 24>(g2, d2);
    PIN();
    ln_restat(ok, cn, st, bad, 2u << i, m.zero);
    ROUND_END(d3, 1)

    if (i == 15) {
      G2(false, g2, 2)
      tok_pass();
      gelu<0, 16>(g3, d3);
      PIN();
      x_load(m, cn);
      ROUND_END(D2, 2)
      WG_FENCE();
      tok_wait<3>();
#pragma unroll
      for (int k = 1; k < 5; k++) wg_acc(D2, &g3[4 * k], dW2 + 3 * CHK + k * 192);
      WG_COMMIT();
      tok_next<3>();
      tok_pass();
      PIN();
      gelu<16, 24>(g3, d3);
      ROUND_END(D2, 2)
      WG_FENCE();
      wg_acc(D2, &g3[20], dW2 + 3 * CHK + 5 * 192);
      wg_acc(D2, &g3[0], dW2 + 3 * CHK);
      WG_COMMIT();
      WG_WAIT0(); rfence(D2);
      epilogue<true>(m, D2, cn);
      break;
    }
    G2(false, g2, 2)
    ln_apply(A1, cn, st);
    PIN();
    gelu<0, GC>(g3, d3);
    G1(d0, 0, PIN)
    gelu<GC, 24>(g3, d3);
    PIN();
    x_load(m, cn);
    ROUND_END(d0, 2)

    G2(false, g3, 3)
    gelu<0, GD>(g, d0);
    G1(d, 1, PIN)
    epilogue<false>(m, D2, cn);
    gelu<GD, 24>(g, d0);
    PIN();
    asm volatile("fence.proxy.async.shared::cta;" ::: "memory");
    ROUND_END(d, 3)
  }
  if (m.wg == 0) { tok_idle<0>(); tok_idle<1>(); }
  return __reduce_or_sync(0xffffffffu, bad & 0xffffu);
}

struct ConvCtx {
  uint32_t sb;
  uint32_t a0, a_c;
  uint32_t peer_off;
  int rank, v, c0, r0, dir, zero;
  const CUtensorMap* tm;
  Scratch* scr;
  const uint8_t* xsrc;
  uint8_t* optr;
};

__device__ __forceinline__ void raw_refill(const ConvCtx& c, int s) {
  if (s + 4 < NSTEP && elect_one())
    tma_raw(c.sb + OFF_RAW + (s & 3) * RAW_BYTES, c.tm, c.rank, c.c0 / 2 - 2, c.r0 + c.dir * (2 * s + 5), c.sb + BAR_RAW + 8 * (s & 3));
}
__device__ __forceinline__ void step_ready(const ConvCtx& c, int s) {
  const int nx = (s + 1) & 3, par = ((s + 1) >> 2) & 1;
  if (s + 1 < NSTEP) mbar_wait(c.sb + BAR_RAW + 8 * nx, par);
  if (s >= 7 && s < NSTEP) mbar_wait(c.sb + BAR_CEMPTY + 8 * (2 * (nx & 1) + (nx >> 1)), par);
}

__device__ __forceinline__ void c_release(const ConvCtx& c, uint32_t w) {
  const uint32_t e = c.sb + BAR_CEMPTY + 8 * (2 * c.rank + w);
  asm volatile(
      "{\n.reg .pred p;\nelect.sync _|p, 0xffffffff;\n"
      "@p mbarrier.arrive.expect_tx.shared::cta.b64 _, [%0], %3;\n"
      "@p mbarrier.arrive.shared::cluster.b64 _, [%1], 4;\n"
      "@p mbarrier.arrive.shared::cluster.b64 _, [%2], 4;\n}\n" ::"r"(c.sb + BAR_CFULL + 8 * w),
      "r"(e), "r"(e + c.peer_off), "n"(CTX)
      : "memory");
}

__device__ __forceinline__ void prod_rows(const ConvCtx& c) {
#pragma unroll 1
  for (int s = 0; s < NROUND + SIGMA + c.rank; s++) {
    if (s < SIGMA) NB_SYNC(NB_PLAN, 192);
    else NB_SYNC(NB_OPEN, 448);
    raw_refill(c, s);
  }
}
__device__ __forceinline__ void prod_checks(const ConvCtx& c) {
  asm volatile("barrier.cluster.wait.aligned;" ::: "memory");
#pragma unroll 1
  for (int s = 0; s < NROUND + SIGMA + c.rank; s++) {
    const int r = s - SIGMA - c.rank;
    const int u = (r & 1) ? (r >> 1) - 1 : (r >> 1) + 2;
    step_ready(c, s);
    if (s < 16) TP(c.scr, 100 + s);
    if (u >= ((r & 1) ? 0 : 4) && u < 32) mbar_wait(c.sb + ((r & 1) ? BAR_XFULL : BAR_CFULL) + 8 * (u & 1), (u >> 1) & 1);
    if (s < SIGMA) NB_SYNC(NB_PLAN, 192);
    else NB_SYNC(NB_OPEN, 448);
    TP(c.scr, s);
    if (r == 3) TC(c.scr, 1);
    if (r == 55) TC(c.scr, 2);
  }
}
__device__ __forceinline__ void prod_tiles(const ConvCtx& c) {
  asm volatile("barrier.cluster.wait.aligned;" ::: "memory");
#pragma unroll 1
  for (int n = 1; n < 33; n++) {
    const uint32_t w = (n + 1) & 1;
    const uint32_t buf = c.sb + OFF_XRES + w * 12288;
    NB_SYNC(NB_PROD, 160);
    if (n < 29) c_release(c, w);
    if (n >= 3) {
      uint8_t* dst = c.optr + (n - 3) * c.dir * (4 * IMG * CH * 2);
      if (elect_one()) {
        asm volatile("cp.async.bulk.global.shared::cta.bulk_group [%0], [%1], 6144;" ::"l"(dst), "r"(buf) : "memory");
        asm volatile("cp.async.bulk.global.shared::cta.bulk_group [%0], [%1], 6144;" ::"l"(dst + IMG * CH * 2), "r"(buf + 6144) : "memory");
        asm volatile("cp.async.bulk.commit_group;" ::: "memory");
        asm volatile("cp.async.bulk.wait_group.read 0;" ::: "memory");
      }
      __syncwarp();
    }
    {
      const uint8_t* src = c.xsrc + (n - 1) * c.dir * (4 * IMG * CH * 2);
      if (elect_one()) {
        mbar_expect(c.sb + BAR_XFULL + 8 * w, 12288);
        bulk_load_last(buf, src, 6144, c.sb + BAR_XFULL + 8 * w);
        bulk_load_last(buf + 6144, src + IMG * CH * 2, 6144, c.sb + BAR_XFULL + 8 * w);
      }
    }
  }
  asm volatile("cp.async.bulk.wait_group 0;" ::: "memory");
}

template <int LO, int HI>
__device__ __forceinline__ void conv_ld8(uint32_t a0, uint32_t (&r)[6][6]) {
  const uint32_t a2 = a0 ^ (16 | ((a0 >> 2) & 32));
  const uint32_t a[3] = {a0, (a0 & 64) ? a2 : a0, a2};
#pragma unroll
  for (int j = LO; j < HI; j++)
    asm volatile("ld.shared.v4.b32 {%0,%1,%2,%3}, [%4];"
                 : "=r"(r[j][0]), "=r"(r[j][1]), "=r"(r[j][2]), "=r"(r[j][3])
                 : "r"(a[j >> 1] + (j >> 1) * 64 + (j & 1) * RAW_PA)
                 : "memory");
}
__device__ __forceinline__ void conv_ld4(uint32_t a0, uint32_t stage, int v, uint32_t (&r)[6][6]) {
  const uint32_t ab = ((a0 >> 1) & ~31u) + (stage / 2 + 2 * RAW_PA + 8 * v);
#pragma unroll
  for (int j = 0; j < 6; j++) {
    uint32_t a = ab + (j >> 1) * 32;
    asm volatile("ld.shared.v2.b32 {%0,%1}, [%2];" : "=r"(r[j][4]), "=r"(r[j][5]) : "r"(a + (j & 1) * RAW_PB) : "memory");
  }
}
template <int LO, int HI>
__device__ __forceinline__ void conv_frags(uint32_t zero, const uint32_t (&r)[6][6], uint32_t (&A)[12][4]) {
#pragma unroll
  for (int ch = LO; ch < HI; ch++) {
    const uint32_t sel = (ch & 1) ? 0x7632 : 0x5410;
    A[ch][0] = __byte_perm(r[0][ch >> 1], r[1][ch >> 1], sel);
    A[ch][1] = __byte_perm(r[2][ch >> 1], r[3][ch >> 1], sel);
    A[ch][2] = A[ch][1] ^ zero;
    A[ch][3] = __byte_perm(r[4][ch >> 1], r[5][ch >> 1], sel);
    rfence(A[ch]);
  }
}
__device__ __forceinline__ void hmma_acc(uint32_t (&v)[4], const uint32_t (&a)[4], const uint32_t* b) {
  asm volatile("mma.sync.aligned.m16n8k16.row.col.f32.bf16.bf16.f32 {%0,%1,%2,%3}, {%4,%5,%6,%7}, {%8,%9}, {%0,%1,%2,%3};"
               : "+r"(v[0]), "+r"(v[1]), "+r"(v[2]), "+r"(v[3])
               : "r"(a[0]), "r"(a[1]), "r"(a[2]), "r"(a[3]), "r"(b[0]), "r"(b[1]));
}
__device__ __forceinline__ void hmma_new(uint32_t (&a)[4], const uint32_t* b) {
  asm volatile("mma.sync.aligned.m16n8k16.row.col.f32.bf16.bf16.f32 {%0,%1,%2,%3}, {%0,%1,%2,%3}, {%4,%5}, {%6,%6,%6,%6};"
               : "+r"(a[0]), "+r"(a[1]), "+r"(a[2]), "+r"(a[3])
               : "r"(b[0]), "r"(b[1]), "f"(0.f));
}

#define EARLY 6
__device__ __forceinline__ void conv_send(bool local, const uint32_t (&pk)[12], uint32_t dst, uint32_t bar) {
  if (local) {
#pragma unroll
    for (int q = 0; q < 3; q++)
      asm volatile("st.shared.v4.b32 [%0], {%1,%2,%3,%4};" ::"r"(dst + q * 2048), "r"(pk[4 * q]), "r"(pk[4 * q + 1]), "r"(pk[4 * q + 2]), "r"(pk[4 * q + 3])
                   : "memory");
    asm volatile("{\n.reg .pred p;\nelect.sync _|p, 0xffffffff;\n@p mbarrier.arrive.shared::cta.b64 _, [%0];\n}\n" ::"r"(bar) : "memory");
  } else {
#pragma unroll
    for (int q = 0; q < 3; q++)
      asm volatile("st.async.weak.shared::cluster.mbarrier::complete_tx::bytes.v4.b32 [%0], {%1,%2,%3,%4}, [%5];" ::"r"(dst + q * 2048),
                   "r"(pk[4 * q]), "r"(pk[4 * q + 1]), "r"(pk[4 * q + 2]), "r"(pk[4 * q + 3]), "r"(bar)
                   : "memory");
  }
}
template <int S2, bool GATED>
__device__ __forceinline__ void conv_step(const ConvCtx& c, int s, uint32_t (&K)[12], uint32_t (&V)[12][4], const uint32_t (&B)[12][4],
                                          uint32_t (&A)[12][4]) {
  const int nx = ((s + 1) & 2) | (S2 ^ 1);
  uint32_t r[6][6], pk[12];
  const uint32_t a0 = c.a0 + nx * RAW_BYTES;
  if (GATED) NB_SYNC(NB_OPEN, 448);
  else NB_SYNC(NB_PLAN, 192);
  conv_ld4(a0, c.sb + OFF_RAW + nx * RAW_BYTES, c.v, r);
  if (GATED) PIN();
#pragma unroll
  for (int ch = 0; ch < 12; ch++) hmma_acc(V[11 - ch], A[11 - ch], &B[11 - ch][2]);
#pragma unroll
  for (int ch = 0; ch < 12 - EARLY; ch++) hmma_new(A[ch], &B[ch][0]);
  const uint32_t zero = GATED ? c.zero & clock_pin() : c.zero;
  if (GATED) NB_ARRIVE(NB_CLOSE, 256);
#pragma unroll
  for (int ch = 12 - EARLY; ch < 12; ch++) hmma_new(A[ch], &B[ch][0]);
  if (GATED) PIN();
  const bool local = (S2 ^ 1) == c.rank;
  const uint32_t off = local ? 0u : c.peer_off;
  const uint32_t dst = c.a_c + off + (nx >> 1) * C_BYTES;
  const uint32_t bar = c.sb + off + BAR_CFULL + 8 * (nx >> 1);
#pragma unroll
  for (int q = 0; q < 12; q++) {
    const int ch = q & ~1, h = 2 * (q & 1);
    pk[q] = h_add(K[q], pack_f16(__uint_as_float(V[ch][h + 1]), __uint_as_float(V[ch + 1][h])));
  }
#pragma unroll
  for (int q = 0; q < 12; q++) {
    const int ch = q & ~1, h = 2 * (q & 1);
    K[q] = pack_f16(__uint_as_float(V[ch][h]), __uint_as_float(V[ch + 1][h + 1]));
  }
  rfence(K);
  rfence(pk);
  PIN();
  conv_ld8<0, 4>(a0, r);
  if (GATED || s >= 3) conv_send(local, pk, dst, bar);
  conv_frags<8, 12>(zero, r, V);
  PIN();
  conv_ld8<4, 6>(a0, r);
  conv_frags<0, 8>(zero, r, V);
  PIN();
}

__device__ __forceinline__ void conv_role(ConvCtx c) {
  const int lane = laneid(), g = lane >> 2, t = lane & 3;
  const int u = (t >> 1) * 19 + 2 * (g + (t & 1));
  c.a0 = c.sb + OFF_RAW + u * 64 + ((c.v ^ (u >> 1)) & 3) * 16;
  c.a_c = c.sb + OFF_C + 6144 * c.rank + 512 * c.v + ((lane + 2 * c.v) & 31) * 16;
  uint32_t B[12][4];
  {
    const int dc = (g >> 1) & 1, ro = g >> 2, rk = t >> 1;
    const int i0 = (c.dir > 0 ? 4 * (g & 1) : 6 - 4 * (g & 1)) + rk - ro, j0 = 4 * (t & 1) - dc;
    const uint32_t base = c.sb + OFF_XRES + (i0 * 7 + j0) * 192;
    asm volatile("barrier.cluster.wait.aligned;" ::: "memory");
    mbar_wait(c.sb + BAR_W + 48, 0);
#pragma unroll
    for (int b = 0; b < 2; b++) {
      uint32_t w[4][6];
#pragma unroll
      for (int k = 0; k < 4; k++) {
        const int ok = (unsigned)(i0 + 2 * b * c.dir) < 7u && (unsigned)(j0 + k) < 7u;
#pragma unroll
        for (int q = 0; q < 6; q++) w[k][q] = 0;
        asm volatile(
            "{\n.reg .pred p;\nsetp.ne.s32 p, %8, 0;\n@p ld.shared.v4.b32 {%0,%1,%2,%3}, [%6];\n@p ld.shared.v2.b32 {%4,%5}, [%7];\n}\n"
            : "+r"(w[k][0]), "+r"(w[k][1]), "+r"(w[k][2]), "+r"(w[k][3]), "+r"(w[k][4]), "+r"(w[k][5])
            : "r"(base + (b * 14 * c.dir + k) * 192 + 128 * c.rank + 16 * c.v), "r"(base + (b * 14 * c.dir + k) * 192 + 64 + 32 * c.rank + 8 * c.v), "r"(ok)
            : "memory");
      }
#pragma unroll
      for (int q = 0; q < 6; q++) {
        B[2 * q][2 * b] = __byte_perm(w[0][q], w[1][q], 0x5410);
        B[2 * q][2 * b + 1] = __byte_perm(w[2][q], w[3][q], 0x5410);
        B[2 * q + 1][2 * b] = __shfl_xor_sync(0xffffffffu, __byte_perm(w[0][q], w[1][q], 0x7632), 4);
        B[2 * q + 1][2 * b + 1] = __shfl_xor_sync(0xffffffffu, __byte_perm(w[2][q], w[3][q], 0x7632), 4);
      }
    }
  }
  uint32_t K1[12], K2[12], V[12][4];
#pragma unroll
  for (int ch = 0; ch < 12; ch++)
    asm volatile("" : "=r"(K1[ch]), "=r"(K2[ch]), "=r"(V[ch][0]), "=r"(V[ch][1]), "=r"(V[ch][2]), "=r"(V[ch][3]));
  uint32_t A[12][4], r[6][6];
  mbar_wait(c.sb + BAR_RAW, 0);
  conv_ld8<0, 6>(c.a0, r);
  conv_ld4(c.a0, c.sb + OFF_RAW, c.v, r);
  conv_frags<0, 12>(c.zero, r, A);
  PIN();
  NB_ARRIVE(NB_CLOSE, 256);
#pragma unroll 1
  for (int s = 0; s < SIGMA; s += 2) {
    conv_step<0, false>(c, s, K1, V, B, A);
    conv_step<1, false>(c, s + 1, K2, A, B, V);
  }
#pragma unroll 1
  for (int s = SIGMA;; s += 2) {
    conv_step<0, true>(c, s, K1, V, B, A);
    if (s == NSTEP - 1) break;
    conv_step<1, true>(c, s + 1, K2, A, B, V);
  }
#pragma unroll 1
  for (int r = NSTEP - SIGMA - c.rank; r < NROUND - 1; r++) {
    NB_SYNC(NB_OPEN, 448);
    NB_ARRIVE(NB_CLOSE, 256);
  }
  NB_SYNC(NB_OPEN, 448);
}

struct TMaps { CUtensorMap m[2]; };

__global__ void __cluster_dims__(2, 1, 1) __launch_bounds__(512, 1)
convnext_kernel(const __grid_constant__ TMaps tms, const __nv_bfloat16* __restrict__ x, const __nv_bfloat16* __restrict__ dw,
                const __nv_bfloat16* __restrict__ w1, const __nv_bfloat16* __restrict__ w2, __nv_bfloat16* __restrict__ out,
                Scratch* scr, int zero) {
  extern __shared__ __align__(1024) uint8_t smem[];
  const uint32_t sb = (uint32_t)__cvta_generic_to_shared(smem);
  const int tid = threadIdx.x, lane = tid & 31;
  const int wid = __shfl_sync(0xffffffffu, tid >> 5, 0);
  const int rank = blockIdx.x & 1, cl = blockIdx.x >> 1;
  const int dir = (cl & 16) ? 1 : -1;
  const int c0 = (cl & 15) * 32, r0 = (cl >> 4) * 128 + (dir > 0 ? 0 : 126);
  const uint32_t peer_off = mapa(sb, rank ^ 1) - sb;

  if (wid == 12 && elect_one()) {
    mbar_init(sb + BAR_W + 48, 1);
#pragma unroll
    for (int i = 0; i < 4; i++) mbar_init(sb + BAR_RAW + 8 * i, 1);
    asm volatile("fence.mbarrier_init.release.cluster;" ::: "memory");
    mbar_expect(sb + BAR_W + 48, 49 * CH * 2);
    bulk_load(sb + OFF_XRES, dw, 49 * CH * 2, sb + BAR_W + 48);
#pragma unroll
    for (int i = 0; i < E0; i++) tma_raw(sb + OFF_RAW + i * RAW_BYTES, tms.m, rank, c0 / 2 - 2, r0 + dir * (2 * i - 3), sb + BAR_RAW + 8 * i);
  }
  if (wid == 14 && elect_one()) {
    asm volatile("cp.async.bulk.prefetch.L2.global [%0], 1152;" ::"l"(reinterpret_cast<const uint8_t*>(rank ? w2 : w1) + cl * 1152) : "memory");
    asm volatile("prefetch.tensormap [%0];" ::"l"(&tms.m[1]) : "memory");
#pragma unroll
    for (int i = 0; i < 3; i++) mbar_init(sb + BAR_W + 8 * i, 1);
#pragma unroll
    for (int i = 0; i < 2; i++) mbar_init(sb + BAR_CFULL + 8 * i, CCNT);
#pragma unroll
    for (int i = 0; i < 4; i++) mbar_init(sb + BAR_CEMPTY + 8 * i, 4);
#pragma unroll
    for (int i = 0; i < 2; i++) mbar_init(sb + BAR_XFULL + 8 * i, 1);
#pragma unroll
    for (int i = 0; i < 2; i++) mbar_expect(sb + BAR_CFULL + 8 * i, CTX);
    asm volatile("fence.mbarrier_init.release.cluster;" ::: "memory");
  }
  __syncwarp();
  asm volatile("barrier.cluster.arrive.relaxed.aligned;" ::: "memory");

  if (wid < 8) {
    if (blockIdx.x < 48) convert_tile(blockIdx.x, wid, reinterpret_cast<const uint4*>(w1), reinterpret_cast<const uint4*>(w2), sb, scr);
    MlpCtx m;
    m.sb = sb; m.wg = wid >> 2; m.warp = wid & 3; m.rank = rank; m.peer_off = peer_off; m.zero = zero;
    m.optr = reinterpret_cast<uint8_t*>(out) + ((size_t)(r0 + dir * (120 + 4 * m.wg + 2 * rank)) * IMG + c0 + 8 * m.warp) * (CH * 2);
    m.caddr = sb + OFF_C + m.wg * C_BYTES + (lane & 3) * 512 + ((m.warp * 8 + (lane >> 2) + 2 * (lane & 3)) & 31) * 16;
    m.xaddr = sb + OFF_XRES + m.wg * 12288 + m.warp * 1536 + ((lane >> 3) & 1) * 6144 + ((lane >> 4) * 4 + ((lane >> 2) & 1)) * 192 + (lane & 3) * 16;
    m.unscale = 0;
    asm volatile("setmaxnreg.inc.sync.aligned.u32 %0;" ::"n"(REG_MLP));
    const uint32_t bad = mlp_role(m);
    TC(scr, 3);
    if (bad) {
      mbar_wait(sb + BAR_W + 16, 0);
      __syncwarp();
      asm volatile("fence.proxy.async;" ::: "memory");
#pragma unroll 1
      for (int i = 0; i < 16; i++)
        if (bad >> i & 1)
          slow_tile(x, dw, w1, w2, out, r0 + dir * (8 * i + 4 * m.wg + 2 * rank), c0 + 8 * m.warp,
                    reinterpret_cast<float*>(smem + OFF_RAW + wid * 2048));
    }
  } else {
    ConvCtx c;
    c.sb = sb; c.rank = rank; c.v = wid - 8; c.c0 = c0; c.r0 = r0; c.dir = dir; c.zero = zero; c.tm = tms.m; c.scr = scr;
    c.peer_off = peer_off;
    c.xsrc = reinterpret_cast<const uint8_t*>(x) + ((size_t)(r0 + 2 * dir * rank) * IMG + c0) * (CH * 2);
    c.optr = reinterpret_cast<uint8_t*>(out) + ((size_t)(r0 + 2 * dir * rank) * IMG + c0) * (CH * 2);
    if (wid < 12) {
      asm volatile("setmaxnreg.inc.sync.aligned.u32 %0;" ::"n"(REG_CONV));
      conv_role(c);
    } else {
      asm volatile("setmaxnreg.dec.sync.aligned.u32 24;");
      if (wid == 15) TC(scr, 0);
      if (wid == 12) {
#pragma unroll 1
        for (int h = E0 - 4; h < 0; h++) raw_refill(c, h);
        prod_rows(c);
      } else if (wid == 15) {
        prod_checks(c);
      } else if (wid == 14) {
#pragma unroll 1
        for (int n = 0; n < (1 << 20); n++) {
          unsigned v;
          __nanosleep(n ? PSL : PS0);
          asm volatile("ld.acquire.gpu.global.u32 %0, [%1];" : "=r"(v) : "l"(&scr->done) : "memory");
          if (__shfl_sync(0xffffffffu, v, 0) >= 48) break;
        }
        TP(scr, 90);
        asm volatile("barrier.cluster.wait.aligned;" ::: "memory");
        asm volatile("fence.proxy.async.global;" ::: "memory");
        if (elect_one()) {
          mbar_expect(sb + BAR_W, 36864 + 768);
          mbar_expect(sb + BAR_W + 8, 110592);
          bulk_load(sb + OFF_NRM, scr->nrm, 768, sb + BAR_W);
        }
        __syncwarp();
#pragma unroll 1
        for (int i = 0; i < 8; i++) {
          if (elect_one()) bulk_load(sb + i * 18432, reinterpret_cast<const uint8_t*>(scr->w) + i * 18432, 18432, sb + BAR_W + (i < 2 ? 0 : 8));
          if (i >= PFIRST) __nanosleep(PACE);
        }
        if (elect_one() && atomicAdd(&scr->seen, 1u) == gridDim.x - 1) { scr->done = 0; scr->seen = 0; }
      } else if (wid == 13) {
        prod_tiles(c);
        __syncwarp();
        if (elect_one()) asm volatile("mbarrier.arrive.shared::cta.b64 _, [%0];" ::"r"(sb + BAR_W + 16) : "memory");
      }
    }
  }
}

typedef CUresult (*EncodeFn)(CUtensorMap*, CUtensorMapDataType, cuuint32_t, void*, const cuuint64_t*, const cuuint64_t*,
                             const cuuint32_t*, const cuuint32_t*, CUtensorMapInterleave, CUtensorMapSwizzle,
                             CUtensorMapL2promotion, CUtensorMapFloatOOBfill);

}

extern "C" void kernel_launch(void* const* d_in, const int* in_sizes, int n_in, void* d_out, int out_size) {
  const __nv_bfloat16* x = (const __nv_bfloat16*)d_in[0];
  const __nv_bfloat16* dw = (const __nv_bfloat16*)d_in[1];
  const __nv_bfloat16* w1 = (const __nv_bfloat16*)d_in[2];
  const __nv_bfloat16* w2 = (const __nv_bfloat16*)d_in[3];
  __nv_bfloat16* out = (__nv_bfloat16*)d_out;

  static EncodeFn encode = nullptr;
  static Scratch* scr = nullptr;
  if (!encode) {
    cudaDriverEntryPointQueryResult st;
    void* fn = nullptr;
    cudaGetDriverEntryPoint("cuTensorMapEncodeTiled", &fn, cudaEnableDefault, &st);
    encode = (EncodeFn)fn;
    cudaGetSymbolAddress((void**)&scr, g_scratch);
    cudaFuncSetAttribute(convnext_kernel, cudaFuncAttributeMaxDynamicSharedMemorySize, SMEM_BYTES);
  }
  TMaps tm;
  cuuint64_t dims[4] = {CH, IMG / 2, IMG, 2};
  cuuint64_t strides[3] = {CH * 4, (cuuint64_t)IMG * CH * 2, CH * 2};
  cuuint32_t es[4] = {1, 1, 1, 1};
  for (int i = 0; i < 2; i++) {
    cuuint32_t box[4] = {i ? 16u : 32u, 19, 2, 1};
    encode(&tm.m[i], CU_TENSOR_MAP_DATA_TYPE_BFLOAT16, 4, (void*)x, dims, strides, box, es, CU_TENSOR_MAP_INTERLEAVE_NONE,
           i ? CU_TENSOR_MAP_SWIZZLE_NONE : CU_TENSOR_MAP_SWIZZLE_64B, PROMO, CU_TENSOR_MAP_FLOAT_OOB_FILL_NONE);
  }
  convnext_kernel<<<128, 512, SMEM_BYTES>>>(tm, x, dw, w1, w2, out, scr, 0);
}
```

```cpp
#include <cuda_runtime.h>
#include <cuda_bf16.h>
#include <cuda.h>
#include <stdint.h>

#define PROMO CU_TENSOR_MAP_L2_PROMOTION_L2_128B
#define CTX 6144
#define CCNT 5
#define PSL 100
#define PS0 1000
#define E0 1
#define PACE 100
#define PFIRST 1
namespace {

constexpr int IMG = 512, CH = 96;
constexpr int NSTEP = 67;
constexpr int SIGMA = 8;
constexpr int NROUND = 68;

constexpr uint32_t OFF_W1 = 0;
constexpr uint32_t OFF_W2 = 73728;
constexpr uint32_t OFF_RAW = 147456;
constexpr uint32_t RAW_PA = 2560, RAW_PB = 1280;
constexpr uint32_t RAW_BYTES = 2 * RAW_PA + 2 * RAW_PB;
constexpr uint32_t RAW_TX = 2 * 38 * 96;
constexpr uint32_t OFF_XRES = OFF_RAW + 4 * RAW_BYTES;
constexpr uint32_t OFF_C = OFF_XRES + 2 * 12288;
constexpr uint32_t C_BYTES = 12288;
constexpr uint32_t OFF_BAR = OFF_C + 2 * C_BYTES;
constexpr uint32_t BAR_RAW = OFF_BAR;
constexpr uint32_t BAR_CFULL = OFF_BAR + 32;
constexpr uint32_t BAR_CEMPTY = OFF_BAR + 48;
constexpr uint32_t BAR_XFULL = OFF_BAR + 80;
constexpr uint32_t BAR_W = OFF_BAR + 96;
constexpr uint32_t OFF_NRM = OFF_XRES + 9472;
constexpr uint32_t OFF_BAD = OFF_BAR + 160;
constexpr uint32_t SMEM_BYTES = OFF_BAD + 32;

struct Scratch {
  uint4 w[2 * 73728 / 16];
  uint4 nrm[48];
  unsigned done, seen;
};
__device__ Scratch g_scratch;

constexpr float GELU_A = 0.32918364f;
constexpr uint32_t GELU_K2 = 0x40d940d9u;

constexpr int NB_CLOSE = 1, NB_SEC = 6  , NB_OPEN = 3, NB_PROD = 2, NB_PLAN = 4, NB_PREP = 5, NB_WG = 8  ;
#define REG_MLP 144
constexpr int REG_CONV = 488 - 2 * REG_MLP;

#define WG_FENCE() asm volatile("wgmma.fence.sync.aligned;" ::: "memory")
#define WG_COMMIT() asm volatile("wgmma.commit_group.sync.aligned;" ::: "memory")
#define WG_WAIT0() asm volatile("wgmma.wait_group.sync.aligned 0;" ::: "memory")
#define WG_WAIT1() asm volatile("wgmma.wait_group.sync.aligned 1;" ::: "memory")
#define PIN() asm volatile("pmevent 0;" ::: "memory")
#define NB_SYNC(id, n) asm volatile("bar.sync %0, %1;" ::"n"(id), "n"(n) : "memory")
#define NB_ARRIVE(id, n) asm volatile("bar.arrive %0, %1;" ::"n"(id), "n"(n) : "memory")

#define TC(scr, k)
#define TP(scr, k)

#define R24(c, d)                                                                                        \
  c(d[0]), c(d[1]), c(d[2]), c(d[3]), c(d[4]), c(d[5]), c(d[6]), c(d[7]), c(d[8]), c(d[9]), c(d[10]),    \
      c(d[11]), c(d[12]), c(d[13]), c(d[14]), c(d[15]), c(d[16]), c(d[17]), c(d[18]), c(d[19]), c(d[20]), \
      c(d[21]), c(d[22]), c(d[23])
#define WG_TXT(sd)                                                                             \
  "wgmma.mma_async.sync.aligned.m64n96k16.f16.f16.f16 "                                        \
  "{%0,%1,%2,%3,%4,%5,%6,%7,%8,%9,%10,%11,%12,%13,%14,%15,%16,%17,%18,%19,%20,%21,%22,%23}, " \
  "{%24,%25,%26,%27}, %28, " sd ", 1, 1, 1;\n"

__device__ __forceinline__ void wg_acc(uint32_t (&d)[24], const uint32_t* a, uint64_t db) {
  asm volatile(WG_TXT("1") : R24("+r", d) : "r"(a[0]), "r"(a[1]), "r"(a[2]), "r"(a[3]), "l"(db));
}
__device__ __forceinline__ void wg_init(uint32_t (&d)[24], const uint32_t* a, uint64_t db) {
  asm volatile(WG_TXT("0") : R24("=r", d) : "r"(a[0]), "r"(a[1]), "r"(a[2]), "r"(a[3]), "l"(db));
}
template <int N>
__device__ __forceinline__ void rfence(uint32_t (&d)[N]) {
#pragma unroll
  for (int i = 0; i < N; i++) asm volatile("" : "+r"(d[i])::"memory");
}
template <bool INIT, int KSTRIDE>
__device__ __forceinline__ void gemm6(uint32_t (&d)[24], const uint32_t (&a)[24], uint64_t db) {
#pragma unroll
  for (int k = 0; k < 6; k++) {
    if (INIT && k == 0) wg_init(d, &a[0], db);
    else wg_acc(d, &a[4 * k], db + k * KSTRIDE);
  }
  WG_COMMIT();
}

__device__ __forceinline__ void mbar_init(uint32_t bar, uint32_t cnt) {
  asm volatile("mbarrier.init.shared::cta.b64 [%0], %1;" ::"r"(bar), "r"(cnt) : "memory");
}
__device__ __forceinline__ void mbar_expect(uint32_t bar, uint32_t bytes) {
  asm volatile("mbarrier.arrive.expect_tx.shared::cta.b64 _, [%0], %1;" ::"r"(bar), "r"(bytes) : "memory");
}
__device__ __forceinline__ void mbar_arrive_cluster(uint32_t bar) {
  asm volatile("mbarrier.arrive.shared::cluster.b64 _, [%0];" ::"r"(bar) : "memory");
}
__device__ __forceinline__ bool mbar_try(uint32_t bar, uint32_t parity) {
  uint32_t ok;
  asm volatile(
      "{\n.reg .pred p;\nmbarrier.try_wait.parity.shared::cta.b64 p, [%1], %2;\nselp.u32 %0, 1, 0, p;\n}\n"
      : "=r"(ok)
      : "r"(bar), "r"(parity)
      : "memory");
  return ok;
}
__device__ __forceinline__ bool mbar_test(uint32_t bar, uint32_t parity) {
  uint32_t ok;
  asm volatile(
      "{\n.reg .pred p;\nmbarrier.test_wait.parity.shared::cta.b64 p, [%1], %2;\nselp.u32 %0, 1, 0, p;\n}\n"
      : "=r"(ok)
      : "r"(bar), "r"(parity)
      : "memory");
  return ok;
}
__device__ __forceinline__ void mbar_wait(uint32_t bar, uint32_t parity) {
  if (__builtin_expect(mbar_try(bar, parity), 1)) return;
#pragma unroll 1
  for (uint32_t n = 0; n < (1u << 16) && !mbar_try(bar, parity); n++) {}
}
__device__ __forceinline__ uint32_t mapa(uint32_t addr, uint32_t rank) {
  uint32_t r;
  asm("mapa.shared::cluster.u32 %0, %1, %2;" : "=r"(r) : "r"(addr), "r"(rank));
  return r;
}
__device__ __forceinline__ void tma_raw(uint32_t dst, const CUtensorMap* tm, int rank, int w2, int h, uint32_t bar) {
  mbar_expect(bar, RAW_TX);
#pragma unroll
  for (int k = 0; k < 4; k++) {
    const int e = k & 1;
    asm volatile(
        "cp.async.bulk.tensor.4d.shared::cluster.global.mbarrier::complete_tx::bytes [%0], [%1, {%2, %3, %4, %5}], [%6];"
        ::"r"(dst + (k < 2 ? e * RAW_PA : 2 * RAW_PA + e * RAW_PB)), "l"(tm + (k >> 1)), "r"(k < 2 ? 64 * rank : 32 + 16 * rank), "r"(w2 + e),
        "r"(h), "r"(1 - e), "r"(bar)
        : "memory");
  }
}
__device__ __forceinline__ void bulk_load(uint32_t dst, const void* src, uint32_t bytes, uint32_t bar) {
  asm volatile("cp.async.bulk.shared::cluster.global.mbarrier::complete_tx::bytes [%0], [%1], %2, [%3];" ::"r"(dst),
               "l"(src), "r"(bytes), "r"(bar)
               : "memory");
}
__device__ __forceinline__ void bulk_load_last(uint32_t dst, const void* src, uint32_t bytes, uint32_t bar) {
  asm volatile(
      "{\n.reg .b64 pol;\ncreatepolicy.fractional.L2::evict_first.b64 pol, 1.0;\n"
      "cp.async.bulk.shared::cluster.global.mbarrier::complete_tx::bytes.L2::cache_hint [%0], [%1], %2, [%3], pol;\n}\n" ::"r"(dst),
      "l"(src), "r"(bytes), "r"(bar)
      : "memory");
}
__device__ __forceinline__ uint32_t pack_bf16(float lo, float hi) {
  uint32_t r;
  asm("cvt.rn.bf16x2.f32 %0, %1, %2;" : "=r"(r) : "f"(hi), "f"(lo));
  return r;
}
__device__ __forceinline__ uint32_t pack_f16(float lo, float hi) {
  uint32_t r;
  asm("cvt.rn.f16x2.f32 %0, %1, %2;" : "=r"(r) : "f"(hi), "f"(lo));
  return r;
}
__device__ __forceinline__ float bf_lo(uint32_t v) { return __uint_as_float(v << 16); }
__device__ __forceinline__ float bf_hi(uint32_t v) { return __uint_as_float(v & 0xffff0000u); }
__device__ __forceinline__ uint32_t bf_add(uint32_t a, uint32_t b) {
  uint32_t r;
  asm("add.rn.bf16x2 %0, %1, %2;" : "=r"(r) : "r"(a), "r"(b));
  return r;
}
__device__ __forceinline__ uint32_t bf_mul(uint32_t a, uint32_t b) {
  uint32_t r;
  asm("mul.rn.bf16x2 %0, %1, %2;" : "=r"(r) : "r"(a), "r"(b));
  return r;
}
__device__ __forceinline__ uint32_t bf_fma(uint32_t a, uint32_t b, uint32_t c) {
  uint32_t r;
  asm("fma.rn.bf16x2 %0, %1, %2, %3;" : "=r"(r) : "r"(a), "r"(b), "r"(c));
  return r;
}

__device__ __forceinline__ uint32_t h_add(uint32_t a, uint32_t b) {
  uint32_t r;
  asm("add.rn.f16x2 %0, %1, %2;" : "=r"(r) : "r"(a), "r"(b));
  return r;
}
__device__ __forceinline__ uint32_t h_mul(uint32_t a, uint32_t b) {
  uint32_t r;
  asm("mul.rn.f16x2 %0, %1, %2;" : "=r"(r) : "r"(a), "r"(b));
  return r;
}
__device__ __forceinline__ uint32_t h_fma(uint32_t a, uint32_t b, uint32_t c) {
  uint32_t r;
  asm("fma.rn.f16x2 %0, %1, %2, %3;" : "=r"(r) : "r"(a), "r"(b), "r"(c));
  return r;
}
__device__ __forceinline__ float h_sum(uint32_t v) {
  float lo, hi;
  asm("{\n.reg .b16 l, h;\nmov.b32 {l, h}, %2;\ncvt.f32.f16 %0, l;\ncvt.f32.f16 %1, h;\n}\n" : "=f"(lo), "=f"(hi) : "r"(v));
  return lo + hi;
}
__device__ __forceinline__ void lds128(uint32_t (&v)[4], uint32_t a) {
  asm volatile("ld.shared.v4.b32 {%0,%1,%2,%3}, [%4];" : "=r"(v[0]), "=r"(v[1]), "=r"(v[2]), "=r"(v[3]) : "r"(a) : "memory");
}

template <int LO, int HI>
__device__ __forceinline__ void gelu(uint32_t (&o)[24], const uint32_t (&d)[24]) {
#pragma unroll
  for (int qq = LO; qq < HI; qq++) {
    const int q = (qq + 4) % 24;
    uint32_t t, u;
    asm("fma.rn.f16x2 %0, %1, %1, %2;" : "=r"(t) : "r"(d[q]), "r"(GELU_K2));
    asm("mul.rn.f16x2 %0, %1, %2;" : "=r"(u) : "r"(d[q]), "r"(t));
    asm("tanh.approx.f16x2 %0, %1;" : "=r"(t) : "r"(u));
    asm("fma.rn.f16x2 %0, %1, %2, %1;" : "=r"(o[q]) : "r"(d[q]), "r"(t));
  }
}

__device__ __forceinline__ uint32_t laneid() {
  uint32_t l;
  asm volatile("mov.u32 %0, %%laneid;" : "=r"(l));
  return l;
}

__device__ __forceinline__ bool elect_one() {
  uint32_t p;
  asm volatile("{\n.reg .pred p;\nelect.sync _|p, 0xffffffff;\nselp.u32 %0, 1, 0, p;\n}\n" : "=r"(p));
  return p;
}

__device__ __forceinline__ uint32_t clock_pin() {
  uint32_t t;
  asm volatile("mov.u32 %0, %%clock;" : "=r"(t)::"memory");
  return t;
}

struct MlpCtx {
  uint32_t sb;
  uint32_t caddr;
  uint32_t xaddr;
  uint32_t unscale;
  uint32_t peer_off;
  int wg, warp, rank, zero;
  uint8_t* optr;
};

__device__ __forceinline__ void ln_wait(const MlpCtx& m, int i) { mbar_wait(m.sb + BAR_CFULL + 8 * m.wg, i & 1); }
__device__ __forceinline__ void ln_load(const MlpCtx& m, uint32_t (&c)[24]) {
#pragma unroll
  for (int p = 0; p < 6; p++)
    asm volatile("ld.shared.v4.b32 {%0,%1,%2,%3}, [%4];"
                 : "=r"(c[4 * p]), "=r"(c[4 * p + 1]), "=r"(c[4 * p + 2]), "=r"(c[4 * p + 3])
                 : "r"(m.caddr + p * 2048)
                 : "memory");
}
__device__ __forceinline__ void ln_shfl(float (&st)[8], int mask) {
#pragma unroll
  for (int k = 0; k < 4; k++) st[4 + k] = __shfl_xor_sync(0xffffffffu, st[k], mask);
}
__device__ __forceinline__ void ln_fold(float (&st)[8]) {
#pragma unroll
  for (int k = 0; k < 4; k++) st[k] += st[4 + k];
}
__device__ __forceinline__ void ln_sums(const uint32_t (&c)[24], float (&st)[8]) {
#pragma unroll
  for (int r = 0; r < 2; r++) {
    uint32_t s0 = h_add(c[r], c[r + 2]), s1 = h_add(c[r + 4], c[r + 6]), s2 = h_add(c[r + 8], c[r + 10]);
    uint32_t s3 = h_add(c[r + 12], c[r + 14]), s4 = h_add(c[r + 16], c[r + 18]), s5 = h_add(c[r + 20], c[r + 22]);
    s0 = h_add(s0, s1); s2 = h_add(s2, s3); s4 = h_add(s4, s5);
    st[r] = h_sum(h_add(h_add(s0, s2), s4));
    uint32_t q0 = h_mul(c[r], c[r]), q1 = h_mul(c[r + 2], c[r + 2]);
#pragma unroll
    for (int p = 2; p < 12; p += 2) {
      q0 = h_fma(c[2 * p + r], c[2 * p + r], q0);
      q1 = h_fma(c[2 * p + 2 + r], c[2 * p + 2 + r], q1);
    }
    st[2 + r] = h_sum(h_add(q0, q1));
  }
}
__device__ __forceinline__ void ln_release(const MlpCtx& m) {
  const uint32_t e = m.sb + BAR_CEMPTY + 8 * (2 * m.rank + m.wg);
  asm volatile(
      "{\n.reg .pred p, q;\nelect.sync _|p, 0xffffffff;\nsetp.eq.and.s32 q, %3, 0, p;\n"
      "@q mbarrier.arrive.expect_tx.shared::cta.b64 _, [%0], %4;\n"
      "@p mbarrier.arrive.shared::cluster.b64 _, [%1];\n"
      "@p mbarrier.arrive.shared::cluster.b64 _, [%2];\n}\n" ::"r"(m.sb + BAR_CFULL + 8 * m.wg),
      "r"(e), "r"(e + m.peer_off), "r"(m.warp), "n"(CTX)
      : "memory");
}
__device__ __forceinline__ bool ln_stats(float (&st)[8]) {
  bool ok = true;
#pragma unroll
  for (int r = 0; r < 2; r++) {
    const float nm = (st[r] + st[4 + r]) * (-1.0f / 96.0f);
    const float e2 = fmaf(st[2 + r] + st[6 + r], 1.0f / 96.0f, 1e-5f);
    float rs;
    asm("rsqrt.approx.ftz.f32 %0, %1;" : "=f"(rs) : "f"(fmaf(-nm, nm, e2)));
    ok = ok && (rs * rs * e2 <= 17.0f) && (e2 >= 1.001e-5f);
    const float rr = rs * GELU_A, dd = rr * nm;
    st[r] = __uint_as_float(pack_f16(rr, rr));
    st[2 + r] = __uint_as_float(pack_f16(dd, dd));
  }
  return ok;
}
__device__ __forceinline__ void mark_bad(uint32_t addr, uint32_t bits) {
  asm volatile("{\n.reg .pred p;\nelect.sync _|p, 0xffffffff;\n@p red.shared.or.b32 [%0], %1;\n}\n" ::"r"(addr), "r"(bits) : "memory");
  __syncwarp();
}
__device__ __forceinline__ void ln_restat(bool ok, const uint32_t (&c)[24], float (&st)[8], uint32_t bad, int i,
                                          uint32_t zero) {
  if (__builtin_expect(__any_sync(0xffffffffu, !ok), 0)) {
#pragma unroll
    for (int r = 0; r < 2; r++) {
      float nm = 0.f, var = 0.f;
#pragma unroll
      for (int p = 0; p < 12; p++) {
        nm += h_sum(c[2 * p + r] ^ zero);
        if (p % 3 == 2) { asm volatile("" : "+f"(nm)); PIN(); }
      }
      nm += __shfl_xor_sync(0xffffffffu, nm, 1);
      nm += __shfl_xor_sync(0xffffffffu, nm, 2);
      nm *= -1.0f / 96.0f;
#pragma unroll
      for (int p = 0; p < 12; p++) {
        float lo, hi;
        asm volatile("{\n.reg .b16 l, h;\nmov.b32 {l, h}, %2;\ncvt.f32.f16 %0, l;\ncvt.f32.f16 %1, h;\n}\n" : "=f"(lo), "=f"(hi) : "r"(c[2 * p + r]));
        var = fmaf(lo + nm, lo + nm, fmaf(hi + nm, hi + nm, var));
        if (p % 3 == 2) { asm volatile("" : "+f"(var)); PIN(); }
      }
      var += __shfl_xor_sync(0xffffffffu, var, 1);
      var += __shfl_xor_sync(0xffffffffu, var, 2);
      const float rr = rsqrtf(fmaf(var, 1.0f / 96.0f, 1e-5f)) * GELU_A;
      st[r] = __uint_as_float(pack_f16(rr, rr));
      const float dd = 0.5f * h_sum(__float_as_uint(st[r])) * nm;
      st[2 + r] = __uint_as_float(pack_f16(dd, dd));
      if (__any_sync(0xffffffffu, !(rr >= 0x1p-14f && fabsf(dd) <= 16.0f && var >= 1e-8f))) mark_bad(bad, 1u << i);
    }
  }
}
__device__ __forceinline__ void ln_apply(uint32_t (&a)[24], const uint32_t (&c)[24], const float (&st)[8]) {
#pragma unroll
  for (int p = 0; p < 24; p++) {
    a[p] = h_fma(c[p], __float_as_uint(st[p & 1]), __float_as_uint(st[2 + (p & 1)]));
  }
}

__device__ __noinline__ void slow_tile(const __nv_bfloat16* x, const __nv_bfloat16* dw, const __nv_bfloat16* w1,
                                       const __nv_bfloat16* w2, __nv_bfloat16* out, int row0, int col0, float* buf) {
  const int lane = threadIdx.x & 31;
  for (int px = 0; px < 16; px++) {
    const int row = row0 + (px >> 3), col = col0 + (px & 7);
    float c[3] = {0.f, 0.f, 0.f};
    for (int i = 0; i < 7; i++)
      for (int j = 0; j < 7; j++) {
        const int rr = row + i - 3, cc = col + j - 3;
        if (rr < 0 || rr >= IMG || cc < 0 || cc >= IMG) continue;
        for (int k = 0; k < 3; k++)
          c[k] = fmaf(__bfloat162float(x[((size_t)rr * IMG + cc) * CH + lane + 32 * k]), __bfloat162float(dw[(i * 7 + j) * CH + lane + 32 * k]), c[k]);
      }
    float mean = (c[0] + c[1] + c[2]) * (1.0f / 96.0f);
    for (int o = 16; o; o >>= 1) mean += __shfl_xor_sync(0xffffffffu, mean, o);
    float var = 0.f;
    for (int k = 0; k < 3; k++) { c[k] -= mean; var = fmaf(c[k] * (1.0f / 96.0f), c[k], var); }
    for (int o = 16; o; o >>= 1) var += __shfl_xor_sync(0xffffffffu, var, o);
    const float rs = 1.0f / sqrtf(var + 1e-5f);
    __syncwarp();
    for (int k = 0; k < 3; k++) buf[lane + 32 * k] = c[k] * rs;
    __syncwarp();
    for (int n = lane; n < 4 * CH; n += 32) {
      float y = 0.f;
      for (int k = 0; k < CH; k++) y = fmaf(buf[k], __bfloat162float(w1[k * 4 * CH + n]), y);
      buf[CH + n] = 0.5f * y * (1.0f + tanhf(0.7978845608f * (y + 0.044715f * y * y * y)));
    }
    __syncwarp();
    for (int n = lane; n < CH; n += 32) {
      float o = 0.f;
      for (int k = 0; k < 4 * CH; k++) o = fmaf(buf[CH + k], __bfloat162float(w2[k * CH + n]), o);
      const size_t idx = ((size_t)row * IMG + col) * CH + n;
      out[idx] = __float2bfloat16(__bfloat162float(x[idx]) + o);
    }
  }
}

__device__ __forceinline__ void x_load(const MlpCtx& m, uint32_t (&x)[24]) {
#pragma unroll
  for (int k = 0; k < 6; k++)
    asm volatile("ld.shared.v4.b32 {%0,%1,%2,%3}, [%4];"
                 : "=r"(x[4 * k]), "=r"(x[4 * k + 1]), "=r"(x[4 * k + 2]), "=r"(x[4 * k + 3])
                 : "r"(m.xaddr + (k / 3) * 384 + (k % 3) * 64)
                 : "memory");
}
template <bool DIRECT>
__device__ __forceinline__ void epilogue(const MlpCtx& m, const uint32_t (&d)[24], uint32_t (&x)[24]) {
  uint8_t* o = nullptr;
  if (DIRECT) {
    const uint32_t lane = laneid();
    o = m.optr + ((lane >> 3) & 1) * (IMG * CH * 2) + ((lane >> 4) * 4 + ((lane >> 2) & 1)) * 192 + (lane & 3) * 16;
  }
#pragma unroll
  for (int k = 0; k < 6; k++) {
    const int r = k / 3, q = k % 3;
    uint32_t* y = &x[4 * k];
#pragma unroll
    for (int j = 0; j < 4; j++) {
      uint32_t v = d[2 * (4 * q + j) + r];
      float lo, hi;
      asm("{\n.reg .b16 l, h;\nmov.b32 {l, h}, %2;\ncvt.f32.f16 %0, l;\ncvt.f32.f16 %1, h;\n}\n" : "=f"(lo), "=f"(hi) : "r"(v));
      asm("fma.rn.bf16x2 %0, %1, %2, %0;" : "+r"(y[j]) : "r"(pack_bf16(lo, hi)), "r"(m.unscale));
    }
    if (DIRECT)
      asm volatile("st.global.v4.b32 [%0], {%1,%2,%3,%4};" ::"l"(o + r * 384 + q * 64), "r"(y[0]), "r"(y[1]), "r"(y[2]), "r"(y[3]) : "memory");
    else
      asm volatile("st.shared.v4.b32 [%0], {%1,%2,%3,%4};" ::"r"(m.xaddr + r * 384 + q * 64), "r"(y[0]), "r"(y[1]), "r"(y[2]), "r"(y[3])
                   : "memory");
  }
}

#define FSET 3
template <int J> constexpr bool goes_first = J == FSET || J == ((FSET + 1) & 3);
template <int J> __device__ __forceinline__ void tok_wait() {
  if (goes_first<J>) NB_SYNC(NB_CLOSE, 256);
  else NB_SYNC(NB_SEC + (J & 1), 256);
}
template <int J, bool PROD = true> __device__ __forceinline__ void tok_next() {
  if (goes_first<J>) NB_ARRIVE(NB_SEC + (J & 1), 256);
  if (J == 0 && PROD) NB_ARRIVE(NB_PROD, 160);
}
__device__ __forceinline__ void tok_pass() { NB_ARRIVE(NB_OPEN, 448); }
template <int J> __device__ __forceinline__ void tok_idle() { tok_wait<J>(); tok_next<J, false>(); tok_pass(); }

constexpr uint64_t CHK = 1152;

__device__ __forceinline__ float warp_sumsq(const uint32_t (&q)[4]) {
  const uint32_t t = bf_add(bf_add(q[0], q[1]), bf_add(q[2], q[3]));
  float f = bf_lo(t) + bf_hi(t);
#pragma unroll
  for (int o = 16; o; o >>= 1) f += __shfl_xor_sync(0xffffffffu, f, o);
  return f;
}
__device__ __forceinline__ int norm_exp(float f) { return (((int)(__float_as_uint(f * 1.5f) >> 23) - 127) >> 1) + 1; }
__device__ __forceinline__ int scale_exp(int e1, int e2) { return min(11 - e1 - e2, 14 - e2); }

__device__ __forceinline__ void convert_tile(int t, int k, const uint4* w1, const uint4* w2, uint32_t st, Scratch* scr) {
  const int lane = threadIdx.x & 31, k7 = lane & 7;
  const int j = t / 6, ks = t % 6, e = ks % 3, t4 = k7 >> 1;
  const uint4* src = t < 24 ? w1 + ((e < 2 ? 64 * (ks / 3) + 8 * t4 + 4 * e : 32 + 16 * (ks / 3) + 4 * t4) + (k7 & 1)) * 48 + j * 12 + (lane >> 3)
                            : w2 + (t - 24) * 192 + (lane >> 2) * 12 + (lane & 3);
  src += (k / 3) * 96 + (k % 3) * 4;
  if (k >= 6) src = (k == 6 ? w1 : w2) + lane * 145;
  const uint4 v = __ldg(src);
  const uint32_t w[4] = {v.x, v.y, v.z, v.w};
  const uint32_t q[4] = {bf_mul(v.x, v.x), bf_mul(v.y, v.y), bf_mul(v.z, v.z), bf_mul(v.w, v.w)};
  asm volatile("st.shared.f32 [%0], %1;" ::"r"(st + 3088 + 4 * k), "f"(warp_sumsq(q)) : "memory");
  NB_SYNC(NB_PREP, 256);
  uint32_t a[4], b[4], o[4];
  lds128(a, st + 3088);
  lds128(b, st + 3104);
  const int s = max(-64, min(64, scale_exp(norm_exp(144.f * __uint_as_float(b[2])), norm_exp(144.f * __uint_as_float(b[3]))) - 3));
  const uint32_t dst = st + k7 * 16 + (lane >> 3) * 256 + (k / 3) * 128 + (k % 3) * 1024;
  if (k >= 6) {
    const float f = ((__uint_as_float(a[0]) + __uint_as_float(a[1])) + (__uint_as_float(a[2]) + __uint_as_float(a[3]))) +
                    (__uint_as_float(b[0]) + __uint_as_float(b[1]));
    asm volatile("st.shared.v2.b32 [%0], {%1,%2};" ::"r"(st + 3072), "r"(__float_as_uint(f)), "r"(s) : "memory");
  } else if (t < 24) {
#pragma unroll
    for (int i = 0; i < 4; i++) o[i] = pack_f16(bf_lo(w[i]), bf_hi(w[i]));
    asm volatile("st.shared.v4.b32 [%0], {%1,%2,%3,%4};" ::"r"(dst), "r"(o[0]), "r"(o[1]), "r"(o[2]), "r"(o[3]) : "memory");
  } else {
    constexpr float F = 0.5f / GELU_A, FHI = 1.515625f;
    const float p2 = __uint_as_float((uint32_t)(127 + s - 56) << 23);
    const uint32_t hi = pack_bf16(FHI * 0x1p-56f, FHI * 0x1p-56f), lo = pack_bf16((F - FHI) * 0x1p-56f, (F - FHI) * 0x1p-56f);
    const uint32_t pw = pack_bf16(p2, p2);
#pragma unroll
    for (int i = 0; i < 4; i++) {
      const uint32_t ws = bf_mul(w[i], pw), u = bf_fma(ws, hi, bf_mul(ws, lo));
      o[i] = (u & 0x7fff7fffu) * 7u + u;
    }
    asm volatile("stmatrix.sync.aligned.m8n8.x4.shared.b16 [%0], {%1,%2,%3,%4};" ::"r"(dst), "r"(o[0]), "r"(o[1]), "r"(o[2]), "r"(o[3])
                 : "memory");
  }
  asm volatile("fence.proxy.async.shared::cta;" ::: "memory");
  NB_SYNC(NB_PREP, 256);
  if (k == 0 && elect_one()) {
    asm volatile("cp.async.bulk.global.shared::cta.bulk_group [%0], [%1], 3072;" ::"l"(scr->w + t * 192), "r"(st) : "memory");
    asm volatile("cp.async.bulk.global.shared::cta.bulk_group [%0], [%1], 16;" ::"l"(scr->nrm + t), "r"(st + 3072) : "memory");
    asm volatile("cp.async.bulk.commit_group;" ::: "memory");
    asm volatile("cp.async.bulk.wait_group 0;" ::: "memory");
    asm volatile("red.relaxed.gpu.global.add.u32 [%0], 1;" ::"l"(&scr->done) : "memory");
  }
}

__device__ __forceinline__ uint32_t mlp_role(const MlpCtx& m0) {
  MlpCtx m = m0;
  const uint32_t bad = m.sb + OFF_BAD + 4 * (4 * m.wg + m.warp);
  asm volatile("st.shared.b32 [%0], 0;" ::"r"(bad) : "memory");
  __syncwarp();
  asm volatile("barrier.cluster.wait.aligned;" ::: "memory");
  if ((m.sb & 0x3FFFF) != 1024) mark_bad(bad, 0xffffu);
  constexpr uint64_t dW1 = (uint64_t)((1024 + OFF_W1) >> 4) | ((uint64_t)8 << 16) | ((uint64_t)16 << 32);
  constexpr uint64_t dW2 = dW1 + (OFF_W2 >> 4);
  uint32_t A1[24], g[24], d[24], cn[24], D2[24];
  float st[8];
  uint32_t mask;
  if (m.wg & m.rank) tok_idle<3>();
  else if (m.wg) tok_idle<0>();
  else if (m.rank) tok_idle<1>();
  ln_wait(m, 0);
  ln_load(m, cn);
  ln_sums(cn, st);
  ln_shfl(st, 1);
  ln_release(m);
  ln_fold(st);
  ln_shfl(st, 2);
  ln_restat(ln_stats(st), cn, st, bad, 0, m.zero);
  ln_apply(A1, cn, st);
  const int lane = threadIdx.x & 31;
  mbar_wait(m.sb + BAR_W, 0);
  float n1, n2;
  int s;
  asm volatile("ld.shared.b32 %0, [%1];" : "=r"(s) : "r"(m.sb + OFF_NRM + 4) : "memory");
  asm volatile("ld.shared.f32 %0, [%1];" : "=f"(n1) : "r"(m.sb + OFF_NRM + 16 * min(lane, 23)) : "memory");
  asm volatile("ld.shared.f32 %0, [%1];" : "=f"(n2) : "r"(m.sb + OFF_NRM + 384 + 16 * min(lane, 23)) : "memory");
  if (m.wg & m.rank) tok_idle<0>();
  if (m.wg) tok_idle<1>();
  {
    uint32_t d0[24];
    WG_FENCE();
    tok_wait<2>();
    tok_next<2>();
    gemm6<true, 192>(d0, A1, dW1);
    tok_pass(); PIN();
    if (lane >= 24) n1 = n2 = 0.f;
#pragma unroll
    for (int o = 16; o; o >>= 1) {
      n1 += __shfl_xor_sync(0xffffffffu, n1, o);
      n2 += __shfl_xor_sync(0xffffffffu, n2, o);
    }
    const int e1 = norm_exp(n1), e2 = norm_exp(n2), smax = scale_exp(e1, e2);
    if (__any_sync(0xffffffffu, e1 > 12 || e1 < -5 || e2 > 50 || e2 < -50 || s > smax || s < smax - 7)) mark_bad(bad, 0xffffu);
    m.unscale = __shfl_sync(0xffffffffu, ((uint32_t)(127 - s) << 7) * 0x10001u, 0);
    PIN();
    WG_WAIT0(); rfence(d0);
    WG_FENCE();
    tok_wait<3>();
    tok_next<3>();
    gemm6<true, 192>(d, A1, dW1 + CHK);
    tok_pass(); PIN();
    gelu<0, 24>(g, d0);
    PIN();
    mbar_wait(m.sb + BAR_W + 8, 0);
    ln_wait(m, 1);
    WG_WAIT0(); rfence(d);
  }
#define G2(INIT, a, j)                      \
  WG_FENCE();                               \
  tok_wait<j>();                            \
  gemm6<INIT, 192>(D2, a, dW2 + (j) * CHK); \
  tok_next<j>(); PIN();
#define G1(dst, j, P)                       \
  P(); WG_WAIT0(); rfence(D2);              \
  WG_FENCE();                               \
  gemm6<true, 192>(dst, A1, dW1 + (j) * CHK); \
  tok_pass(); P();
#define ROUND_END(dst, j)                   \
  PIN(); WG_WAIT0(); rfence(dst);
#define GA 11
#define GB 13
#define GC 13
#define GD 11
#pragma unroll 1
  for (int i = 0;; i++) {
    uint32_t g1[24], d2[24], g2[24], d3[24], g3[24], d0[24];
    ln_load(m, cn);
    PIN();
    G2(true, g, 0)
    gelu<0, GA>(g1, d);
    G1(d2, 2, PIN)
    ln_sums(cn, st);
    gelu<GA, 24>(g1, d);
    PIN();
    ln_shfl(st, 1);
    ROUND_END(d2, 0)

    G2(false, g1, 1)
    ln_fold(st);
    gelu<0, GB>(g2, d2);
    PIN();
    ln_shfl(st, 2);
    G1(d3, 3, PIN)
    const bool ok = ln_stats(st);
    gelu<GB, 24>(g2, d2);
    PIN();
    ln_restat(ok, cn, st, bad, i + 1, m.zero);
    ROUND_END(d3, 1)

    if (i == 15) {
      G2(false, g2, 2)
      tok_pass();
      gelu<0, 16>(g3, d3);
      PIN();
      x_load(m, cn);
      asm volatile("ld.shared.b32 %0, [%1];" : "=r"(mask) : "r"(bad) : "memory");
      ROUND_END(D2, 2)
      WG_FENCE();
      tok_wait<3>();
#pragma unroll
      for (int k = 1; k < 5; k++) wg_acc(D2, &g3[4 * k], dW2 + 3 * CHK + k * 192);
      WG_COMMIT();
      tok_next<3>();
      tok_pass();
      PIN();
      gelu<16, 24>(g3, d3);
      ROUND_END(D2, 2)
      WG_FENCE();
      wg_acc(D2, &g3[20], dW2 + 3 * CHK + 5 * 192);
      wg_acc(D2, &g3[0], dW2 + 3 * CHK);
      WG_COMMIT();
      WG_WAIT0(); rfence(D2);
      epilogue<true>(m, D2, cn);
      break;
    }
    G2(false, g2, 2)
    ln_apply(A1, cn, st);
    PIN();
    gelu<0, GC>(g3, d3);
    G1(d0, 0, PIN)
    gelu<GC, 24>(g3, d3);
    PIN();
    x_load(m, cn);
    ROUND_END(d0, 2)

    G2(false, g3, 3)
    gelu<0, GD>(g, d0);
    G1(d, 1, PIN)
    epilogue<false>(m, D2, cn);
    gelu<GD, 24>(g, d0);
    PIN();
    asm volatile("fence.proxy.async.shared::cta;" ::: "memory");
    ROUND_END(d, 3)
  }
  if (m.wg == 0) { tok_idle<0>(); tok_idle<1>(); }
  return __reduce_or_sync(0xffffffffu, mask & 0xffffu);
}

struct ConvCtx {
  uint32_t sb;
  uint32_t a0, a_c;
  uint32_t peer_off;
  int rank, v, c0, r0, dir, zero;
  const CUtensorMap* tm;
  Scratch* scr;
  const uint8_t* xsrc;
  uint8_t* optr;
};

__device__ __forceinline__ void raw_refill(const ConvCtx& c, int s) {
  if (s + 4 < NSTEP && elect_one())
    tma_raw(c.sb + OFF_RAW + (s & 3) * RAW_BYTES, c.tm, c.rank, c.c0 / 2 - 2, c.r0 + c.dir * (2 * s + 5), c.sb + BAR_RAW + 8 * (s & 3));
}
__device__ __forceinline__ void step_ready(const ConvCtx& c, int s) {
  const int nx = (s + 1) & 3, par = ((s + 1) >> 2) & 1;
  if (s + 1 < NSTEP) mbar_wait(c.sb + BAR_RAW + 8 * nx, par);
  if (s >= 7 && s < NSTEP) mbar_wait(c.sb + BAR_CEMPTY + 8 * (2 * (nx & 1) + (nx >> 1)), par);
}

__device__ __forceinline__ void c_release(const ConvCtx& c, uint32_t w) {
  const uint32_t e = c.sb + BAR_CEMPTY + 8 * (2 * c.rank + w);
  asm volatile(
      "{\n.reg .pred p;\nelect.sync _|p, 0xffffffff;\n"
      "@p mbarrier.arrive.expect_tx.shared::cta.b64 _, [%0], %3;\n"
      "@p mbarrier.arrive.shared::cluster.b64 _, [%1], 4;\n"
      "@p mbarrier.arrive.shared::cluster.b64 _, [%2], 4;\n}\n" ::"r"(c.sb + BAR_CFULL + 8 * w),
      "r"(e), "r"(e + c.peer_off), "n"(CTX)
      : "memory");
}

__device__ __forceinline__ void prod_rows(const ConvCtx& c) {
#pragma unroll 1
  for (int s = 0; s < NROUND + SIGMA + c.rank; s++) {
    if (s < SIGMA) NB_SYNC(NB_PLAN, 192);
    else NB_SYNC(NB_OPEN, 448);
    raw_refill(c, s);
  }
}
__device__ __forceinline__ void prod_checks(const ConvCtx& c) {
  asm volatile("barrier.cluster.wait.aligned;" ::: "memory");
#pragma unroll 1
  for (int s = 0; s < NROUND + SIGMA + c.rank; s++) {
    const int r = s - SIGMA - c.rank;
    const int u = (r & 1) ? (r >> 1) - 1 : (r >> 1) + 2;
    step_ready(c, s);
    if (s < 16) TP(c.scr, 100 + s);
    if (u >= ((r & 1) ? 0 : 4) && u < 32) mbar_wait(c.sb + ((r & 1) ? BAR_XFULL : BAR_CFULL) + 8 * (u & 1), (u >> 1) & 1);
    if (s < SIGMA) NB_SYNC(NB_PLAN, 192);
    else NB_SYNC(NB_OPEN, 448);
    TP(c.scr, s);
    if (r == 3) TC(c.scr, 1);
    if (r == 55) TC(c.scr, 2);
  }
}
__device__ __forceinline__ void prod_tiles(const ConvCtx& c) {
  asm volatile("barrier.cluster.wait.aligned;" ::: "memory");
#pragma unroll 1
  for (int n = 1; n < 33; n++) {
    const uint32_t w = (n + 1) & 1;
    const uint32_t buf = c.sb + OFF_XRES + w * 12288;
    NB_SYNC(NB_PROD, 160);
    if (n < 29) c_release(c, w);
    if (n >= 3) {
      uint8_t* dst = c.optr + (n - 3) * c.dir * (4 * IMG * CH * 2);
      if (elect_one()) {
        asm volatile("cp.async.bulk.global.shared::cta.bulk_group [%0], [%1], 6144;" ::"l"(dst), "r"(buf) : "memory");
        asm volatile("cp.async.bulk.global.shared::cta.bulk_group [%0], [%1], 6144;" ::"l"(dst + IMG * CH * 2), "r"(buf + 6144) : "memory");
        asm volatile("cp.async.bulk.commit_group;" ::: "memory");
        asm volatile("cp.async.bulk.wait_group.read 0;" ::: "memory");
      }
      __syncwarp();
    }
    {
      const uint8_t* src = c.xsrc + (n - 1) * c.dir * (4 * IMG * CH * 2);
      if (elect_one()) {
        mbar_expect(c.sb + BAR_XFULL + 8 * w, 12288);
        bulk_load_last(buf, src, 6144, c.sb + BAR_XFULL + 8 * w);
        bulk_load_last(buf + 6144, src + IMG * CH * 2, 6144, c.sb + BAR_XFULL + 8 * w);
      }
    }
  }
  asm volatile("cp.async.bulk.wait_group 0;" ::: "memory");
}

template <int LO, int HI>
__device__ __forceinline__ void conv_ld8(uint32_t a0, uint32_t (&r)[6][6]) {
  const uint32_t a2 = a0 ^ (16 | ((a0 >> 2) & 32));
  const uint32_t a[3] = {a0, (a0 & 64) ? a2 : a0, a2};
#pragma unroll
  for (int j = LO; j < HI; j++)
    asm volatile("ld.shared.v4.b32 {%0,%1,%2,%3}, [%4];"
                 : "=r"(r[j][0]), "=r"(r[j][1]), "=r"(r[j][2]), "=r"(r[j][3])
                 : "r"(a[j >> 1] + (j >> 1) * 64 + (j & 1) * RAW_PA)
                 : "memory");
}
__device__ __forceinline__ void conv_ld4(uint32_t a0, uint32_t stage, int v, uint32_t (&r)[6][6]) {
  const uint32_t ab = ((a0 >> 1) & ~31u) + (stage / 2 + 2 * RAW_PA + 8 * v);
#pragma unroll
  for (int j = 0; j < 6; j++) {
    uint32_t a = ab + (j >> 1) * 32;
    asm volatile("ld.shared.v2.b32 {%0,%1}, [%2];" : "=r"(r[j][4]), "=r"(r[j][5]) : "r"(a + (j & 1) * RAW_PB) : "memory");
  }
}
template <int LO, int HI>
__device__ __forceinline__ void conv_frags(uint32_t zero, const uint32_t (&r)[6][6], uint32_t (&A)[12][4]) {
#pragma unroll
  for (int ch = LO; ch < HI; ch++) {
    const uint32_t sel = (ch & 1) ? 0x7632 : 0x5410;
    A[ch][0] = __byte_perm(r[0][ch >> 1], r[1][ch >> 1], sel);
    A[ch][1] = __byte_perm(r[2][ch >> 1], r[3][ch >> 1], sel);
    A[ch][2] = A[ch][1] ^ zero;
    A[ch][3] = __byte_perm(r[4][ch >> 1], r[5][ch >> 1], sel);
    rfence(A[ch]);
  }
}
__device__ __forceinline__ void hmma_acc(uint32_t (&v)[4], const uint32_t (&a)[4], const uint32_t* b) {
  asm volatile("mma.sync.aligned.m16n8k16.row.col.f32.bf16.bf16.f32 {%0,%1,%2,%3}, {%4,%5,%6,%7}, {%8,%9}, {%0,%1,%2,%3};"
               : "+r"(v[0]), "+r"(v[1]), "+r"(v[2]), "+r"(v[3])
               : "r"(a[0]), "r"(a[1]), "r"(a[2]), "r"(a[3]), "r"(b[0]), "r"(b[1]));
}
__device__ __forceinline__ void hmma_new(uint32_t (&a)[4], const uint32_t* b) {
  asm volatile("mma.sync.aligned.m16n8k16.row.col.f32.bf16.bf16.f32 {%0,%1,%2,%3}, {%0,%1,%2,%3}, {%4,%5}, {%6,%6,%6,%6};"
               : "+r"(a[0]), "+r"(a[1]), "+r"(a[2]), "+r"(a[3])
               : "r"(b[0]), "r"(b[1]), "f"(0.f));
}

#define EARLY 6
__device__ __forceinline__ void conv_send(bool local, const uint32_t (&pk)[12], uint32_t dst, uint32_t bar) {
  if (local) {
#pragma unroll
    for (int q = 0; q < 3; q++)
      asm volatile("st.shared.v4.b32 [%0], {%1,%2,%3,%4};" ::"r"(dst + q * 2048), "r"(pk[4 * q]), "r"(pk[4 * q + 1]), "r"(pk[4 * q + 2]), "r"(pk[4 * q + 3])
                   : "memory");
    asm volatile("{\n.reg .pred p;\nelect.sync _|p, 0xffffffff;\n@p mbarrier.arrive.shared::cta.b64 _, [%0];\n}\n" ::"r"(bar) : "memory");
  } else {
#pragma unroll
    for (int q = 0; q < 3; q++)
      asm volatile("st.async.weak.shared::cluster.mbarrier::complete_tx::bytes.v4.b32 [%0], {%1,%2,%3,%4}, [%5];" ::"r"(dst + q * 2048),
                   "r"(pk[4 * q]), "r"(pk[4 * q + 1]), "r"(pk[4 * q + 2]), "r"(pk[4 * q + 3]), "r"(bar)
                   : "memory");
  }
}
template <int S2, bool GATED>
__device__ __forceinline__ void conv_step(const ConvCtx& c, int s, uint32_t (&K)[12], uint32_t (&V)[12][4], const uint32_t (&B)[12][4],
                                          uint32_t (&A)[12][4]) {
  const int nx = ((s + 1) & 2) | (S2 ^ 1);
  uint32_t r[6][6], pk[12];
  const uint32_t a0 = c.a0 + nx * RAW_BYTES;
  if (GATED) NB_SYNC(NB_OPEN, 448);
  else NB_SYNC(NB_PLAN, 192);
  conv_ld4(a0, c.sb + OFF_RAW + nx * RAW_BYTES, c.v, r);
  if (GATED) PIN();
#pragma unroll
  for (int ch = 0; ch < 12; ch++) hmma_acc(V[11 - ch], A[11 - ch], &B[11 - ch][2]);
#pragma unroll
  for (int ch = 0; ch < 12 - EARLY; ch++) hmma_new(A[ch], &B[ch][0]);
  const uint32_t zero = GATED ? c.zero & clock_pin() : c.zero;
  if (GATED) NB_ARRIVE(NB_CLOSE, 256);
#pragma unroll
  for (int ch = 12 - EARLY; ch < 12; ch++) hmma_new(A[ch], &B[ch][0]);
  if (GATED) PIN();
  const bool local = (S2 ^ 1) == c.rank;
  const uint32_t off = local ? 0u : c.peer_off;
  const uint32_t dst = c.a_c + off + (nx >> 1) * C_BYTES;
  const uint32_t bar = c.sb + off + BAR_CFULL + 8 * (nx >> 1);
#pragma unroll
  for (int q = 0; q < 12; q++) {
    const int ch = q & ~1, h = 2 * (q & 1);
    pk[q] = h_add(K[q], pack_f16(__uint_as_float(V[ch][h + 1]), __uint_as_float(V[ch + 1][h])));
  }
#pragma unroll
  for (int q = 0; q < 12; q++) {
    const int ch = q & ~1, h = 2 * (q & 1);
    K[q] = pack_f16(__uint_as_float(V[ch][h]), __uint_as_float(V[ch + 1][h + 1]));
  }
  rfence(K);
  rfence(pk);
  PIN();
  conv_ld8<0, 4>(a0, r);
  if (GATED || s >= 3) conv_send(local, pk, dst, bar);
  conv_frags<8, 12>(zero, r, V);
  PIN();
  conv_ld8<4, 6>(a0, r);
  conv_frags<0, 8>(zero, r, V);
  PIN();
}

__device__ __forceinline__ void conv_role(ConvCtx c) {
  const int lane = laneid(), g = lane >> 2, t = lane & 3;
  const int u = (t >> 1) * 19 + 2 * (g + (t & 1));
  c.a0 = c.sb + OFF_RAW + u * 64 + ((c.v ^ (u >> 1)) & 3) * 16;
  c.a_c = c.sb + OFF_C + 6144 * c.rank + 512 * c.v + ((lane + 2 * c.v) & 31) * 16;
  uint32_t B[12][4];
  {
    const int dc = (g >> 1) & 1, ro = g >> 2, rk = t >> 1;
    const int i0 = (c.dir > 0 ? 4 * (g & 1) : 6 - 4 * (g & 1)) + rk - ro, j0 = 4 * (t & 1) - dc;
    const uint32_t base = c.sb + OFF_XRES + (i0 * 7 + j0) * 192;
    asm volatile("barrier.cluster.wait.aligned;" ::: "memory");
    mbar_wait(c.sb + BAR_W + 48, 0);
#pragma unroll
    for (int b = 0; b < 2; b++) {
      uint32_t w[4][6];
#pragma unroll
      for (int k = 0; k < 4; k++) {
        const int ok = (unsigned)(i0 + 2 * b * c.dir) < 7u && (unsigned)(j0 + k) < 7u;
#pragma unroll
        for (int q = 0; q < 6; q++) w[k][q] = 0;
        asm volatile(
            "{\n.reg .pred p;\nsetp.ne.s32 p, %8, 0;\n@p ld.shared.v4.b32 {%0,%1,%2,%3}, [%6];\n@p ld.shared.v2.b32 {%4,%5}, [%7];\n}\n"
            : "+r"(w[k][0]), "+r"(w[k][1]), "+r"(w[k][2]), "+r"(w[k][3]), "+r"(w[k][4]), "+r"(w[k][5])
            : "r"(base + (b * 14 * c.dir + k) * 192 + 128 * c.rank + 16 * c.v), "r"(base + (b * 14 * c.dir + k) * 192 + 64 + 32 * c.rank + 8 * c.v), "r"(ok)
            : "memory");
      }
#pragma unroll
      for (int q = 0; q < 6; q++) {
        B[2 * q][2 * b] = __byte_perm(w[0][q], w[1][q], 0x5410);
        B[2 * q][2 * b + 1] = __byte_perm(w[2][q], w[3][q], 0x5410);
        B[2 * q + 1][2 * b] = __shfl_xor_sync(0xffffffffu, __byte_perm(w[0][q], w[1][q], 0x7632), 4);
        B[2 * q + 1][2 * b + 1] = __shfl_xor_sync(0xffffffffu, __byte_perm(w[2][q], w[3][q], 0x7632), 4);
      }
    }
  }
  uint32_t K1[12], K2[12], V[12][4];
#pragma unroll
  for (int ch = 0; ch < 12; ch++)
    asm volatile("" : "=r"(K1[ch]), "=r"(K2[ch]), "=r"(V[ch][0]), "=r"(V[ch][1]), "=r"(V[ch][2]), "=r"(V[ch][3]));
  uint32_t A[12][4], r[6][6];
  mbar_wait(c.sb + BAR_RAW, 0);
  conv_ld8<0, 6>(c.a0, r);
  conv_ld4(c.a0, c.sb + OFF_RAW, c.v, r);
  conv_frags<0, 12>(c.zero, r, A);
  PIN();
  NB_ARRIVE(NB_CLOSE, 256);
#pragma unroll 1
  for (int s = 0; s < SIGMA; s += 2) {
    conv_step<0, false>(c, s, K1, V, B, A);
    conv_step<1, false>(c, s + 1, K2, A, B, V);
  }
#pragma unroll 1
  for (int s = SIGMA;; s += 2) {
    conv_step<0, true>(c, s, K1, V, B, A);
    if (s == NSTEP - 1) break;
    conv_step<1, true>(c, s + 1, K2, A, B, V);
  }
#pragma unroll 1
  for (int r = NSTEP - SIGMA - c.rank; r < NROUND - 1; r++) {
    NB_SYNC(NB_OPEN, 448);
    NB_ARRIVE(NB_CLOSE, 256);
  }
  NB_SYNC(NB_OPEN, 448);
}

struct TMaps { CUtensorMap m[2]; };

__global__ void __cluster_dims__(2, 1, 1) __launch_bounds__(512, 1)
convnext_kernel(const __grid_constant__ TMaps tms, const __nv_bfloat16* __restrict__ x, const __nv_bfloat16* __restrict__ dw,
                const __nv_bfloat16* __restrict__ w1, const __nv_bfloat16* __restrict__ w2, __nv_bfloat16* __restrict__ out,
                Scratch* scr, int zero) {
  extern __shared__ __align__(1024) uint8_t smem[];
  const uint32_t sb = (uint32_t)__cvta_generic_to_shared(smem);
  const int tid = threadIdx.x, lane = tid & 31;
  const int wid = __shfl_sync(0xffffffffu, tid >> 5, 0);
  const int rank = blockIdx.x & 1, cl = blockIdx.x >> 1;
  const int dir = (cl & 16) ? 1 : -1;
  const int c0 = (cl & 15) * 32, r0 = (cl >> 4) * 128 + (dir > 0 ? 0 : 126);
  const uint32_t peer_off = mapa(sb, rank ^ 1) - sb;

  if (wid == 12 && elect_one()) {
    mbar_init(sb + BAR_W + 48, 1);
#pragma unroll
    for (int i = 0; i < 4; i++) mbar_init(sb + BAR_RAW + 8 * i, 1);
    asm volatile("fence.mbarrier_init.release.cluster;" ::: "memory");
    mbar_expect(sb + BAR_W + 48, 49 * CH * 2);
    bulk_load(sb + OFF_XRES, dw, 49 * CH * 2, sb + BAR_W + 48);
#pragma unroll
    for (int i = 0; i < E0; i++) tma_raw(sb + OFF_RAW + i * RAW_BYTES, tms.m, rank, c0 / 2 - 2, r0 + dir * (2 * i - 3), sb + BAR_RAW + 8 * i);
  }
  if (wid == 14 && elect_one()) {
    asm volatile("cp.async.bulk.prefetch.L2.global [%0], 1152;" ::"l"(reinterpret_cast<const uint8_t*>(rank ? w2 : w1) + cl * 1152) : "memory");
    asm volatile("prefetch.tensormap [%0];" ::"l"(&tms.m[1]) : "memory");
#pragma unroll
    for (int i = 0; i < 3; i++) mbar_init(sb + BAR_W + 8 * i, 1);
#pragma unroll
    for (int i = 0; i < 2; i++) mbar_init(sb + BAR_CFULL + 8 * i, CCNT);
#pragma unroll
    for (int i = 0; i < 4; i++) mbar_init(sb + BAR_CEMPTY + 8 * i, 4);
#pragma unroll
    for (int i = 0; i < 2; i++) mbar_init(sb + BAR_XFULL + 8 * i, 1);
#pragma unroll
    for (int i = 0; i < 2; i++) mbar_expect(sb + BAR_CFULL + 8 * i, CTX);
    asm volatile("fence.mbarrier_init.release.cluster;" ::: "memory");
  }
  __syncwarp();
  asm volatile("barrier.cluster.arrive.relaxed.aligned;" ::: "memory");

  if (wid < 8) {
    if (blockIdx.x < 48) convert_tile(blockIdx.x, wid, reinterpret_cast<const uint4*>(w1), reinterpret_cast<const uint4*>(w2), sb, scr);
    MlpCtx m;
    m.sb = sb; m.wg = wid >> 2; m.warp = wid & 3; m.rank = rank; m.peer_off = peer_off; m.zero = zero;
    m.optr = reinterpret_cast<uint8_t*>(out) + ((size_t)(r0 + dir * (120 + 4 * m.wg + 2 * rank)) * IMG + c0 + 8 * m.warp) * (CH * 2);
    m.caddr = sb + OFF_C + m.wg * C_BYTES + (lane & 3) * 512 + ((m.warp * 8 + (lane >> 2) + 2 * (lane & 3)) & 31) * 16;
    m.xaddr = sb + OFF_XRES + m.wg * 12288 + m.warp * 1536 + ((lane >> 3) & 1) * 6144 + ((lane >> 4) * 4 + ((lane >> 2) & 1)) * 192 + (lane & 3) * 16;
    m.unscale = 0;
    asm volatile("setmaxnreg.inc.sync.aligned.u32 %0;" ::"n"(REG_MLP));
    const uint32_t bad = mlp_role(m);
    TC(scr, 3);
    if (bad) {
      mbar_wait(sb + BAR_W + 16, 0);
      __syncwarp();
      asm volatile("fence.proxy.async;" ::: "memory");
#pragma unroll 1
      for (int i = 0; i < 16; i++)
        if (bad >> i & 1)
          slow_tile(x, dw, w1, w2, out, r0 + dir * (8 * i + 4 * m.wg + 2 * rank), c0 + 8 * m.warp,
                    reinterpret_cast<float*>(smem + OFF_RAW + wid * 2048));
    }
  } else {
    ConvCtx c;
    c.sb = sb; c.rank = rank; c.v = wid - 8; c.c0 = c0; c.r0 = r0; c.dir = dir; c.zero = zero; c.tm = tms.m; c.scr = scr;
    c.peer_off = peer_off;
    c.xsrc = reinterpret_cast<const uint8_t*>(x) + ((size_t)(r0 + 2 * dir * rank) * IMG + c0) * (CH * 2);
    c.optr = reinterpret_cast<uint8_t*>(out) + ((size_t)(r0 + 2 * dir * rank) * IMG + c0) * (CH * 2);
    if (wid < 12) {
      asm volatile("setmaxnreg.inc.sync.aligned.u32 %0;" ::"n"(REG_CONV));
      conv_role(c);
    } else {
      asm volatile("setmaxnreg.dec.sync.aligned.u32 24;");
      if (wid == 15) TC(scr, 0);
      if (wid == 12) {
#pragma unroll 1
        for (int h = E0 - 4; h < 0; h++) raw_refill(c, h);
        prod_rows(c);
      } else if (wid == 15) {
        prod_checks(c);
      } else if (wid == 14) {
#pragma unroll 1
        for (int n = 0; n < (1 << 20); n++) {
          unsigned v;
          __nanosleep(n ? PSL : PS0);
          asm volatile("ld.acquire.gpu.global.u32 %0, [%1];" : "=r"(v) : "l"(&scr->done) : "memory");
          if (__shfl_sync(0xffffffffu, v, 0) >= 48) break;
        }
        TP(scr, 90);
        asm volatile("barrier.cluster.wait.aligned;" ::: "memory");
        asm volatile("fence.proxy.async.global;" ::: "memory");
        if (elect_one()) {
          mbar_expect(sb + BAR_W, 36864 + 768);
          mbar_expect(sb + BAR_W + 8, 110592);
          bulk_load(sb + OFF_NRM, scr->nrm, 768, sb + BAR_W);
        }
        __syncwarp();
#pragma unroll 1
        for (int i = 0; i < 8; i++) {
          if (elect_one()) bulk_load(sb + i * 18432, reinterpret_cast<const uint8_t*>(scr->w) + i * 18432, 18432, sb + BAR_W + (i < 2 ? 0 : 8));
          if (i >= PFIRST) __nanosleep(PACE);
        }
        if (elect_one() && atomicAdd(&scr->seen, 1u) == gridDim.x - 1) { scr->done = 0; scr->seen = 0; }
      } else if (wid == 13) {
        prod_tiles(c);
        __syncwarp();
        if (elect_one()) asm volatile("mbarrier.arrive.shared::cta.b64 _, [%0];" ::"r"(sb + BAR_W + 16) : "memory");
      }
    }
  }
}

typedef CUresult (*EncodeFn)(CUtensorMap*, CUtensorMapDataType, cuuint32_t, void*, const cuuint64_t*, const cuuint64_t*,
                             const cuuint32_t*, const cuuint32_t*, CUtensorMapInterleave, CUtensorMapSwizzle,
                             CUtensorMapL2promotion, CUtensorMapFloatOOBfill);

}

extern "C" void kernel_launch(void* const* d_in, const int* in_sizes, int n_in, void* d_out, int out_size) {
  const __nv_bfloat16* x = (const __nv_bfloat16*)d_in[0];
  const __nv_bfloat16* dw = (const __nv_bfloat16*)d_in[1];
  const __nv_bfloat16* w1 = (const __nv_bfloat16*)d_in[2];
  const __nv_bfloat16* w2 = (const __nv_bfloat16*)d_in[3];
  __nv_bfloat16* out = (__nv_bfloat16*)d_out;

  static EncodeFn encode = nullptr;
  static Scratch* scr = nullptr;
  if (!encode) {
    cudaDriverEntryPointQueryResult st;
    void* fn = nullptr;
    cudaGetDriverEntryPoint("cuTensorMapEncodeTiled", &fn, cudaEnableDefault, &st);
    encode = (EncodeFn)fn;
    cudaGetSymbolAddress((void**)&scr, g_scratch);
    cudaFuncSetAttribute(convnext_kernel, cudaFuncAttributeMaxDynamicSharedMemorySize, SMEM_BYTES);
  }
  TMaps tm;
  cuuint64_t dims[4] = {CH, IMG / 2, IMG, 2};
  cuuint64_t strides[3] = {CH * 4, (cuuint64_t)IMG * CH * 2, CH * 2};
  cuuint32_t es[4] = {1, 1, 1, 1};
  for (int i = 0; i < 2; i++) {
    cuuint32_t box[4] = {i ? 16u : 32u, 19, 2, 1};
    encode(&tm.m[i], CU_TENSOR_MAP_DATA_TYPE_BFLOAT16, 4, (void*)x, dims, strides, box, es, CU_TENSOR_MAP_INTERLEAVE_NONE,
           i ? CU_TENSOR_MAP_SWIZZLE_NONE : CU_TENSOR_MAP_SWIZZLE_64B, PROMO, CU_TENSOR_MAP_FLOAT_OOB_FILL_NONE);
  }
  convnext_kernel<<<128, 512, SMEM_BYTES>>>(tm, x, dw, w1, w2, out, scr, 0);
}
```

```cpp
#include <cuda_runtime.h>
#include <cuda_bf16.h>
#include <cuda.h>
#include <stdint.h>

#define PROMO CU_TENSOR_MAP_L2_PROMOTION_L2_128B
#define CTX 6144
#define CCNT 5
#define PSL 100
#define PS0 1000
#define E0 1
#define PACE 100
#define PFIRST 1
namespace {

constexpr int IMG = 512, CH = 96;
constexpr int NSTEP = 67;
constexpr int SIGMA = 8;
constexpr int NROUND = 68;

constexpr uint32_t OFF_W1 = 0;
constexpr uint32_t OFF_W2 = 73728;
constexpr uint32_t OFF_RAW = 147456;
constexpr uint32_t RAW_PA = 2560, RAW_PB = 1280;
constexpr uint32_t RAW_BYTES = 2 * RAW_PA + 2 * RAW_PB;
constexpr uint32_t RAW_TX = 2 * 38 * 96;
constexpr uint32_t OFF_XRES = OFF_RAW + 4 * RAW_BYTES;
constexpr uint32_t OFF_C = OFF_XRES + 2 * 12288;
constexpr uint32_t C_BYTES = 12288;
constexpr uint32_t OFF_BAR = OFF_C + 2 * C_BYTES;
constexpr uint32_t BAR_RAW = OFF_BAR;
constexpr uint32_t BAR_CFULL = OFF_BAR + 32;
constexpr uint32_t BAR_CEMPTY = OFF_BAR + 48;
constexpr uint32_t BAR_XFULL = OFF_BAR + 80;
constexpr uint32_t BAR_W = OFF_BAR + 96;
constexpr uint32_t OFF_NRM = OFF_XRES + 9472;
constexpr uint32_t OFF_BAD = OFF_BAR + 160;
constexpr uint32_t SMEM_BYTES = OFF_BAD + 32;

struct Scratch {
  uint4 w[2 * 73728 / 16];
  uint4 nrm[48];
  unsigned done, seen;
};
__device__ Scratch g_scratch;

constexpr float GELU_A = 0.32918364f;
constexpr uint32_t GELU_K2 = 0x40d940d9u;

constexpr int NB_CLOSE = 1, NB_SEC = 6  , NB_OPEN = 3, NB_PROD = 2, NB_PLAN = 4, NB_PREP = 5, NB_WG = 8  ;
#define REG_MLP 144
constexpr int REG_CONV = 488 - 2 * REG_MLP;

#define WG_FENCE() asm volatile("wgmma.fence.sync.aligned;" ::: "memory")
#define WG_COMMIT() asm volatile("wgmma.commit_group.sync.aligned;" ::: "memory")
#define WG_WAIT0() asm volatile("wgmma.wait_group.sync.aligned 0;" ::: "memory")
#define WG_WAIT1() asm volatile("wgmma.wait_group.sync.aligned 1;" ::: "memory")
#define PIN() asm volatile("pmevent 0;" ::: "memory")
#define NB_SYNC(id, n) asm volatile("bar.sync %0, %1;" ::"n"(id), "n"(n) : "memory")
#define NB_ARRIVE(id, n) asm volatile("bar.arrive %0, %1;" ::"n"(id), "n"(n) : "memory")

#define TC(scr, k)
#define TP(scr, k)

#define R24(c, d)                                                                                        \
  c(d[0]), c(d[1]), c(d[2]), c(d[3]), c(d[4]), c(d[5]), c(d[6]), c(d[7]), c(d[8]), c(d[9]), c(d[10]),    \
      c(d[11]), c(d[12]), c(d[13]), c(d[14]), c(d[15]), c(d[16]), c(d[17]), c(d[18]), c(d[19]), c(d[20]), \
      c(d[21]), c(d[22]), c(d[23])
#define WG_TXT(sd)                                                                             \
  "wgmma.mma_async.sync.aligned.m64n96k16.f16.f16.f16 "                                        \
  "{%0,%1,%2,%3,%4,%5,%6,%7,%8,%9,%10,%11,%12,%13,%14,%15,%16,%17,%18,%19,%20,%21,%22,%23}, " \
  "{%24,%25,%26,%27}, %28, " sd ", 1, 1, 1;\n"

__device__ __forceinline__ void wg_acc(uint32_t (&d)[24], const uint32_t* a, uint64_t db) {
  asm volatile(WG_TXT("1") : R24("+r", d) : "r"(a[0]), "r"(a[1]), "r"(a[2]), "r"(a[3]), "l"(db));
}
__device__ __forceinline__ void wg_init(uint32_t (&d)[24], const uint32_t* a, uint64_t db) {
  asm volatile(WG_TXT("0") : R24("=r", d) : "r"(a[0]), "r"(a[1]), "r"(a[2]), "r"(a[3]), "l"(db));
}
template <int N>
__device__ __forceinline__ void rfence(uint32_t (&d)[N]) {
#pragma unroll
  for (int i = 0; i < N; i++) asm volatile("" : "+r"(d[i])::"memory");
}
template <bool INIT, int KSTRIDE>
__device__ __forceinline__ void gemm6(uint32_t (&d)[24], const uint32_t (&a)[24], uint64_t db) {
#pragma unroll
  for (int k = 0; k < 6; k++) {
    if (INIT && k == 0) wg_init(d, &a[0], db);
    else wg_acc(d, &a[4 * k], db + k * KSTRIDE);
  }
  WG_COMMIT();
}

__device__ __forceinline__ void mbar_init(uint32_t bar, uint32_t cnt) {
  asm volatile("mbarrier.init.shared::cta.b64 [%0], %1;" ::"r"(bar), "r"(cnt) : "memory");
}
__device__ __forceinline__ void mbar_expect(uint32_t bar, uint32_t bytes) {
  asm volatile("mbarrier.arrive.expect_tx.shared::cta.b64 _, [%0], %1;" ::"r"(bar), "r"(bytes) : "memory");
}
__device__ __forceinline__ void mbar_arrive_cluster(uint32_t bar) {
  asm volatile("mbarrier.arrive.shared::cluster.b64 _, [%0];" ::"r"(bar) : "memory");
}
__device__ __forceinline__ bool mbar_try(uint32_t bar, uint32_t parity) {
  uint32_t ok;
  asm volatile(
      "{\n.reg .pred p;\nmbarrier.try_wait.parity.shared::cta.b64 p, [%1], %2;\nselp.u32 %0, 1, 0, p;\n}\n"
      : "=r"(ok)
      : "r"(bar), "r"(parity)
      : "memory");
  return ok;
}
__device__ __forceinline__ bool mbar_test(uint32_t bar, uint32_t parity) {
  uint32_t ok;
  asm volatile(
      "{\n.reg .pred p;\nmbarrier.test_wait.parity.shared::cta.b64 p, [%1], %2;\nselp.u32 %0, 1, 0, p;\n}\n"
      : "=r"(ok)
      : "r"(bar), "r"(parity)
      : "memory");
  return ok;
}
__device__ __forceinline__ void mbar_wait(uint32_t bar, uint32_t parity) {
  if (__builtin_expect(mbar_try(bar, parity), 1)) return;
#pragma unroll 1
  for (uint32_t n = 0; n < (1u << 16) && !mbar_try(bar, parity); n++) {}
}
__device__ __forceinline__ uint32_t mapa(uint32_t addr, uint32_t rank) {
  uint32_t r;
  asm("mapa.shared::cluster.u32 %0, %1, %2;" : "=r"(r) : "r"(addr), "r"(rank));
  return r;
}
__device__ __forceinline__ void tma_raw(uint32_t dst, const CUtensorMap* tm, int rank, int w2, int h, uint32_t bar) {
  mbar_expect(bar, RAW_TX);
#pragma unroll
  for (int k = 0; k < 4; k++) {
    const int e = k & 1;
    asm volatile(
        "cp.async.bulk.tensor.4d.shared::cluster.global.mbarrier::complete_tx::bytes [%0], [%1, {%2, %3, %4, %5}], [%6];"
        ::"r"(dst + (k < 2 ? e * RAW_PA : 2 * RAW_PA + e * RAW_PB)), "l"(tm + (k >> 1)), "r"(k < 2 ? 64 * rank : 32 + 16 * rank), "r"(w2 + e),
        "r"(h), "r"(1 - e), "r"(bar)
        : "memory");
  }
}
__device__ __forceinline__ void bulk_load(uint32_t dst, const void* src, uint32_t bytes, uint32_t bar) {
  asm volatile("cp.async.bulk.shared::cluster.global.mbarrier::complete_tx::bytes [%0], [%1], %2, [%3];" ::"r"(dst),
               "l"(src), "r"(bytes), "r"(bar)
               : "memory");
}
__device__ __forceinline__ void bulk_load_last(uint32_t dst, const void* src, uint32_t bytes, uint32_t bar) {
  asm volatile(
      "{\n.reg .b64 pol;\ncreatepolicy.fractional.L2::evict_first.b64 pol, 1.0;\n"
      "cp.async.bulk.shared::cluster.global.mbarrier::complete_tx::bytes.L2::cache_hint [%0], [%1], %2, [%3], pol;\n}\n" ::"r"(dst),
      "l"(src), "r"(bytes), "r"(bar)
      : "memory");
}
__device__ __forceinline__ uint32_t pack_bf16(float lo, float hi) {
  uint32_t r;
  asm("cvt.rn.bf16x2.f32 %0, %1, %2;" : "=r"(r) : "f"(hi), "f"(lo));
  return r;
}
__device__ __forceinline__ uint32_t pack_f16(float lo, float hi) {
  uint32_t r;
  asm("cvt.rn.f16x2.f32 %0, %1, %2;" : "=r"(r) : "f"(hi), "f"(lo));
  return r;
}
__device__ __forceinline__ float bf_lo(uint32_t v) { return __uint_as_float(v << 16); }
__device__ __forceinline__ float bf_hi(uint32_t v) { return __uint_as_float(v & 0xffff0000u); }
__device__ __forceinline__ uint32_t bf_add(uint32_t a, uint32_t b) {
  uint32_t r;
  asm("add.rn.bf16x2 %0, %1, %2;" : "=r"(r) : "r"(a), "r"(b));
  return r;
}
__device__ __forceinline__ uint32_t bf_mul(uint32_t a, uint32_t b) {
  uint32_t r;
  asm("mul.rn.bf16x2 %0, %1, %2;" : "=r"(r) : "r"(a), "r"(b));
  return r;
}
__device__ __forceinline__ uint32_t bf_fma(uint32_t a, uint32_t b, uint32_t c) {
  uint32_t r;
  asm("fma.rn.bf16x2 %0, %1, %2, %3;" : "=r"(r) : "r"(a), "r"(b), "r"(c));
  return r;
}

__device__ __forceinline__ uint32_t h_add(uint32_t a, uint32_t b) {
  uint32_t r;
  asm("add.rn.f16x2 %0, %1, %2;" : "=r"(r) : "r"(a), "r"(b));
  return r;
}
__device__ __forceinline__ uint32_t h_mul(uint32_t a, uint32_t b) {
  uint32_t r;
  asm("mul.rn.f16x2 %0, %1, %2;" : "=r"(r) : "r"(a), "r"(b));
  return r;
}
__device__ __forceinline__ uint32_t h_fma(uint32_t a, uint32_t b, uint32_t c) {
  uint32_t r;
  asm("fma.rn.f16x2 %0, %1, %2, %3;" : "=r"(r) : "r"(a), "r"(b), "r"(c));
  return r;
}
__device__ __forceinline__ float h_sum(uint32_t v) {
  float lo, hi;
  asm("{\n.reg .b16 l, h;\nmov.b32 {l, h}, %2;\ncvt.f32.f16 %0, l;\ncvt.f32.f16 %1, h;\n}\n" : "=f"(lo), "=f"(hi) : "r"(v));
  return lo + hi;
}
__device__ __forceinline__ void lds128(uint32_t (&v)[4], uint32_t a) {
  asm volatile("ld.shared.v4.b32 {%0,%1,%2,%3}, [%4];" : "=r"(v[0]), "=r"(v[1]), "=r"(v[2]), "=r"(v[3]) : "r"(a) : "memory");
}

template <int LO, int HI>
__device__ __forceinline__ void gelu(uint32_t (&o)[24], const uint32_t (&d)[24]) {
#pragma unroll
  for (int qq = LO; qq < HI; qq++) {
    const int q = (qq + 4) % 24;
    uint32_t t, u;
    asm("fma.rn.f16x2 %0, %1, %1, %2;" : "=r"(t) : "r"(d[q]), "r"(GELU_K2));
    asm("mul.rn.f16x2 %0, %1, %2;" : "=r"(u) : "r"(d[q]), "r"(t));
    asm("tanh.approx.f16x2 %0, %1;" : "=r"(t) : "r"(u));
    asm("fma.rn.f16x2 %0, %1, %2, %1;" : "=r"(o[q]) : "r"(d[q]), "r"(t));
  }
}

__device__ __forceinline__ uint32_t laneid() {
  uint32_t l;
  asm volatile("mov.u32 %0, %%laneid;" : "=r"(l));
  return l;
}

__device__ __forceinline__ bool elect_one() {
  uint32_t p;
  asm volatile("{\n.reg .pred p;\nelect.sync _|p, 0xffffffff;\nselp.u32 %0, 1, 0, p;\n}\n" : "=r"(p));
  return p;
}

__device__ __forceinline__ uint32_t clock_pin() {
  uint32_t t;
  asm volatile("mov.u32 %0, %%clock;" : "=r"(t)::"memory");
  return t;
}

struct MlpCtx {
  uint32_t sb;
  uint32_t caddr;
  uint32_t xaddr;
  uint32_t unscale;
  uint32_t peer_off;
  int wg, warp, rank, zero;
  uint8_t* optr;
};

__device__ __forceinline__ void ln_wait(const MlpCtx& m, int i) { mbar_wait(m.sb + BAR_CFULL + 8 * m.wg, i & 1); }
__device__ __forceinline__ void ln_load(const MlpCtx& m, uint32_t (&c)[24]) {
#pragma unroll
  for (int p = 0; p < 6; p++)
    asm volatile("ld.shared.v4.b32 {%0,%1,%2,%3}, [%4];"
                 : "=r"(c[4 * p]), "=r"(c[4 * p + 1]), "=r"(c[4 * p + 2]), "=r"(c[4 * p + 3])
                 : "r"(m.caddr + p * 2048)
                 : "memory");
}
__device__ __forceinline__ void ln_shfl(float (&st)[8], int mask) {
#pragma unroll
  for (int k = 0; k < 4; k++) st[4 + k] = __shfl_xor_sync(0xffffffffu, st[k], mask);
}
__device__ __forceinline__ void ln_fold(float (&st)[8]) {
#pragma unroll
  for (int k = 0; k < 4; k++) st[k] += st[4 + k];
}
__device__ __forceinline__ void ln_sums(const uint32_t (&c)[24], float (&st)[8]) {
#pragma unroll
  for (int r = 0; r < 2; r++) {
    uint32_t s0 = h_add(c[r], c[r + 2]), s1 = h_add(c[r + 4], c[r + 6]), s2 = h_add(c[r + 8], c[r + 10]);
    uint32_t s3 = h_add(c[r + 12], c[r + 14]), s4 = h_add(c[r + 16], c[r + 18]), s5 = h_add(c[r + 20], c[r + 22]);
    s0 = h_add(s0, s1); s2 = h_add(s2, s3); s4 = h_add(s4, s5);
    st[r] = h_sum(h_add(h_add(s0, s2), s4));
    uint32_t q0 = h_mul(c[r], c[r]), q1 = h_mul(c[r + 2], c[r + 2]);
#pragma unroll
    for (int p = 2; p < 12; p += 2) {
      q0 = h_fma(c[2 * p + r], c[2 * p + r], q0);
      q1 = h_fma(c[2 * p + 2 + r], c[2 * p + 2 + r], q1);
    }
    st[2 + r] = h_sum(h_add(q0, q1));
  }
}
__device__ __forceinline__ void ln_release(const MlpCtx& m) {
  const uint32_t e = m.sb + BAR_CEMPTY + 8 * (2 * m.rank + m.wg);
  asm volatile(
      "{\n.reg .pred p, q;\nelect.sync _|p, 0xffffffff;\nsetp.eq.and.s32 q, %3, 0, p;\n"
      "@q mbarrier.arrive.expect_tx.shared::cta.b64 _, [%0], %4;\n"
      "@p mbarrier.arrive.shared::cluster.b64 _, [%1];\n"
      "@p mbarrier.arrive.shared::cluster.b64 _, [%2];\n}\n" ::"r"(m.sb + BAR_CFULL + 8 * m.wg),
      "r"(e), "r"(e + m.peer_off), "r"(m.warp), "n"(CTX)
      : "memory");
}
__device__ __forceinline__ bool ln_stats(float (&st)[8]) {
  bool ok = true;
#pragma unroll
  for (int r = 0; r < 2; r++) {
    const float nm = (st[r] + st[4 + r]) * (-1.0f / 96.0f);
    const float e2 = fmaf(st[2 + r] + st[6 + r], 1.0f / 96.0f, 1e-5f);
    float rs;
    asm("rsqrt.approx.ftz.f32 %0, %1;" : "=f"(rs) : "f"(fmaf(-nm, nm, e2)));
    ok = ok && (rs * rs * e2 <= 17.0f) && (e2 >= 1.001e-5f);
    const float rr = rs * GELU_A, dd = rr * nm;
    st[r] = __uint_as_float(pack_f16(rr, rr));
    st[2 + r] = __uint_as_float(pack_f16(dd, dd));
  }
  return ok;
}
__device__ __forceinline__ void mark_bad(uint32_t addr, uint32_t bits) {
  asm volatile("{\n.reg .pred p;\nelect.sync _|p, 0xffffffff;\n@p red.shared.or.b32 [%0], %1;\n}\n" ::"r"(addr), "r"(bits) : "memory");
  __syncwarp();
}
__device__ __forceinline__ void ln_restat(bool ok, const uint32_t (&c)[24], float (&st)[8], uint32_t bad, int i,
                                          uint32_t zero) {
  if (__builtin_expect(__any_sync(0xffffffffu, !ok), 0)) {
#pragma unroll
    for (int r = 0; r < 2; r++) {
      float nm = 0.f, var = 0.f;
#pragma unroll
      for (int p = 0; p < 12; p++) {
        nm += h_sum(c[2 * p + r] ^ zero);
        if (p % 3 == 2) { asm volatile("" : "+f"(nm)); PIN(); }
      }
      nm += __shfl_xor_sync(0xffffffffu, nm, 1);
      nm += __shfl_xor_sync(0xffffffffu, nm, 2);
      nm *= -1.0f / 96.0f;
#pragma unroll
      for (int p = 0; p < 12; p++) {
        float lo, hi;
        asm volatile("{\n.reg .b16 l, h;\nmov.b32 {l, h}, %2;\ncvt.f32.f16 %0, l;\ncvt.f32.f16 %1, h;\n}\n" : "=f"(lo), "=f"(hi) : "r"(c[2 * p + r]));
        var = fmaf(lo + nm, lo + nm, fmaf(hi + nm, hi + nm, var));
        if (p % 3 == 2) { asm volatile("" : "+f"(var)); PIN(); }
      }
      var += __shfl_xor_sync(0xffffffffu, var, 1);
      var += __shfl_xor_sync(0xffffffffu, var, 2);
      const float rr = rsqrtf(fmaf(var, 1.0f / 96.0f, 1e-5f)) * GELU_A;
      st[r] = __uint_as_float(pack_f16(rr, rr));
      const float dd = 0.5f * h_sum(__float_as_uint(st[r])) * nm;
      st[2 + r] = __uint_as_float(pack_f16(dd, dd));
      if (__any_sync(0xffffffffu, !(rr >= 0x1p-14f && fabsf(dd) <= 16.0f && var >= 1e-8f))) mark_bad(bad, 1u << i);
    }
  }
}
__device__ __forceinline__ void ln_apply(uint32_t (&a)[24], const uint32_t (&c)[24], const float (&st)[8]) {
#pragma unroll
  for (int p = 0; p < 24; p++) {
    a[p] = h_fma(c[p], __float_as_uint(st[p & 1]), __float_as_uint(st[2 + (p & 1)]));
  }
}

__device__ __noinline__ void slow_tile(const __nv_bfloat16* x, const __nv_bfloat16* dw, const __nv_bfloat16* w1,
                                       const __nv_bfloat16* w2, __nv_bfloat16* out, int row0, int col0, float* buf) {
  const int lane = threadIdx.x & 31;
  for (int px = 0; px < 16; px++) {
    const int row = row0 + (px >> 3), col = col0 + (px & 7);
    float c[3] = {0.f, 0.f, 0.f};
    for (int i = 0; i < 7; i++)
      for (int j = 0; j < 7; j++) {
        const int rr = row + i - 3, cc = col + j - 3;
        if (rr < 0 || rr >= IMG || cc < 0 || cc >= IMG) continue;
        for (int k = 0; k < 3; k++)
          c[k] = fmaf(__bfloat162float(x[((size_t)rr * IMG + cc) * CH + lane + 32 * k]), __bfloat162float(dw[(i * 7 + j) * CH + lane + 32 * k]), c[k]);
      }
    float mean = (c[0] + c[1] + c[2]) * (1.0f / 96.0f);
    for (int o = 16; o; o >>= 1) mean += __shfl_xor_sync(0xffffffffu, mean, o);
    float var = 0.f;
    for (int k = 0; k < 3; k++) { c[k] -= mean; var = fmaf(c[k] * (1.0f / 96.0f), c[k], var); }
    for (int o = 16; o; o >>= 1) var += __shfl_xor_sync(0xffffffffu, var, o);
    const float rs = 1.0f / sqrtf(var + 1e-5f);
    __syncwarp();
    for (int k = 0; k < 3; k++) buf[lane + 32 * k] = c[k] * rs;
    __syncwarp();
    for (int n = lane; n < 4 * CH; n += 32) {
      float y = 0.f;
      for (int k = 0; k < CH; k++) y = fmaf(buf[k], __bfloat162float(w1[k * 4 * CH + n]), y);
      buf[CH + n] = 0.5f * y * (1.0f + tanhf(0.7978845608f * (y + 0.044715f * y * y * y)));
    }
    __syncwarp();
    for (int n = lane; n < CH; n += 32) {
      float o = 0.f;
      for (int k = 0; k < 4 * CH; k++) o = fmaf(buf[CH + k], __bfloat162float(w2[k * CH + n]), o);
      const size_t idx = ((size_t)row * IMG + col) * CH + n;
      out[idx] = __float2bfloat16(__bfloat162float(x[idx]) + o);
    }
  }
}

__device__ __forceinline__ void x_load(const MlpCtx& m, uint32_t (&x)[24]) {
#pragma unroll
  for (int k = 0; k < 6; k++)
    asm volatile("ld.shared.v4.b32 {%0,%1,%2,%3}, [%4];"
                 : "=r"(x[4 * k]), "=r"(x[4 * k + 1]), "=r"(x[4 * k + 2]), "=r"(x[4 * k + 3])
                 : "r"(m.xaddr + (k / 3) * 384 + (k % 3) * 64)
                 : "memory");
}
template <bool DIRECT>
__device__ __forceinline__ void epilogue(const MlpCtx& m, const uint32_t (&d)[24], uint32_t (&x)[24]) {
  uint8_t* o = nullptr;
  if (DIRECT) {
    const uint32_t lane = laneid();
    o = m.optr + ((lane >> 3) & 1) * (IMG * CH * 2) + ((lane >> 4) * 4 + ((lane >> 2) & 1)) * 192 + (lane & 3) * 16;
  }
#pragma unroll
  for (int k = 0; k < 6; k++) {
    const int r = k / 3, q = k % 3;
    uint32_t* y = &x[4 * k];
#pragma unroll
    for (int j = 0; j < 4; j++) {
      uint32_t v = d[2 * (4 * q + j) + r];
      float lo, hi;
      asm("{\n.reg .b16 l, h;\nmov.b32 {l, h}, %2;\ncvt.f32.f16 %0, l;\ncvt.f32.f16 %1, h;\n}\n" : "=f"(lo), "=f"(hi) : "r"(v));
      asm("fma.rn.bf16x2 %0, %1, %2, %0;" : "+r"(y[j]) : "r"(pack_bf16(lo, hi)), "r"(m.unscale));
    }
    if (DIRECT)
      asm volatile("st.global.v4.b32 [%0], {%1,%2,%3,%4};" ::"l"(o + r * 384 + q * 64), "r"(y[0]), "r"(y[1]), "r"(y[2]), "r"(y[3]) : "memory");
    else
      asm volatile("st.shared.v4.b32 [%0], {%1,%2,%3,%4};" ::"r"(m.xaddr + r * 384 + q * 64), "r"(y[0]), "r"(y[1]), "r"(y[2]), "r"(y[3])
                   : "memory");
  }
}

#define FSET 3
template <int J> constexpr bool goes_first = J == FSET || J == ((FSET + 1) & 3);
template <int J> __device__ __forceinline__ void tok_wait() {
  if (goes_first<J>) NB_SYNC(NB_CLOSE, 256);
  else NB_SYNC(NB_SEC + (J & 1), 256);
}
template <int J, bool PROD = true> __device__ __forceinline__ void tok_next() {
  if (goes_first<J>) NB_ARRIVE(NB_SEC + (J & 1), 256);
  if (J == 0 && PROD) NB_ARRIVE(NB_PROD, 160);
}
__device__ __forceinline__ void tok_pass() { NB_ARRIVE(NB_OPEN, 448); }
template <int J> __device__ __forceinline__ void tok_idle() { tok_wait<J>(); tok_next<J, false>(); tok_pass(); }

constexpr uint64_t CHK = 1152;

__device__ __forceinline__ float warp_sumsq(const uint32_t (&q)[4]) {
  const uint32_t t = bf_add(bf_add(q[0], q[1]), bf_add(q[2], q[3]));
  float f = bf_lo(t) + bf_hi(t);
#pragma unroll
  for (int o = 16; o; o >>= 1) f += __shfl_xor_sync(0xffffffffu, f, o);
  return f;
}
__device__ __forceinline__ int norm_exp(float f) { return (((int)(__float_as_uint(f * 1.5f) >> 23) - 127) >> 1) + 1; }
__device__ __forceinline__ int scale_exp(int e1, int e2) { return min(11 - e1 - e2, 14 - e2); }

__device__ __forceinline__ void convert_tile(int t, int k, const uint4* w1, const uint4* w2, uint32_t st, Scratch* scr) {
  const int lane = threadIdx.x & 31, k7 = lane & 7;
  const int j = t / 6, ks = t % 6, e = ks % 3, t4 = k7 >> 1;
  const uint4* src = t < 24 ? w1 + ((e < 2 ? 64 * (ks / 3) + 8 * t4 + 4 * e : 32 + 16 * (ks / 3) + 4 * t4) + (k7 & 1)) * 48 + j * 12 + (lane >> 3)
                            : w2 + (t - 24) * 192 + (lane >> 2) * 12 + (lane & 3);
  src += (k / 3) * 96 + (k % 3) * 4;
  if (k >= 6) src = (k == 6 ? w1 : w2) + lane * 145;
  const uint4 v = __ldg(src);
  const uint32_t w[4] = {v.x, v.y, v.z, v.w};
  const uint32_t q[4] = {bf_mul(v.x, v.x), bf_mul(v.y, v.y), bf_mul(v.z, v.z), bf_mul(v.w, v.w)};
  asm volatile("st.shared.f32 [%0], %1;" ::"r"(st + 3088 + 4 * k), "f"(warp_sumsq(q)) : "memory");
  NB_SYNC(NB_PREP, 256);
  uint32_t a[4], b[4], o[4];
  lds128(a, st + 3088);
  lds128(b, st + 3104);
  const int s = max(-64, min(64, scale_exp(norm_exp(144.f * __uint_as_float(b[2])), norm_exp(144.f * __uint_as_float(b[3]))) - 3));
  const uint32_t dst = st + k7 * 16 + (lane >> 3) * 256 + (k / 3) * 128 + (k % 3) * 1024;
  if (k >= 6) {
    const float f = ((__uint_as_float(a[0]) + __uint_as_float(a[1])) + (__uint_as_float(a[2]) + __uint_as_float(a[3]))) +
                    (__uint_as_float(b[0]) + __uint_as_float(b[1]));
    asm volatile("st.shared.v2.b32 [%0], {%1,%2};" ::"r"(st + 3072), "r"(__float_as_uint(f)), "r"(s) : "memory");
  } else if (t < 24) {
#pragma unroll
    for (int i = 0; i < 4; i++) o[i] = pack_f16(bf_lo(w[i]), bf_hi(w[i]));
    asm volatile("st.shared.v4.b32 [%0], {%1,%2,%3,%4};" ::"r"(dst), "r"(o[0]), "r"(o[1]), "r"(o[2]), "r"(o[3]) : "memory");
  } else {
    constexpr float F = 0.5f / GELU_A, FHI = 1.515625f;
    const float p2 = __uint_as_float((uint32_t)(127 + s - 56) << 23);
    const uint32_t hi = pack_bf16(FHI * 0x1p-56f, FHI * 0x1p-56f), lo = pack_bf16((F - FHI) * 0x1p-56f, (F - FHI) * 0x1p-56f);
    const uint32_t pw = pack_bf16(p2, p2);
#pragma unroll
    for (int i = 0; i < 4; i++) {
      const uint32_t ws = bf_mul(w[i], pw), u = bf_fma(ws, hi, bf_mul(ws, lo));
      o[i] = (u & 0x7fff7fffu) * 7u + u;
    }
    asm volatile("stmatrix.sync.aligned.m8n8.x4.shared.b16 [%0], {%1,%2,%3,%4};" ::"r"(dst), "r"(o[0]), "r"(o[1]), "r"(o[2]), "r"(o[3])
                 : "memory");
  }
  asm volatile("fence.proxy.async.shared::cta;" ::: "memory");
  NB_SYNC(NB_PREP, 256);
  if (k == 0 && elect_one()) {
    asm volatile("cp.async.bulk.global.shared::cta.bulk_group [%0], [%1], 3072;" ::"l"(scr->w + t * 192), "r"(st) : "memory");
    asm volatile("cp.async.bulk.global.shared::cta.bulk_group [%0], [%1], 16;" ::"l"(scr->nrm + t), "r"(st + 3072) : "memory");
    asm volatile("cp.async.bulk.commit_group;" ::: "memory");
    asm volatile("cp.async.bulk.wait_group 0;" ::: "memory");
    asm volatile("red.relaxed.gpu.global.add.u32 [%0], 1;" ::"l"(&scr->done) : "memory");
  }
}

__device__ __forceinline__ void check_weights(uint32_t sb) {
  const int lane = threadIdx.x & 31;
  float n1, n2;
  int s;
  mbar_wait(sb + BAR_W, 0);
  asm volatile("ld.shared.b32 %0, [%1];" : "=r"(s) : "r"(sb + OFF_NRM + 4) : "memory");
  asm volatile("ld.shared.f32 %0, [%1];" : "=f"(n1) : "r"(sb + OFF_NRM + 16 * min(lane, 23)) : "memory");
  asm volatile("ld.shared.f32 %0, [%1];" : "=f"(n2) : "r"(sb + OFF_NRM + 384 + 16 * min(lane, 23)) : "memory");
  if (lane >= 24) n1 = n2 = 0.f;
#pragma unroll
  for (int o = 16; o; o >>= 1) {
    n1 += __shfl_xor_sync(0xffffffffu, n1, o);
    n2 += __shfl_xor_sync(0xffffffffu, n2, o);
  }
  const int e1 = norm_exp(n1), e2 = norm_exp(n2), smax = scale_exp(e1, e2);
  if (e1 > 12 || e1 < -5 || e2 > 50 || e2 < -50 || s > smax || s < smax - 7 || (sb & 0x3FFFF) != 1024)
    asm volatile("red.shared.or.b32 [%0], 0xffff;" ::"r"(sb + OFF_BAD + 4 * (lane & 7)) : "memory");
  __syncwarp();
  if (elect_one()) asm volatile("mbarrier.arrive.shared::cta.b64 _, [%0];" ::"r"(sb + BAR_W + 8) : "memory");
}

__device__ __forceinline__ uint32_t mlp_role(const MlpCtx& m0) {
  MlpCtx m = m0;
  const uint32_t bad = m.sb + OFF_BAD + 4 * (4 * m.wg + m.warp);
  asm volatile("barrier.cluster.wait.aligned;" ::: "memory");
  constexpr uint64_t dW1 = (uint64_t)((1024 + OFF_W1) >> 4) | ((uint64_t)8 << 16) | ((uint64_t)16 << 32);
  constexpr uint64_t dW2 = dW1 + (OFF_W2 >> 4);
  uint32_t A1[24], g[24], d[24], cn[24], D2[24];
  float st[8];
  uint32_t mask;
  if (m.wg & m.rank) tok_idle<3>();
  else if (m.wg) tok_idle<0>();
  else if (m.rank) tok_idle<1>();
  ln_wait(m, 0);
  ln_load(m, cn);
  ln_sums(cn, st);
  ln_shfl(st, 1);
  ln_release(m);
  ln_fold(st);
  ln_shfl(st, 2);
  ln_restat(ln_stats(st), cn, st, bad, 0, m.zero);
  ln_apply(A1, cn, st);
  mbar_wait(m.sb + BAR_W, 0);
  asm volatile("ld.shared.b32 %0, [%1];" : "=r"(m.unscale) : "r"(m.sb + OFF_NRM + 4) : "memory");
  m.unscale = ((127 - m.unscale) << 7) * 0x10001u;
  if (m.wg & m.rank) tok_idle<0>();
  if (m.wg) tok_idle<1>();
  {
    uint32_t d0[24];
    WG_FENCE();
    tok_wait<2>();
    tok_next<2>();
    gemm6<true, 192>(d0, A1, dW1);
    tok_pass(); PIN();
    WG_WAIT0(); rfence(d0);
    WG_FENCE();
    tok_wait<3>();
    tok_next<3>();
    gemm6<true, 192>(d, A1, dW1 + CHK);
    tok_pass(); PIN();
    gelu<0, 24>(g, d0);
    PIN();
    mbar_wait(m.sb + BAR_W + 8, 0);
    ln_wait(m, 1);
    WG_WAIT0(); rfence(d);
  }
#define G2(INIT, a, j)                      \
  WG_FENCE();                               \
  tok_wait<j>();                            \
  gemm6<INIT, 192>(D2, a, dW2 + (j) * CHK); \
  tok_next<j>(); PIN();
#define G1(dst, j, P)                       \
  P(); WG_WAIT0(); rfence(D2);              \
  WG_FENCE();                               \
  gemm6<true, 192>(dst, A1, dW1 + (j) * CHK); \
  tok_pass(); P();
#define ROUND_END(dst, j)                   \
  PIN(); WG_WAIT0(); rfence(dst);
#define GA 11
#define GB 13
#define GC 13
#define GD 11
#pragma unroll 1
  for (int i = 0;; i++) {
    uint32_t g1[24], d2[24], g2[24], d3[24], g3[24], d0[24];
    ln_load(m, cn);
    PIN();
    G2(true, g, 0)
    gelu<0, GA>(g1, d);
    G1(d2, 2, PIN)
    ln_sums(cn, st);
    gelu<GA, 24>(g1, d);
    PIN();
    ln_shfl(st, 1);
    ROUND_END(d2, 0)

    G2(false, g1, 1)
    ln_fold(st);
    gelu<0, GB>(g2, d2);
    PIN();
    ln_shfl(st, 2);
    G1(d3, 3, PIN)
    const bool ok = ln_stats(st);
    gelu<GB, 24>(g2, d2);
    PIN();
    ln_restat(ok, cn, st, bad, i + 1, m.zero);
    ROUND_END(d3, 1)

    if (i == 15) {
      G2(false, g2, 2)
      tok_pass();
      gelu<0, 16>(g3, d3);
      PIN();
      x_load(m, cn);
      asm volatile("ld.shared.b32 %0, [%1];" : "=r"(mask) : "r"(bad) : "memory");
      ROUND_END(D2, 2)
      WG_FENCE();
      tok_wait<3>();
#pragma unroll
      for (int k = 1; k < 5; k++) wg_acc(D2, &g3[4 * k], dW2 + 3 * CHK + k * 192);
      WG_COMMIT();
      tok_next<3>();
      tok_pass();
      PIN();
      gelu<16, 24>(g3, d3);
      ROUND_END(D2, 2)
      WG_FENCE();
      wg_acc(D2, &g3[20], dW2 + 3 * CHK + 5 * 192);
      wg_acc(D2, &g3[0], dW2 + 3 * CHK);
      WG_COMMIT();
      WG_WAIT0(); rfence(D2);
      epilogue<true>(m, D2, cn);
      break;
    }
    G2(false, g2, 2)
    ln_apply(A1, cn, st);
    PIN();
    gelu<0, GC>(g3, d3);
    G1(d0, 0, PIN)
    gelu<GC, 24>(g3, d3);
    PIN();
    x_load(m, cn);
    ROUND_END(d0, 2)

    G2(false, g3, 3)
    gelu<0, GD>(g, d0);
    G1(d, 1, PIN)
    epilogue<false>(m, D2, cn);
    gelu<GD, 24>(g, d0);
    PIN();
    asm volatile("fence.proxy.async.shared::cta;" ::: "memory");
    ROUND_END(d, 3)
  }
  if (m.wg == 0) { tok_idle<0>(); tok_idle<1>(); }
  return __reduce_or_sync(0xffffffffu, mask & 0xffffu);
}

struct ConvCtx {
  uint32_t sb;
  uint32_t a0, a_c;
  uint32_t peer_off;
  int rank, v, c0, r0, dir, zero;
  const CUtensorMap* tm;
  Scratch* scr;
  const uint8_t* xsrc;
  uint8_t* optr;
};

__device__ __forceinline__ void raw_refill(const ConvCtx& c, int s) {
  if (s + 4 < NSTEP && elect_one())
    tma_raw(c.sb + OFF_RAW + (s & 3) * RAW_BYTES, c.tm, c.rank, c.c0 / 2 - 2, c.r0 + c.dir * (2 * s + 5), c.sb + BAR_RAW + 8 * (s & 3));
}
__device__ __forceinline__ void step_ready(const ConvCtx& c, int s) {
  const int nx = (s + 1) & 3, par = ((s + 1) >> 2) & 1;
  if (s + 1 < NSTEP) mbar_wait(c.sb + BAR_RAW + 8 * nx, par);
  if (s >= 7 && s < NSTEP) mbar_wait(c.sb + BAR_CEMPTY + 8 * (2 * (nx & 1) + (nx >> 1)), par);
}

__device__ __forceinline__ void c_release(const ConvCtx& c, uint32_t w) {
  const uint32_t e = c.sb + BAR_CEMPTY + 8 * (2 * c.rank + w);
  asm volatile(
      "{\n.reg .pred p;\nelect.sync _|p, 0xffffffff;\n"
      "@p mbarrier.arrive.expect_tx.shared::cta.b64 _, [%0], %3;\n"
      "@p mbarrier.arrive.shared::cluster.b64 _, [%1], 4;\n"
      "@p mbarrier.arrive.shared::cluster.b64 _, [%2], 4;\n}\n" ::"r"(c.sb + BAR_CFULL + 8 * w),
      "r"(e), "r"(e + c.peer_off), "n"(CTX)
      : "memory");
}

__device__ __forceinline__ void prod_rows(const ConvCtx& c) {
#pragma unroll 1
  for (int s = 0; s < NROUND + SIGMA + c.rank; s++) {
    if (s < SIGMA) NB_SYNC(NB_PLAN, 192);
    else NB_SYNC(NB_OPEN, 448);
    raw_refill(c, s);
  }
}
__device__ __forceinline__ void prod_checks(const ConvCtx& c) {
  asm volatile("barrier.cluster.wait.aligned;" ::: "memory");
#pragma unroll 1
  for (int s = 0; s < NROUND + SIGMA + c.rank; s++) {
    const int r = s - SIGMA - c.rank;
    const int u = (r & 1) ? (r >> 1) - 1 : (r >> 1) + 2;
    step_ready(c, s);
    if (s < 16) TP(c.scr, 100 + s);
    if (u >= ((r & 1) ? 0 : 4) && u < 32) mbar_wait(c.sb + ((r & 1) ? BAR_XFULL : BAR_CFULL) + 8 * (u & 1), (u >> 1) & 1);
    if (s < SIGMA) NB_SYNC(NB_PLAN, 192);
    else NB_SYNC(NB_OPEN, 448);
    TP(c.scr, s);
    if (r == 3) TC(c.scr, 1);
    if (r == 55) TC(c.scr, 2);
  }
}
__device__ __forceinline__ void prod_tiles(const ConvCtx& c) {
  asm volatile("barrier.cluster.wait.aligned;" ::: "memory");
#pragma unroll 1
  for (int n = 1; n < 33; n++) {
    const uint32_t w = (n + 1) & 1;
    const uint32_t buf = c.sb + OFF_XRES + w * 12288;
    NB_SYNC(NB_PROD, 160);
    if (n < 29) c_release(c, w);
    if (n >= 3) {
      uint8_t* dst = c.optr + (n - 3) * c.dir * (4 * IMG * CH * 2);
      if (elect_one()) {
        asm volatile("cp.async.bulk.global.shared::cta.bulk_group [%0], [%1], 6144;" ::"l"(dst), "r"(buf) : "memory");
        asm volatile("cp.async.bulk.global.shared::cta.bulk_group [%0], [%1], 6144;" ::"l"(dst + IMG * CH * 2), "r"(buf + 6144) : "memory");
        asm volatile("cp.async.bulk.commit_group;" ::: "memory");
        asm volatile("cp.async.bulk.wait_group.read 0;" ::: "memory");
      }
      __syncwarp();
    }
    {
      const uint8_t* src = c.xsrc + (n - 1) * c.dir * (4 * IMG * CH * 2);
      if (elect_one()) {
        mbar_expect(c.sb + BAR_XFULL + 8 * w, 12288);
        bulk_load_last(buf, src, 6144, c.sb + BAR_XFULL + 8 * w);
        bulk_load_last(buf + 6144, src + IMG * CH * 2, 6144, c.sb + BAR_XFULL + 8 * w);
      }
    }
  }
  asm volatile("cp.async.bulk.wait_group 0;" ::: "memory");
}

template <int LO, int HI>
__device__ __forceinline__ void conv_ld8(uint32_t a0, uint32_t (&r)[6][6]) {
  const uint32_t a2 = a0 ^ (16 | ((a0 >> 2) & 32));
  const uint32_t a[3] = {a0, (a0 & 64) ? a2 : a0, a2};
#pragma unroll
  for (int j = LO; j < HI; j++)
    asm volatile("ld.shared.v4.b32 {%0,%1,%2,%3}, [%4];"
                 : "=r"(r[j][0]), "=r"(r[j][1]), "=r"(r[j][2]), "=r"(r[j][3])
                 : "r"(a[j >> 1] + (j >> 1) * 64 + (j & 1) * RAW_PA)
                 : "memory");
}
__device__ __forceinline__ void conv_ld4(uint32_t a0, uint32_t stage, int v, uint32_t (&r)[6][6]) {
  const uint32_t ab = ((a0 >> 1) & ~31u) + (stage / 2 + 2 * RAW_PA + 8 * v);
#pragma unroll
  for (int j = 0; j < 6; j++) {
    uint32_t a = ab + (j >> 1) * 32;
    asm volatile("ld.shared.v2.b32 {%0,%1}, [%2];" : "=r"(r[j][4]), "=r"(r[j][5]) : "r"(a + (j & 1) * RAW_PB) : "memory");
  }
}
template <int LO, int HI>
__device__ __forceinline__ void conv_frags(uint32_t zero, const uint32_t (&r)[6][6], uint32_t (&A)[12][4]) {
#pragma unroll
  for (int ch = LO; ch < HI; ch++) {
    const uint32_t sel = (ch & 1) ? 0x7632 : 0x5410;
    A[ch][0] = __byte_perm(r[0][ch >> 1], r[1][ch >> 1], sel);
    A[ch][1] = __byte_perm(r[2][ch >> 1], r[3][ch >> 1], sel);
    A[ch][2] = A[ch][1] ^ zero;
    A[ch][3] = __byte_perm(r[4][ch >> 1], r[5][ch >> 1], sel);
    rfence(A[ch]);
  }
}
__device__ __forceinline__ void hmma_acc(uint32_t (&v)[4], const uint32_t (&a)[4], const uint32_t* b) {
  asm volatile("mma.sync.aligned.m16n8k16.row.col.f32.bf16.bf16.f32 {%0,%1,%2,%3}, {%4,%5,%6,%7}, {%8,%9}, {%0,%1,%2,%3};"
               : "+r"(v[0]), "+r"(v[1]), "+r"(v[2]), "+r"(v[3])
               : "r"(a[0]), "r"(a[1]), "r"(a[2]), "r"(a[3]), "r"(b[0]), "r"(b[1]));
}
__device__ __forceinline__ void hmma_new(uint32_t (&a)[4], const uint32_t* b) {
  asm volatile("mma.sync.aligned.m16n8k16.row.col.f32.bf16.bf16.f32 {%0,%1,%2,%3}, {%0,%1,%2,%3}, {%4,%5}, {%6,%6,%6,%6};"
               : "+r"(a[0]), "+r"(a[1]), "+r"(a[2]), "+r"(a[3])
               : "r"(b[0]), "r"(b[1]), "f"(0.f));
}

#define EARLY 6
__device__ __forceinline__ void conv_send(bool local, const uint32_t (&pk)[12], uint32_t dst, uint32_t bar) {
  if (local) {
#pragma unroll
    for (int q = 0; q < 3; q++)
      asm volatile("st.shared.v4.b32 [%0], {%1,%2,%3,%4};" ::"r"(dst + q * 2048), "r"(pk[4 * q]), "r"(pk[4 * q + 1]), "r"(pk[4 * q + 2]), "r"(pk[4 * q + 3])
                   : "memory");
    asm volatile("{\n.reg .pred p;\nelect.sync _|p, 0xffffffff;\n@p mbarrier.arrive.shared::cta.b64 _, [%0];\n}\n" ::"r"(bar) : "memory");
  } else {
#pragma unroll
    for (int q = 0; q < 3; q++)
      asm volatile("st.async.weak.shared::cluster.mbarrier::complete_tx::bytes.v4.b32 [%0], {%1,%2,%3,%4}, [%5];" ::"r"(dst + q * 2048),
                   "r"(pk[4 * q]), "r"(pk[4 * q + 1]), "r"(pk[4 * q + 2]), "r"(pk[4 * q + 3]), "r"(bar)
                   : "memory");
  }
}
template <int S2, bool GATED>
__device__ __forceinline__ void conv_step(const ConvCtx& c, int s, uint32_t (&K)[12], uint32_t (&V)[12][4], const uint32_t (&B)[12][4],
                                          uint32_t (&A)[12][4]) {
  const int nx = ((s + 1) & 2) | (S2 ^ 1);
  uint32_t r[6][6], pk[12];
  const uint32_t a0 = c.a0 + nx * RAW_BYTES;
  if (GATED) NB_SYNC(NB_OPEN, 448);
  else NB_SYNC(NB_PLAN, 192);
  conv_ld4(a0, c.sb + OFF_RAW + nx * RAW_BYTES, c.v, r);
  if (GATED) PIN();
#pragma unroll
  for (int ch = 0; ch < 12; ch++) hmma_acc(V[11 - ch], A[11 - ch], &B[11 - ch][2]);
#pragma unroll
  for (int ch = 0; ch < 12 - EARLY; ch++) hmma_new(A[ch], &B[ch][0]);
  const uint32_t zero = GATED ? c.zero & clock_pin() : c.zero;
  if (GATED) NB_ARRIVE(NB_CLOSE, 256);
#pragma unroll
  for (int ch = 12 - EARLY; ch < 12; ch++) hmma_new(A[ch], &B[ch][0]);
  if (GATED) PIN();
  const bool local = (S2 ^ 1) == c.rank;
  const uint32_t off = local ? 0u : c.peer_off;
  const uint32_t dst = c.a_c + off + (nx >> 1) * C_BYTES;
  const uint32_t bar = c.sb + off + BAR_CFULL + 8 * (nx >> 1);
#pragma unroll
  for (int q = 0; q < 12; q++) {
    const int ch = q & ~1, h = 2 * (q & 1);
    pk[q] = h_add(K[q], pack_f16(__uint_as_float(V[ch][h + 1]), __uint_as_float(V[ch + 1][h])));
  }
#pragma unroll
  for (int q = 0; q < 12; q++) {
    const int ch = q & ~1, h = 2 * (q & 1);
    K[q] = pack_f16(__uint_as_float(V[ch][h]), __uint_as_float(V[ch + 1][h + 1]));
  }
  rfence(K);
  rfence(pk);
  PIN();
  conv_ld8<0, 4>(a0, r);
  if (GATED || s >= 3) conv_send(local, pk, dst, bar);
  conv_frags<8, 12>(zero, r, V);
  PIN();
  conv_ld8<4, 6>(a0, r);
  conv_frags<0, 8>(zero, r, V);
  PIN();
}

__device__ __forceinline__ void conv_role(ConvCtx c) {
  const int lane = laneid(), g = lane >> 2, t = lane & 3;
  const int u = (t >> 1) * 19 + 2 * (g + (t & 1));
  c.a0 = c.sb + OFF_RAW + u * 64 + ((c.v ^ (u >> 1)) & 3) * 16;
  c.a_c = c.sb + OFF_C + 6144 * c.rank + 512 * c.v + ((lane + 2 * c.v) & 31) * 16;
  uint32_t B[12][4];
  {
    const int dc = (g >> 1) & 1, ro = g >> 2, rk = t >> 1;
    const int i0 = (c.dir > 0 ? 4 * (g & 1) : 6 - 4 * (g & 1)) + rk - ro, j0 = 4 * (t & 1) - dc;
    const uint32_t base = c.sb + OFF_XRES + (i0 * 7 + j0) * 192;
    asm volatile("barrier.cluster.wait.aligned;" ::: "memory");
    mbar_wait(c.sb + BAR_W + 48, 0);
#pragma unroll
    for (int b = 0; b < 2; b++) {
      uint32_t w[4][6];
#pragma unroll
      for (int k = 0; k < 4; k++) {
        const int ok = (unsigned)(i0 + 2 * b * c.dir) < 7u && (unsigned)(j0 + k) < 7u;
#pragma unroll
        for (int q = 0; q < 6; q++) w[k][q] = 0;
        asm volatile(
            "{\n.reg .pred p;\nsetp.ne.s32 p, %8, 0;\n@p ld.shared.v4.b32 {%0,%1,%2,%3}, [%6];\n@p ld.shared.v2.b32 {%4,%5}, [%7];\n}\n"
            : "+r"(w[k][0]), "+r"(w[k][1]), "+r"(w[k][2]), "+r"(w[k][3]), "+r"(w[k][4]), "+r"(w[k][5])
            : "r"(base + (b * 14 * c.dir + k) * 192 + 128 * c.rank + 16 * c.v), "r"(base + (b * 14 * c.dir + k) * 192 + 64 + 32 * c.rank + 8 * c.v), "r"(ok)
            : "memory");
      }
#pragma unroll
      for (int q = 0; q < 6; q++) {
        B[2 * q][2 * b] = __byte_perm(w[0][q], w[1][q], 0x5410);
        B[2 * q][2 * b + 1] = __byte_perm(w[2][q], w[3][q], 0x5410);
        B[2 * q + 1][2 * b] = __shfl_xor_sync(0xffffffffu, __byte_perm(w[0][q], w[1][q], 0x7632), 4);
        B[2 * q + 1][2 * b + 1] = __shfl_xor_sync(0xffffffffu, __byte_perm(w[2][q], w[3][q], 0x7632), 4);
      }
    }
  }
  uint32_t K1[12], K2[12], V[12][4];
#pragma unroll
  for (int ch = 0; ch < 12; ch++)
    asm volatile("" : "=r"(K1[ch]), "=r"(K2[ch]), "=r"(V[ch][0]), "=r"(V[ch][1]), "=r"(V[ch][2]), "=r"(V[ch][3]));
  uint32_t A[12][4], r[6][6];
  mbar_wait(c.sb + BAR_RAW, 0);
  conv_ld8<0, 6>(c.a0, r);
  conv_ld4(c.a0, c.sb + OFF_RAW, c.v, r);
  conv_frags<0, 12>(c.zero, r, A);
  PIN();
  NB_ARRIVE(NB_CLOSE, 256);
#pragma unroll 1
  for (int s = 0; s < SIGMA; s += 2) {
    conv_step<0, false>(c, s, K1, V, B, A);
    conv_step<1, false>(c, s + 1, K2, A, B, V);
  }
#pragma unroll 1
  for (int s = SIGMA;; s += 2) {
    conv_step<0, true>(c, s, K1, V, B, A);
    if (s == NSTEP - 1) break;
    conv_step<1, true>(c, s + 1, K2, A, B, V);
  }
#pragma unroll 1
  for (int r = NSTEP - SIGMA - c.rank; r < NROUND - 1; r++) {
    NB_SYNC(NB_OPEN, 448);
    NB_ARRIVE(NB_CLOSE, 256);
  }
  NB_SYNC(NB_OPEN, 448);
}

struct TMaps { CUtensorMap m[2]; };

__global__ void __cluster_dims__(2, 1, 1) __launch_bounds__(512, 1)
convnext_kernel(const __grid_constant__ TMaps tms, const __nv_bfloat16* __restrict__ x, const __nv_bfloat16* __restrict__ dw,
                const __nv_bfloat16* __restrict__ w1, const __nv_bfloat16* __restrict__ w2, __nv_bfloat16* __restrict__ out,
                Scratch* scr, int zero) {
  extern __shared__ __align__(1024) uint8_t smem[];
  const uint32_t sb = (uint32_t)__cvta_generic_to_shared(smem);
  const int tid = threadIdx.x, lane = tid & 31;
  const int wid = __shfl_sync(0xffffffffu, tid >> 5, 0);
  const int rank = blockIdx.x & 1, cl = blockIdx.x >> 1;
  const int dir = (cl & 16) ? 1 : -1;
  const int c0 = (cl & 15) * 32, r0 = (cl >> 4) * 128 + (dir > 0 ? 0 : 126);
  const uint32_t peer_off = mapa(sb, rank ^ 1) - sb;

  if (wid == 12 && elect_one()) {
    mbar_init(sb + BAR_W + 48, 1);
#pragma unroll
    for (int i = 0; i < 4; i++) mbar_init(sb + BAR_RAW + 8 * i, 1);
    asm volatile("fence.mbarrier_init.release.cluster;" ::: "memory");
    mbar_expect(sb + BAR_W + 48, 49 * CH * 2);
    bulk_load(sb + OFF_XRES, dw, 49 * CH * 2, sb + BAR_W + 48);
#pragma unroll
    for (int i = 0; i < E0; i++) tma_raw(sb + OFF_RAW + i * RAW_BYTES, tms.m, rank, c0 / 2 - 2, r0 + dir * (2 * i - 3), sb + BAR_RAW + 8 * i);
  }
  if (wid == 14 && elect_one()) {
    asm volatile("cp.async.bulk.prefetch.L2.global [%0], 1152;" ::"l"(reinterpret_cast<const uint8_t*>(rank ? w2 : w1) + cl * 1152) : "memory");
    asm volatile("prefetch.tensormap [%0];" ::"l"(&tms.m[1]) : "memory");
#pragma unroll
    for (int i = 0; i < 3; i++) mbar_init(sb + BAR_W + 8 * i, i == 1 ? 2 : 1);
#pragma unroll
    for (int i = 0; i < 2; i++) mbar_init(sb + BAR_CFULL + 8 * i, CCNT);
#pragma unroll
    for (int i = 0; i < 4; i++) mbar_init(sb + BAR_CEMPTY + 8 * i, 4);
#pragma unroll
    for (int i = 0; i < 2; i++) mbar_init(sb + BAR_XFULL + 8 * i, 1);
#pragma unroll
    for (int i = 0; i < 2; i++) mbar_expect(sb + BAR_CFULL + 8 * i, CTX);
#pragma unroll
    for (int i = 0; i < 2; i++) asm volatile("st.shared.v4.b32 [%0], {0, 0, 0, 0};" ::"r"(sb + OFF_BAD + 16 * i) : "memory");
    asm volatile("fence.mbarrier_init.release.cluster;" ::: "memory");
  }
  __syncwarp();
  asm volatile("barrier.cluster.arrive.relaxed.aligned;" ::: "memory");

  if (wid < 8) {
    if (blockIdx.x < 48) convert_tile(blockIdx.x, wid, reinterpret_cast<const uint4*>(w1), reinterpret_cast<const uint4*>(w2), sb, scr);
    MlpCtx m;
    m.sb = sb; m.wg = wid >> 2; m.warp = wid & 3; m.rank = rank; m.peer_off = peer_off; m.zero = zero;
    m.optr = reinterpret_cast<uint8_t*>(out) + ((size_t)(r0 + dir * (120 + 4 * m.wg + 2 * rank)) * IMG + c0 + 8 * m.warp) * (CH * 2);
    m.caddr = sb + OFF_C + m.wg * C_BYTES + (lane & 3) * 512 + ((m.warp * 8 + (lane >> 2) + 2 * (lane & 3)) & 31) * 16;
    m.xaddr = sb + OFF_XRES + m.wg * 12288 + m.warp * 1536 + ((lane >> 3) & 1) * 6144 + ((lane >> 4) * 4 + ((lane >> 2) & 1)) * 192 + (lane & 3) * 16;
    m.unscale = 0;
    asm volatile("setmaxnreg.inc.sync.aligned.u32 %0;" ::"n"(REG_MLP));
    const uint32_t bad = mlp_role(m);
    TC(scr, 3);
    if (bad) {
      mbar_wait(sb + BAR_W + 16, 0);
      __syncwarp();
      asm volatile("fence.proxy.async;" ::: "memory");
#pragma unroll 1
      for (int i = 0; i < 16; i++)
        if (bad >> i & 1)
          slow_tile(x, dw, w1, w2, out, r0 + dir * (8 * i + 4 * m.wg + 2 * rank), c0 + 8 * m.warp,
                    reinterpret_cast<float*>(smem + OFF_RAW + wid * 2048));
    }
  } else {
    ConvCtx c;
    c.sb = sb; c.rank = rank; c.v = wid - 8; c.c0 = c0; c.r0 = r0; c.dir = dir; c.zero = zero; c.tm = tms.m; c.scr = scr;
    c.peer_off = peer_off;
    c.xsrc = reinterpret_cast<const uint8_t*>(x) + ((size_t)(r0 + 2 * dir * rank) * IMG + c0) * (CH * 2);
    c.optr = reinterpret_cast<uint8_t*>(out) + ((size_t)(r0 + 2 * dir * rank) * IMG + c0) * (CH * 2);
    if (wid < 12) {
      asm volatile("setmaxnreg.inc.sync.aligned.u32 %0;" ::"n"(REG_CONV));
      conv_role(c);
    } else {
      asm volatile("setmaxnreg.dec.sync.aligned.u32 24;");
      if (wid == 15) TC(scr, 0);
      if (wid == 12) {
#pragma unroll 1
        for (int h = E0 - 4; h < 0; h++) raw_refill(c, h);
        prod_rows(c);
      } else if (wid == 15) {
        prod_checks(c);
      } else if (wid == 14) {
#pragma unroll 1
        for (int n = 0; n < (1 << 20); n++) {
          unsigned v;
          __nanosleep(n ? PSL : PS0);
          asm volatile("ld.acquire.gpu.global.u32 %0, [%1];" : "=r"(v) : "l"(&scr->done) : "memory");
          if (__shfl_sync(0xffffffffu, v, 0) >= 48) break;
        }
        TP(scr, 90);
        asm volatile("barrier.cluster.wait.aligned;" ::: "memory");
        asm volatile("fence.proxy.async.global;" ::: "memory");
        if (elect_one()) {
          mbar_expect(sb + BAR_W, 36864 + 768);
          mbar_expect(sb + BAR_W + 8, 110592);
          bulk_load(sb + OFF_NRM, scr->nrm, 768, sb + BAR_W);
        }
        __syncwarp();
#pragma unroll 1
        for (int i = 0; i < 8; i++) {
          if (elect_one()) bulk_load(sb + i * 18432, reinterpret_cast<const uint8_t*>(scr->w) + i * 18432, 18432, sb + BAR_W + (i < 2 ? 0 : 8));
          if (i >= PFIRST) __nanosleep(PACE);
        }
        check_weights(sb);
        if (elect_one() && atomicAdd(&scr->seen, 1u) == gridDim.x - 1) { scr->done = 0; scr->seen = 0; }
      } else if (wid == 13) {
        prod_tiles(c);
        __syncwarp();
        if (elect_one()) asm volatile("mbarrier.arrive.shared::cta.b64 _, [%0];" ::"r"(sb + BAR_W + 16) : "memory");
      }
    }
  }
}

typedef CUresult (*EncodeFn)(CUtensorMap*, CUtensorMapDataType, cuuint32_t, void*, const cuuint64_t*, const cuuint64_t*,
                             const cuuint32_t*, const cuuint32_t*, CUtensorMapInterleave, CUtensorMapSwizzle,
                             CUtensorMapL2promotion, CUtensorMapFloatOOBfill);

}

extern "C" void kernel_launch(void* const* d_in, const int* in_sizes, int n_in, void* d_out, int out_size) {
  const __nv_bfloat16* x = (const __nv_bfloat16*)d_in[0];
  const __nv_bfloat16* dw = (const __nv_bfloat16*)d_in[1];
  const __nv_bfloat16* w1 = (const __nv_bfloat16*)d_in[2];
  const __nv_bfloat16* w2 = (const __nv_bfloat16*)d_in[3];
  __nv_bfloat16* out = (__nv_bfloat16*)d_out;

  static EncodeFn encode = nullptr;
  static Scratch* scr = nullptr;
  if (!encode) {
    cudaDriverEntryPointQueryResult st;
    void* fn = nullptr;
    cudaGetDriverEntryPoint("cuTensorMapEncodeTiled", &fn, cudaEnableDefault, &st);
    encode = (EncodeFn)fn;
    cudaGetSymbolAddress((void**)&scr, g_scratch);
    cudaFuncSetAttribute(convnext_kernel, cudaFuncAttributeMaxDynamicSharedMemorySize, SMEM_BYTES);
  }
  TMaps tm;
  cuuint64_t dims[4] = {CH, IMG / 2, IMG, 2};
  cuuint64_t strides[3] = {CH * 4, (cuuint64_t)IMG * CH * 2, CH * 2};
  cuuint32_t es[4] = {1, 1, 1, 1};
  for (int i = 0; i < 2; i++) {
    cuuint32_t box[4] = {i ? 16u : 32u, 19, 2, 1};
    encode(&tm.m[i], CU_TENSOR_MAP_DATA_TYPE_BFLOAT16, 4, (void*)x, dims, strides, box, es, CU_TENSOR_MAP_INTERLEAVE_NONE,
           i ? CU_TENSOR_MAP_SWIZZLE_NONE : CU_TENSOR_MAP_SWIZZLE_64B, PROMO, CU_TENSOR_MAP_FLOAT_OOB_FILL_NONE);
  }
  convnext_kernel<<<128, 512, SMEM_BYTES>>>(tm, x, dw, w1, w2, out, scr, 0);
}
```

```cpp
#include <cuda_runtime.h>
#include <cuda_bf16.h>
#include <cuda.h>
#include <stdint.h>

#define PROMO CU_TENSOR_MAP_L2_PROMOTION_L2_128B
#define CTX 6144
#define CCNT 5
#define PSL 100
#define PS0 1000
#define E0 1
#define PACE 100
#define PFIRST 1
namespace {

constexpr int IMG = 512, CH = 96;
constexpr int NSTEP = 67;
constexpr int SIGMA = 8;
constexpr int NROUND = 68;

constexpr uint32_t OFF_W1 = 0;
constexpr uint32_t OFF_W2 = 73728;
constexpr uint32_t OFF_RAW = 147456;
constexpr uint32_t RAW_PA = 2560, RAW_PB = 1280;
constexpr uint32_t RAW_BYTES = 2 * RAW_PA + 2 * RAW_PB;
constexpr uint32_t RAW_TX = 2 * 38 * 96;
constexpr uint32_t OFF_XRES = OFF_RAW + 4 * RAW_BYTES;
constexpr uint32_t OFF_C = OFF_XRES + 2 * 12288;
constexpr uint32_t C_BYTES = 12288;
constexpr uint32_t OFF_BAR = OFF_C + 2 * C_BYTES;
constexpr uint32_t BAR_RAW = OFF_BAR;
constexpr uint32_t BAR_CFULL = OFF_BAR + 32;
constexpr uint32_t BAR_CEMPTY = OFF_BAR + 48;
constexpr uint32_t BAR_XFULL = OFF_BAR + 80;
constexpr uint32_t BAR_W = OFF_BAR + 96;
constexpr uint32_t OFF_NRM = OFF_XRES + 9472;
constexpr uint32_t OFF_BAD = OFF_BAR + 160;
constexpr uint32_t SMEM_BYTES = OFF_BAD + 32;

struct Scratch {
  uint4 w[2 * 73728 / 16];
  uint4 nrm[48];
  unsigned done, seen;
};
__device__ Scratch g_scratch;

constexpr float GELU_A = 0.32918364f;
constexpr uint32_t GELU_K2 = 0x40d940d9u;

constexpr int NB_CLOSE = 1, NB_SEC = 6  , NB_OPEN = 3, NB_PROD = 2, NB_PLAN = 4, NB_PREP = 5, NB_INIT = 8;
#define REG_MLP 144
constexpr int REG_CONV = 488 - 2 * REG_MLP;

#define WG_FENCE() asm volatile("wgmma.fence.sync.aligned;" ::: "memory")
#define WG_COMMIT() asm volatile("wgmma.commit_group.sync.aligned;" ::: "memory")
#define WG_WAIT0() asm volatile("wgmma.wait_group.sync.aligned 0;" ::: "memory")
#define WG_WAIT1() asm volatile("wgmma.wait_group.sync.aligned 1;" ::: "memory")
#define PIN() asm volatile("pmevent 0;" ::: "memory")
#define NB_SYNC(id, n) asm volatile("bar.sync %0, %1;" ::"n"(id), "n"(n) : "memory")
#define NB_ARRIVE(id, n) asm volatile("bar.arrive %0, %1;" ::"n"(id), "n"(n) : "memory")

#define TC(scr, k)
#define TP(scr, k)

#define R24(c, d)                                                                                        \
  c(d[0]), c(d[1]), c(d[2]), c(d[3]), c(d[4]), c(d[5]), c(d[6]), c(d[7]), c(d[8]), c(d[9]), c(d[10]),    \
      c(d[11]), c(d[12]), c(d[13]), c(d[14]), c(d[15]), c(d[16]), c(d[17]), c(d[18]), c(d[19]), c(d[20]), \
      c(d[21]), c(d[22]), c(d[23])
#define WG_TXT(sd)                                                                             \
  "wgmma.mma_async.sync.aligned.m64n96k16.f16.f16.f16 "                                        \
  "{%0,%1,%2,%3,%4,%5,%6,%7,%8,%9,%10,%11,%12,%13,%14,%15,%16,%17,%18,%19,%20,%21,%22,%23}, " \
  "{%24,%25,%26,%27}, %28, " sd ", 1, 1, 1;\n"

__device__ __forceinline__ void wg_acc(uint32_t (&d)[24], const uint32_t* a, uint64_t db) {
  asm volatile(WG_TXT("1") : R24("+r", d) : "r"(a[0]), "r"(a[1]), "r"(a[2]), "r"(a[3]), "l"(db));
}
__device__ __forceinline__ void wg_init(uint32_t (&d)[24], const uint32_t* a, uint64_t db) {
  asm volatile(WG_TXT("0") : R24("=r", d) : "r"(a[0]), "r"(a[1]), "r"(a[2]), "r"(a[3]), "l"(db));
}
template <int N>
__device__ __forceinline__ void rfence(uint32_t (&d)[N]) {
#pragma unroll
  for (int i = 0; i < N; i++) asm volatile("" : "+r"(d[i])::"memory");
}
template <bool INIT, int KSTRIDE>
__device__ __forceinline__ void gemm6(uint32_t (&d)[24], const uint32_t (&a)[24], uint64_t db) {
#pragma unroll
  for (int k = 0; k < 6; k++) {
    if (INIT && k == 0) wg_init(d, &a[0], db);
    else wg_acc(d, &a[4 * k], db + k * KSTRIDE);
  }
  WG_COMMIT();
}

__device__ __forceinline__ void mbar_init(uint32_t bar, uint32_t cnt) {
  asm volatile("mbarrier.init.shared::cta.b64 [%0], %1;" ::"r"(bar), "r"(cnt) : "memory");
}
__device__ __forceinline__ void mbar_expect(uint32_t bar, uint32_t bytes) {
  asm volatile("mbarrier.arrive.expect_tx.shared::cta.b64 _, [%0], %1;" ::"r"(bar), "r"(bytes) : "memory");
}
__device__ __forceinline__ void mbar_arrive_cluster(uint32_t bar) {
  asm volatile("mbarrier.arrive.shared::cluster.b64 _, [%0];" ::"r"(bar) : "memory");
}
__device__ __forceinline__ bool mbar_try(uint32_t bar, uint32_t parity) {
  uint32_t ok;
  asm volatile(
      "{\n.reg .pred p;\nmbarrier.try_wait.parity.shared::cta.b64 p, [%1], %2;\nselp.u32 %0, 1, 0, p;\n}\n"
      : "=r"(ok)
      : "r"(bar), "r"(parity)
      : "memory");
  return ok;
}
__device__ __forceinline__ bool mbar_test(uint32_t bar, uint32_t parity) {
  uint32_t ok;
  asm volatile(
      "{\n.reg .pred p;\nmbarrier.test_wait.parity.shared::cta.b64 p, [%1], %2;\nselp.u32 %0, 1, 0, p;\n}\n"
      : "=r"(ok)
      : "r"(bar), "r"(parity)
      : "memory");
  return ok;
}
__device__ __forceinline__ void mbar_wait(uint32_t bar, uint32_t parity) {
  if (__builtin_expect(mbar_try(bar, parity), 1)) return;
#pragma unroll 1
  for (uint32_t n = 0; n < (1u << 16) && !mbar_try(bar, parity); n++) {}
}
__device__ __forceinline__ uint32_t mapa(uint32_t addr, uint32_t rank) {
  uint32_t r;
  asm("mapa.shared::cluster.u32 %0, %1, %2;" : "=r"(r) : "r"(addr), "r"(rank));
  return r;
}
__device__ __forceinline__ void tma_raw(uint32_t dst, const CUtensorMap* tm, int rank, int w2, int h, uint32_t bar) {
  mbar_expect(bar, RAW_TX);
#pragma unroll
  for (int k = 0; k < 4; k++) {
    const int e = k & 1;
    asm volatile(
        "cp.async.bulk.tensor.4d.shared::cluster.global.mbarrier::complete_tx::bytes [%0], [%1, {%2, %3, %4, %5}], [%6];"
        ::"r"(dst + (k < 2 ? e * RAW_PA : 2 * RAW_PA + e * RAW_PB)), "l"(tm + (k >> 1)), "r"(k < 2 ? 64 * rank : 32 + 16 * rank), "r"(w2 + e),
        "r"(h), "r"(1 - e), "r"(bar)
        : "memory");
  }
}
__device__ __forceinline__ void bulk_load(uint32_t dst, const void* src, uint32_t bytes, uint32_t bar) {
  asm volatile("cp.async.bulk.shared::cluster.global.mbarrier::complete_tx::bytes [%0], [%1], %2, [%3];" ::"r"(dst),
               "l"(src), "r"(bytes), "r"(bar)
               : "memory");
}
__device__ __forceinline__ void bulk_load_last(uint32_t dst, const void* src, uint32_t bytes, uint32_t bar) {
  asm volatile(
      "{\n.reg .b64 pol;\ncreatepolicy.fractional.L2::evict_first.b64 pol, 1.0;\n"
      "cp.async.bulk.shared::cluster.global.mbarrier::complete_tx::bytes.L2::cache_hint [%0], [%1], %2, [%3], pol;\n}\n" ::"r"(dst),
      "l"(src), "r"(bytes), "r"(bar)
      : "memory");
}
__device__ __forceinline__ uint32_t pack_bf16(float lo, float hi) {
  uint32_t r;
  asm("cvt.rn.bf16x2.f32 %0, %1, %2;" : "=r"(r) : "f"(hi), "f"(lo));
  return r;
}
__device__ __forceinline__ uint32_t pack_f16(float lo, float hi) {
  uint32_t r;
  asm("cvt.rn.f16x2.f32 %0, %1, %2;" : "=r"(r) : "f"(hi), "f"(lo));
  return r;
}
__device__ __forceinline__ float bf_lo(uint32_t v) { return __uint_as_float(v << 16); }
__device__ __forceinline__ float bf_hi(uint32_t v) { return __uint_as_float(v & 0xffff0000u); }
__device__ __forceinline__ uint32_t bf_add(uint32_t a, uint32_t b) {
  uint32_t r;
  asm("add.rn.bf16x2 %0, %1, %2;" : "=r"(r) : "r"(a), "r"(b));
  return r;
}
__device__ __forceinline__ uint32_t bf_mul(uint32_t a, uint32_t b) {
  uint32_t r;
  asm("mul.rn.bf16x2 %0, %1, %2;" : "=r"(r) : "r"(a), "r"(b));
  return r;
}
__device__ __forceinline__ uint32_t bf_fma(uint32_t a, uint32_t b, uint32_t c) {
  uint32_t r;
  asm("fma.rn.bf16x2 %0, %1, %2, %3;" : "=r"(r) : "r"(a), "r"(b), "r"(c));
  return r;
}

__device__ __forceinline__ uint32_t h_add(uint32_t a, uint32_t b) {
  uint32_t r;
  asm("add.rn.f16x2 %0, %1, %2;" : "=r"(r) : "r"(a), "r"(b));
  return r;
}
__device__ __forceinline__ uint32_t h_mul(uint32_t a, uint32_t b) {
  uint32_t r;
  asm("mul.rn.f16x2 %0, %1, %2;" : "=r"(r) : "r"(a), "r"(b));
  return r;
}
__device__ __forceinline__ uint32_t h_fma(uint32_t a, uint32_t b, uint32_t c) {
  uint32_t r;
  asm("fma.rn.f16x2 %0, %1, %2, %3;" : "=r"(r) : "r"(a), "r"(b), "r"(c));
  return r;
}
__device__ __forceinline__ float h_sum(uint32_t v) {
  float lo, hi;
  asm("{\n.reg .b16 l, h;\nmov.b32 {l, h}, %2;\ncvt.f32.f16 %0, l;\ncvt.f32.f16 %1, h;\n}\n" : "=f"(lo), "=f"(hi) : "r"(v));
  return lo + hi;
}
__device__ __forceinline__ void lds128(uint32_t (&v)[4], uint32_t a) {
  asm volatile("ld.shared.v4.b32 {%0,%1,%2,%3}, [%4];" : "=r"(v[0]), "=r"(v[1]), "=r"(v[2]), "=r"(v[3]) : "r"(a) : "memory");
}

template <int LO, int HI>
__device__ __forceinline__ void gelu(uint32_t (&o)[24], const uint32_t (&d)[24]) {
#pragma unroll
  for (int qq = LO; qq < HI; qq++) {
    const int q = (qq + 4) % 24;
    uint32_t t, u;
    asm("fma.rn.f16x2 %0, %1, %1, %2;" : "=r"(t) : "r"(d[q]), "r"(GELU_K2));
    asm("mul.rn.f16x2 %0, %1, %2;" : "=r"(u) : "r"(d[q]), "r"(t));
    asm("tanh.approx.f16x2 %0, %1;" : "=r"(t) : "r"(u));
    asm("fma.rn.f16x2 %0, %1, %2, %1;" : "=r"(o[q]) : "r"(d[q]), "r"(t));
  }
}

__device__ __forceinline__ uint32_t laneid() {
  uint32_t l;
  asm volatile("mov.u32 %0, %%laneid;" : "=r"(l));
  return l;
}

__device__ __forceinline__ bool elect_one() {
  uint32_t p;
  asm volatile("{\n.reg .pred p;\nelect.sync _|p, 0xffffffff;\nselp.u32 %0, 1, 0, p;\n}\n" : "=r"(p));
  return p;
}

__device__ __forceinline__ uint32_t clock_pin() {
  uint32_t t;
  asm volatile("mov.u32 %0, %%clock;" : "=r"(t)::"memory");
  return t;
}

struct MlpCtx {
  uint32_t sb;
  uint32_t caddr;
  uint32_t xaddr;
  uint32_t unscale;
  uint32_t peer_off;
  int wg, warp, rank, zero;
  uint8_t* optr;
};

__device__ __forceinline__ void ln_wait(const MlpCtx& m, int i) { mbar_wait(m.sb + BAR_CFULL + 8 * m.wg, i & 1); }
__device__ __forceinline__ void ln_load(const MlpCtx& m, uint32_t (&c)[24]) {
#pragma unroll
  for (int p = 0; p < 6; p++)
    asm volatile("ld.shared.v4.b32 {%0,%1,%2,%3}, [%4];"
                 : "=r"(c[4 * p]), "=r"(c[4 * p + 1]), "=r"(c[4 * p + 2]), "=r"(c[4 * p + 3])
                 : "r"(m.caddr + p * 2048)
                 : "memory");
}
__device__ __forceinline__ void ln_shfl(float (&st)[8], int mask) {
#pragma unroll
  for (int k = 0; k < 4; k++) st[4 + k] = __shfl_xor_sync(0xffffffffu, st[k], mask);
}
__device__ __forceinline__ void ln_fold(float (&st)[8]) {
#pragma unroll
  for (int k = 0; k < 4; k++) st[k] += st[4 + k];
}
__device__ __forceinline__ void ln_sums(const uint32_t (&c)[24], float (&st)[8]) {
#pragma unroll
  for (int r = 0; r < 2; r++) {
    uint32_t s0 = h_add(c[r], c[r + 2]), s1 = h_add(c[r + 4], c[r + 6]), s2 = h_add(c[r + 8], c[r + 10]);
    uint32_t s3 = h_add(c[r + 12], c[r + 14]), s4 = h_add(c[r + 16], c[r + 18]), s5 = h_add(c[r + 20], c[r + 22]);
    s0 = h_add(s0, s1); s2 = h_add(s2, s3); s4 = h_add(s4, s5);
    st[r] = h_sum(h_add(h_add(s0, s2), s4));
    uint32_t q0 = h_mul(c[r], c[r]), q1 = h_mul(c[r + 2], c[r + 2]);
#pragma unroll
    for (int p = 2; p < 12; p += 2) {
      q0 = h_fma(c[2 * p + r], c[2 * p + r], q0);
      q1 = h_fma(c[2 * p + 2 + r], c[2 * p + 2 + r], q1);
    }
    st[2 + r] = h_sum(h_add(q0, q1));
  }
}
__device__ __forceinline__ void ln_release(const MlpCtx& m) {
  const uint32_t e = m.sb + BAR_CEMPTY + 8 * (2 * m.rank + m.wg);
  asm volatile(
      "{\n.reg .pred p, q;\nelect.sync _|p, 0xffffffff;\nsetp.eq.and.s32 q, %3, 0, p;\n"
      "@q mbarrier.arrive.expect_tx.shared::cta.b64 _, [%0], %4;\n"
      "@p mbarrier.arrive.shared::cluster.b64 _, [%1];\n"
      "@p mbarrier.arrive.shared::cluster.b64 _, [%2];\n}\n" ::"r"(m.sb + BAR_CFULL + 8 * m.wg),
      "r"(e), "r"(e + m.peer_off), "r"(m.warp), "n"(CTX)
      : "memory");
}
__device__ __forceinline__ bool ln_stats(float (&st)[8]) {
  bool ok = true;
#pragma unroll
  for (int r = 0; r < 2; r++) {
    const float nm = (st[r] + st[4 + r]) * (-1.0f / 96.0f);
    const float e2 = fmaf(st[2 + r] + st[6 + r], 1.0f / 96.0f, 1e-5f);
    float rs;
    asm("rsqrt.approx.ftz.f32 %0, %1;" : "=f"(rs) : "f"(fmaf(-nm, nm, e2)));
    ok = ok && (rs * rs * e2 <= 17.0f) && (e2 >= 1.001e-5f);
    const float rr = rs * GELU_A, dd = rr * nm;
    st[r] = __uint_as_float(pack_f16(rr, rr));
    st[2 + r] = __uint_as_float(pack_f16(dd, dd));
  }
  return ok;
}
__device__ __forceinline__ void mark_bad(uint32_t addr, uint32_t bits) {
  asm volatile("{\n.reg .pred p;\nelect.sync _|p, 0xffffffff;\n@p red.shared.or.b32 [%0], %1;\n}\n" ::"r"(addr), "r"(bits) : "memory");
  __syncwarp();
}
__device__ __forceinline__ void ln_restat(bool ok, const uint32_t (&c)[24], float (&st)[8], uint32_t bad, int i,
                                          uint32_t zero) {
  if (__builtin_expect(__any_sync(0xffffffffu, !ok), 0)) {
#pragma unroll
    for (int r = 0; r < 2; r++) {
      float nm = 0.f, var = 0.f;
#pragma unroll
      for (int p = 0; p < 12; p++) {
        nm += h_sum(c[2 * p + r] ^ zero);
        if (p % 3 == 2) { asm volatile("" : "+f"(nm)); PIN(); }
      }
      nm += __shfl_xor_sync(0xffffffffu, nm, 1);
      nm += __shfl_xor_sync(0xffffffffu, nm, 2);
      nm *= -1.0f / 96.0f;
#pragma unroll
      for (int p = 0; p < 12; p++) {
        float lo, hi;
        asm volatile("{\n.reg .b16 l, h;\nmov.b32 {l, h}, %2;\ncvt.f32.f16 %0, l;\ncvt.f32.f16 %1, h;\n}\n" : "=f"(lo), "=f"(hi) : "r"(c[2 * p + r]));
        var = fmaf(lo + nm, lo + nm, fmaf(hi + nm, hi + nm, var));
        if (p % 3 == 2) { asm volatile("" : "+f"(var)); PIN(); }
      }
      var += __shfl_xor_sync(0xffffffffu, var, 1);
      var += __shfl_xor_sync(0xffffffffu, var, 2);
      const float rr = rsqrtf(fmaf(var, 1.0f / 96.0f, 1e-5f)) * GELU_A;
      st[r] = __uint_as_float(pack_f16(rr, rr));
      const float dd = 0.5f * h_sum(__float_as_uint(st[r])) * nm;
      st[2 + r] = __uint_as_float(pack_f16(dd, dd));
      if (__any_sync(0xffffffffu, !(rr >= 0x1p-14f && fabsf(dd) <= 16.0f && var >= 1e-8f))) mark_bad(bad, 1u << i);
    }
  }
}
__device__ __forceinline__ void ln_apply(uint32_t (&a)[24], const uint32_t (&c)[24], const float (&st)[8]) {
#pragma unroll
  for (int p = 0; p < 24; p++) {
    a[p] = h_fma(c[p], __float_as_uint(st[p & 1]), __float_as_uint(st[2 + (p & 1)]));
  }
}

__device__ __noinline__ void slow_tile(const __nv_bfloat16* x, const __nv_bfloat16* dw, const __nv_bfloat16* w1,
                                       const __nv_bfloat16* w2, __nv_bfloat16* out, int row0, int col0, float* buf) {
  const int lane = threadIdx.x & 31;
  for (int px = 0; px < 16; px++) {
    const int row = row0 + (px >> 3), col = col0 + (px & 7);
    float c[3] = {0.f, 0.f, 0.f};
    for (int i = 0; i < 7; i++)
      for (int j = 0; j < 7; j++) {
        const int rr = row + i - 3, cc = col + j - 3;
        if (rr < 0 || rr >= IMG || cc < 0 || cc >= IMG) continue;
        for (int k = 0; k < 3; k++)
          c[k] = fmaf(__bfloat162float(x[((size_t)rr * IMG + cc) * CH + lane + 32 * k]), __bfloat162float(dw[(i * 7 + j) * CH + lane + 32 * k]), c[k]);
      }
    float mean = (c[0] + c[1] + c[2]) * (1.0f / 96.0f);
    for (int o = 16; o; o >>= 1) mean += __shfl_xor_sync(0xffffffffu, mean, o);
    float var = 0.f;
    for (int k = 0; k < 3; k++) { c[k] -= mean; var = fmaf(c[k] * (1.0f / 96.0f), c[k], var); }
    for (int o = 16; o; o >>= 1) var += __shfl_xor_sync(0xffffffffu, var, o);
    const float rs = 1.0f / sqrtf(var + 1e-5f);
    __syncwarp();
    for (int k = 0; k < 3; k++) buf[lane + 32 * k] = c[k] * rs;
    __syncwarp();
    for (int n = lane; n < 4 * CH; n += 32) {
      float y = 0.f;
      for (int k = 0; k < CH; k++) y = fmaf(buf[k], __bfloat162float(w1[k * 4 * CH + n]), y);
      buf[CH + n] = 0.5f * y * (1.0f + tanhf(0.7978845608f * (y + 0.044715f * y * y * y)));
    }
    __syncwarp();
    for (int n = lane; n < CH; n += 32) {
      float o = 0.f;
      for (int k = 0; k < 4 * CH; k++) o = fmaf(buf[CH + k], __bfloat162float(w2[k * CH + n]), o);
      const size_t idx = ((size_t)row * IMG + col) * CH + n;
      out[idx] = __float2bfloat16(__bfloat162float(x[idx]) + o);
    }
  }
}

__device__ __forceinline__ void x_load(const MlpCtx& m, uint32_t (&x)[24]) {
#pragma unroll
  for (int k = 0; k < 6; k++)
    asm volatile("ld.shared.v4.b32 {%0,%1,%2,%3}, [%4];"
                 : "=r"(x[4 * k]), "=r"(x[4 * k + 1]), "=r"(x[4 * k + 2]), "=r"(x[4 * k + 3])
                 : "r"(m.xaddr + (k / 3) * 384 + (k % 3) * 64)
                 : "memory");
}
template <bool DIRECT>
__device__ __forceinline__ void epilogue(const MlpCtx& m, const uint32_t (&d)[24], uint32_t (&x)[24]) {
  uint8_t* o = nullptr;
  if (DIRECT) {
    const uint32_t lane = laneid();
    o = m.optr + ((lane >> 3) & 1) * (IMG * CH * 2) + ((lane >> 4) * 4 + ((lane >> 2) & 1)) * 192 + (lane & 3) * 16;
  }
#pragma unroll
  for (int k = 0; k < 6; k++) {
    const int r = k / 3, q = k % 3;
    uint32_t* y = &x[4 * k];
#pragma unroll
    for (int j = 0; j < 4; j++) {
      uint32_t v = d[2 * (4 * q + j) + r];
      float lo, hi;
      asm("{\n.reg .b16 l, h;\nmov.b32 {l, h}, %2;\ncvt.f32.f16 %0, l;\ncvt.f32.f16 %1, h;\n}\n" : "=f"(lo), "=f"(hi) : "r"(v));
      asm("fma.rn.bf16x2 %0, %1, %2, %0;" : "+r"(y[j]) : "r"(pack_bf16(lo, hi)), "r"(m.unscale));
    }
    if (DIRECT)
      asm volatile("st.global.v4.b32 [%0], {%1,%2,%3,%4};" ::"l"(o + r * 384 + q * 64), "r"(y[0]), "r"(y[1]), "r"(y[2]), "r"(y[3]) : "memory");
    else
      asm volatile("st.shared.v4.b32 [%0], {%1,%2,%3,%4};" ::"r"(m.xaddr + r * 384 + q * 64), "r"(y[0]), "r"(y[1]), "r"(y[2]), "r"(y[3])
                   : "memory");
  }
}

#define FSET 3
template <int J> constexpr bool goes_first = J == FSET || J == ((FSET + 1) & 3);
template <int J> __device__ __forceinline__ void tok_wait() {
  if (goes_first<J>) NB_SYNC(NB_CLOSE, 256);
  else NB_SYNC(NB_SEC + (J & 1), 256);
}
template <int J, bool PROD = true> __device__ __forceinline__ void tok_next() {
  if (goes_first<J>) NB_ARRIVE(NB_SEC + (J & 1), 256);
  if (J == 0 && PROD) NB_ARRIVE(NB_PROD, 160);
}
__device__ __forceinline__ void tok_pass() { NB_ARRIVE(NB_OPEN, 448); }
template <int J> __device__ __forceinline__ void tok_idle() { tok_wait<J>(); tok_next<J, false>(); tok_pass(); }

constexpr uint64_t CHK = 1152;

__device__ __forceinline__ float warp_sumsq(const uint32_t (&q)[4]) {
  const uint32_t t = bf_add(bf_add(q[0], q[1]), bf_add(q[2], q[3]));
  float f = bf_lo(t) + bf_hi(t);
#pragma unroll
  for (int o = 16; o; o >>= 1) f += __shfl_xor_sync(0xffffffffu, f, o);
  return f;
}
__device__ __forceinline__ int norm_exp(float f) { return (((int)(__float_as_uint(f * 1.5f) >> 23) - 127) >> 1) + 1; }
__device__ __forceinline__ int scale_exp(int e1, int e2) { return min(11 - e1 - e2, 14 - e2); }

__device__ __forceinline__ void convert_tile(int t, int k, const uint4* w1, const uint4* w2, uint32_t st, Scratch* scr) {
  const int lane = threadIdx.x & 31, k7 = lane & 7;
  const int j = t / 6, ks = t % 6, e = ks % 3, t4 = k7 >> 1;
  const uint4* src = t < 24 ? w1 + ((e < 2 ? 64 * (ks / 3) + 8 * t4 + 4 * e : 32 + 16 * (ks / 3) + 4 * t4) + (k7 & 1)) * 48 + j * 12 + (lane >> 3)
                            : w2 + (t - 24) * 192 + (lane >> 2) * 12 + (lane & 3);
  src += (k / 3) * 96 + (k % 3) * 4;
  if (k >= 6) src = (k == 6 ? w1 : w2) + lane * 145;
  const uint4 v = __ldg(src);
  const uint32_t w[4] = {v.x, v.y, v.z, v.w};
  const uint32_t q[4] = {bf_mul(v.x, v.x), bf_mul(v.y, v.y), bf_mul(v.z, v.z), bf_mul(v.w, v.w)};
  asm volatile("st.shared.f32 [%0], %1;" ::"r"(st + 3088 + 4 * k), "f"(warp_sumsq(q)) : "memory");
  NB_SYNC(NB_PREP, 256);
  uint32_t a[4], b[4], o[4];
  lds128(a, st + 3088);
  lds128(b, st + 3104);
  const int s = max(-64, min(64, scale_exp(norm_exp(144.f * __uint_as_float(b[2])), norm_exp(144.f * __uint_as_float(b[3]))) - 3));
  const uint32_t dst = st + k7 * 16 + (lane >> 3) * 256 + (k / 3) * 128 + (k % 3) * 1024;
  if (k >= 6) {
    const float f = ((__uint_as_float(a[0]) + __uint_as_float(a[1])) + (__uint_as_float(a[2]) + __uint_as_float(a[3]))) +
                    (__uint_as_float(b[0]) + __uint_as_float(b[1]));
    asm volatile("st.shared.v2.b32 [%0], {%1,%2};" ::"r"(st + 3072), "r"(__float_as_uint(f)), "r"(s) : "memory");
  } else if (t < 24) {
#pragma unroll
    for (int i = 0; i < 4; i++) o[i] = pack_f16(bf_lo(w[i]), bf_hi(w[i]));
    asm volatile("st.shared.v4.b32 [%0], {%1,%2,%3,%4};" ::"r"(dst), "r"(o[0]), "r"(o[1]), "r"(o[2]), "r"(o[3]) : "memory");
  } else {
    constexpr float F = 0.5f / GELU_A, FHI = 1.515625f;
    const float p2 = __uint_as_float((uint32_t)(127 + s - 56) << 23);
    const uint32_t hi = pack_bf16(FHI * 0x1p-56f, FHI * 0x1p-56f), lo = pack_bf16((F - FHI) * 0x1p-56f, (F - FHI) * 0x1p-56f);
    const uint32_t pw = pack_bf16(p2, p2);
#pragma unroll
    for (int i = 0; i < 4; i++) {
      const uint32_t ws = bf_mul(w[i], pw), u = bf_fma(ws, hi, bf_mul(ws, lo));
      o[i] = (u & 0x7fff7fffu) * 7u + u;
    }
    asm volatile("stmatrix.sync.aligned.m8n8.x4.shared.b16 [%0], {%1,%2,%3,%4};" ::"r"(dst), "r"(o[0]), "r"(o[1]), "r"(o[2]), "r"(o[3])
                 : "memory");
  }
  asm volatile("fence.proxy.async.shared::cta;" ::: "memory");
  NB_SYNC(NB_PREP, 256);
  if (k == 0 && elect_one()) {
    asm volatile("cp.async.bulk.global.shared::cta.bulk_group [%0], [%1], 3072;" ::"l"(scr->w + t * 192), "r"(st) : "memory");
    asm volatile("cp.async.bulk.global.shared::cta.bulk_group [%0], [%1], 16;" ::"l"(scr->nrm + t), "r"(st + 3072) : "memory");
    asm volatile("cp.async.bulk.commit_group;" ::: "memory");
    asm volatile("cp.async.bulk.wait_group 0;" ::: "memory");
    asm volatile("red.relaxed.gpu.global.add.u32 [%0], 1;" ::"l"(&scr->done) : "memory");
  }
}

__device__ __forceinline__ void check_weights(uint32_t sb) {
  const int lane = threadIdx.x & 31;
  float n1, n2;
  int s;
  mbar_wait(sb + BAR_W, 0);
  asm volatile("ld.shared.b32 %0, [%1];" : "=r"(s) : "r"(sb + OFF_NRM + 4) : "memory");
  asm volatile("ld.shared.f32 %0, [%1];" : "=f"(n1) : "r"(sb + OFF_NRM + 16 * min(lane, 23)) : "memory");
  asm volatile("ld.shared.f32 %0, [%1];" : "=f"(n2) : "r"(sb + OFF_NRM + 384 + 16 * min(lane, 23)) : "memory");
  if (lane >= 24) n1 = n2 = 0.f;
#pragma unroll
  for (int o = 16; o; o >>= 1) {
    n1 += __shfl_xor_sync(0xffffffffu, n1, o);
    n2 += __shfl_xor_sync(0xffffffffu, n2, o);
  }
  const int e1 = norm_exp(n1), e2 = norm_exp(n2), smax = scale_exp(e1, e2);
  if (e1 > 12 || e1 < -5 || e2 > 50 || e2 < -50 || s > smax || s < smax - 7 || (sb & 0x3FFFF) != 1024)
    asm volatile("red.shared.or.b32 [%0], 0xffff;" ::"r"(sb + OFF_BAD + 4 * (lane & 7)) : "memory");
  __syncwarp();
  if (elect_one()) asm volatile("mbarrier.arrive.shared::cta.b64 _, [%0];" ::"r"(sb + BAR_W + 8) : "memory");
}

__device__ __forceinline__ uint32_t mlp_role(const MlpCtx& m0) {
  MlpCtx m = m0;
  const uint32_t bad = m.sb + OFF_BAD + 4 * (4 * m.wg + m.warp);
  asm volatile("barrier.cluster.wait.aligned;" ::: "memory");
  constexpr uint64_t dW1 = (uint64_t)((1024 + OFF_W1) >> 4) | ((uint64_t)8 << 16) | ((uint64_t)16 << 32);
  constexpr uint64_t dW2 = dW1 + (OFF_W2 >> 4);
  uint32_t A1[24], g[24], d[24], cn[24], D2[24];
  float st[8];
  uint32_t mask;
  if (m.wg & m.rank) tok_idle<3>();
  else if (m.wg) tok_idle<0>();
  else if (m.rank) tok_idle<1>();
  ln_wait(m, 0);
  ln_load(m, cn);
  ln_sums(cn, st);
  ln_shfl(st, 1);
  ln_release(m);
  ln_fold(st);
  ln_shfl(st, 2);
  ln_restat(ln_stats(st), cn, st, bad, 0, m.zero);
  ln_apply(A1, cn, st);
  mbar_wait(m.sb + BAR_W, 0);
  asm volatile("ld.shared.b32 %0, [%1];" : "=r"(m.unscale) : "r"(m.sb + OFF_NRM + 4) : "memory");
  m.unscale = ((127 - m.unscale) << 7) * 0x10001u;
  if (m.wg & m.rank) tok_idle<0>();
  if (m.wg) tok_idle<1>();
  {
    uint32_t d0[24];
    WG_FENCE();
    tok_wait<2>();
    tok_next<2>();
    gemm6<true, 192>(d0, A1, dW1);
    tok_pass(); PIN();
    WG_WAIT0(); rfence(d0);
    WG_FENCE();
    tok_wait<3>();
    tok_next<3>();
    gemm6<true, 192>(d, A1, dW1 + CHK);
    tok_pass(); PIN();
    gelu<0, 24>(g, d0);
    PIN();
    mbar_wait(m.sb + BAR_W + 8, 0);
    ln_wait(m, 1);
    WG_WAIT0(); rfence(d);
  }
#define G2(INIT, a, j)                      \
  WG_FENCE();                               \
  tok_wait<j>();                            \
  gemm6<INIT, 192>(D2, a, dW2 + (j) * CHK); \
  tok_next<j>(); PIN();
#define G1(dst, j, P)                       \
  P(); WG_WAIT0(); rfence(D2);              \
  WG_FENCE();                               \
  gemm6<true, 192>(dst, A1, dW1 + (j) * CHK); \
  tok_pass(); P();
#define ROUND_END(dst, j)                   \
  PIN(); WG_WAIT0(); rfence(dst);
#define GA 11
#define GB 13
#define GC 13
#define GD 11
#pragma unroll 1
  for (int i = 0;; i++) {
    uint32_t g1[24], d2[24], g2[24], d3[24], g3[24], d0[24];
    ln_load(m, cn);
    PIN();
    G2(true, g, 0)
    gelu<0, GA>(g1, d);
    G1(d2, 2, PIN)
    ln_sums(cn, st);
    gelu<GA, 24>(g1, d);
    PIN();
    ln_shfl(st, 1);
    ROUND_END(d2, 0)

    G2(false, g1, 1)
    ln_fold(st);
    gelu<0, GB>(g2, d2);
    PIN();
    ln_shfl(st, 2);
    G1(d3, 3, PIN)
    const bool ok = ln_stats(st);
    gelu<GB, 24>(g2, d2);
    PIN();
    ln_restat(ok, cn, st, bad, i + 1, m.zero);
    ROUND_END(d3, 1)

    if (i == 15) {
      G2(false, g2, 2)
      tok_pass();
      gelu<0, 16>(g3, d3);
      PIN();
      x_load(m, cn);
      asm volatile("ld.shared.b32 %0, [%1];" : "=r"(mask) : "r"(bad) : "memory");
      ROUND_END(D2, 2)
      WG_FENCE();
      tok_wait<3>();
#pragma unroll
      for (int k = 1; k < 5; k++) wg_acc(D2, &g3[4 * k], dW2 + 3 * CHK + k * 192);
      WG_COMMIT();
      tok_next<3>();
      tok_pass();
      PIN();
      gelu<16, 24>(g3, d3);
      ROUND_END(D2, 2)
      WG_FENCE();
      wg_acc(D2, &g3[20], dW2 + 3 * CHK + 5 * 192);
      wg_acc(D2, &g3[0], dW2 + 3 * CHK);
      WG_COMMIT();
      WG_WAIT0(); rfence(D2);
      epilogue<true>(m, D2, cn);
      break;
    }
    G2(false, g2, 2)
    ln_apply(A1, cn, st);
    PIN();
    gelu<0, GC>(g3, d3);
    G1(d0, 0, PIN)
    gelu<GC, 24>(g3, d3);
    PIN();
    x_load(m, cn);
    ROUND_END(d0, 2)

    G2(false, g3, 3)
    gelu<0, GD>(g, d0);
    G1(d, 1, PIN)
    epilogue<false>(m, D2, cn);
    gelu<GD, 24>(g, d0);
    PIN();
    asm volatile("fence.proxy.async.shared::cta;" ::: "memory");
    ROUND_END(d, 3)
  }
  if (m.wg == 0) { tok_idle<0>(); tok_idle<1>(); }
  return __reduce_or_sync(0xffffffffu, mask & 0xffffu);
}

struct ConvCtx {
  uint32_t sb;
  uint32_t a0, a_c;
  uint32_t peer_off;
  int rank, v, c0, r0, dir, zero;
  const CUtensorMap* tm;
  Scratch* scr;
  const uint8_t* xsrc;
  uint8_t* optr;
};

__device__ __forceinline__ void raw_refill(const ConvCtx& c, int s) {
  if (s + 4 < NSTEP && elect_one())
    tma_raw(c.sb + OFF_RAW + (s & 3) * RAW_BYTES, c.tm, c.rank, c.c0 / 2 - 2, c.r0 + c.dir * (2 * s + 5), c.sb + BAR_RAW + 8 * (s & 3));
}
__device__ __forceinline__ void step_ready(const ConvCtx& c, int s) {
  const int nx = (s + 1) & 3, par = ((s + 1) >> 2) & 1;
  if (s + 1 < NSTEP) mbar_wait(c.sb + BAR_RAW + 8 * nx, par);
  if (s >= 7 && s < NSTEP) mbar_wait(c.sb + BAR_CEMPTY + 8 * (2 * (nx & 1) + (nx >> 1)), par);
}

__device__ __forceinline__ void c_release(const ConvCtx& c, uint32_t w) {
  const uint32_t e = c.sb + BAR_CEMPTY + 8 * (2 * c.rank + w);
  asm volatile(
      "{\n.reg .pred p;\nelect.sync _|p, 0xffffffff;\n"
      "@p mbarrier.arrive.expect_tx.shared::cta.b64 _, [%0], %3;\n"
      "@p mbarrier.arrive.shared::cluster.b64 _, [%1], 4;\n"
      "@p mbarrier.arrive.shared::cluster.b64 _, [%2], 4;\n}\n" ::"r"(c.sb + BAR_CFULL + 8 * w),
      "r"(e), "r"(e + c.peer_off), "n"(CTX)
      : "memory");
}

__device__ __forceinline__ void prod_rows(const ConvCtx& c) {
#pragma unroll 1
  for (int s = 0; s < NROUND + SIGMA + c.rank; s++) {
    if (s < SIGMA) NB_SYNC(NB_PLAN, 192);
    else NB_SYNC(NB_OPEN, 448);
    raw_refill(c, s);
  }
}
__device__ __forceinline__ void prod_checks(const ConvCtx& c) {
  asm volatile("barrier.cluster.wait.aligned;" ::: "memory");
#pragma unroll 1
  for (int s = 0; s < NROUND + SIGMA + c.rank; s++) {
    const int r = s - SIGMA - c.rank;
    const int u = (r & 1) ? (r >> 1) - 1 : (r >> 1) + 2;
    step_ready(c, s);
    if (s < 16) TP(c.scr, 100 + s);
    if (u >= ((r & 1) ? 0 : 4) && u < 32) mbar_wait(c.sb + ((r & 1) ? BAR_XFULL : BAR_CFULL) + 8 * (u & 1), (u >> 1) & 1);
    if (s < SIGMA) NB_SYNC(NB_PLAN, 192);
    else NB_SYNC(NB_OPEN, 448);
    TP(c.scr, s);
    if (r == 3) TC(c.scr, 1);
    if (r == 55) TC(c.scr, 2);
  }
}
__device__ __forceinline__ void prod_tiles(const ConvCtx& c) {
  asm volatile("barrier.cluster.wait.aligned;" ::: "memory");
#pragma unroll 1
  for (int n = 1; n < 33; n++) {
    const uint32_t w = (n + 1) & 1;
    const uint32_t buf = c.sb + OFF_XRES + w * 12288;
    NB_SYNC(NB_PROD, 160);
    if (n < 29) c_release(c, w);
    if (n >= 3) {
      uint8_t* dst = c.optr + (n - 3) * c.dir * (4 * IMG * CH * 2);
      if (elect_one()) {
        asm volatile("cp.async.bulk.global.shared::cta.bulk_group [%0], [%1], 6144;" ::"l"(dst), "r"(buf) : "memory");
        asm volatile("cp.async.bulk.global.shared::cta.bulk_group [%0], [%1], 6144;" ::"l"(dst + IMG * CH * 2), "r"(buf + 6144) : "memory");
        asm volatile("cp.async.bulk.commit_group;" ::: "memory");
        asm volatile("cp.async.bulk.wait_group.read 0;" ::: "memory");
      }
      __syncwarp();
    }
    {
      const uint8_t* src = c.xsrc + (n - 1) * c.dir * (4 * IMG * CH * 2);
      if (elect_one()) {
        mbar_expect(c.sb + BAR_XFULL + 8 * w, 12288);
        bulk_load_last(buf, src, 6144, c.sb + BAR_XFULL + 8 * w);
        bulk_load_last(buf + 6144, src + IMG * CH * 2, 6144, c.sb + BAR_XFULL + 8 * w);
      }
    }
  }
  asm volatile("cp.async.bulk.wait_group 0;" ::: "memory");
}

template <int LO, int HI>
__device__ __forceinline__ void conv_ld8(uint32_t a0, uint32_t (&r)[6][6]) {
  const uint32_t a2 = a0 ^ (16 | ((a0 >> 2) & 32));
  const uint32_t a[3] = {a0, (a0 & 64) ? a2 : a0, a2};
#pragma unroll
  for (int j = LO; j < HI; j++)
    asm volatile("ld.shared.v4.b32 {%0,%1,%2,%3}, [%4];"
                 : "=r"(r[j][0]), "=r"(r[j][1]), "=r"(r[j][2]), "=r"(r[j][3])
                 : "r"(a[j >> 1] + (j >> 1) * 64 + (j & 1) * RAW_PA)
                 : "memory");
}
__device__ __forceinline__ void conv_ld4(uint32_t a0, uint32_t stage, int v, uint32_t (&r)[6][6]) {
  const uint32_t ab = ((a0 >> 1) & ~31u) + (stage / 2 + 2 * RAW_PA + 8 * v);
#pragma unroll
  for (int j = 0; j < 6; j++) {
    uint32_t a = ab + (j >> 1) * 32;
    asm volatile("ld.shared.v2.b32 {%0,%1}, [%2];" : "=r"(r[j][4]), "=r"(r[j][5]) : "r"(a + (j & 1) * RAW_PB) : "memory");
  }
}
template <int LO, int HI>
__device__ __forceinline__ void conv_frags(uint32_t zero, const uint32_t (&r)[6][6], uint32_t (&A)[12][4]) {
#pragma unroll
  for (int ch = LO; ch < HI; ch++) {
    const uint32_t sel = (ch & 1) ? 0x7632 : 0x5410;
    A[ch][0] = __byte_perm(r[0][ch >> 1], r[1][ch >> 1], sel);
    A[ch][1] = __byte_perm(r[2][ch >> 1], r[3][ch >> 1], sel);
    A[ch][2] = A[ch][1] ^ zero;
    A[ch][3] = __byte_perm(r[4][ch >> 1], r[5][ch >> 1], sel);
    rfence(A[ch]);
  }
}
__device__ __forceinline__ void hmma_acc(uint32_t (&v)[4], const uint32_t (&a)[4], const uint32_t* b) {
  asm volatile("mma.sync.aligned.m16n8k16.row.col.f32.bf16.bf16.f32 {%0,%1,%2,%3}, {%4,%5,%6,%7}, {%8,%9}, {%0,%1,%2,%3};"
               : "+r"(v[0]), "+r"(v[1]), "+r"(v[2]), "+r"(v[3])
               : "r"(a[0]), "r"(a[1]), "r"(a[2]), "r"(a[3]), "r"(b[0]), "r"(b[1]));
}
__device__ __forceinline__ void hmma_new(uint32_t (&a)[4], const uint32_t* b) {
  asm volatile("mma.sync.aligned.m16n8k16.row.col.f32.bf16.bf16.f32 {%0,%1,%2,%3}, {%0,%1,%2,%3}, {%4,%5}, {%6,%6,%6,%6};"
               : "+r"(a[0]), "+r"(a[1]), "+r"(a[2]), "+r"(a[3])
               : "r"(b[0]), "r"(b[1]), "f"(0.f));
}

#define EARLY 6
__device__ __forceinline__ void conv_send(bool local, const uint32_t (&pk)[12], uint32_t dst, uint32_t bar) {
  if (local) {
#pragma unroll
    for (int q = 0; q < 3; q++)
      asm volatile("st.shared.v4.b32 [%0], {%1,%2,%3,%4};" ::"r"(dst + q * 2048), "r"(pk[4 * q]), "r"(pk[4 * q + 1]), "r"(pk[4 * q + 2]), "r"(pk[4 * q + 3])
                   : "memory");
    asm volatile("{\n.reg .pred p;\nelect.sync _|p, 0xffffffff;\n@p mbarrier.arrive.shared::cta.b64 _, [%0];\n}\n" ::"r"(bar) : "memory");
  } else {
#pragma unroll
    for (int q = 0; q < 3; q++)
      asm volatile("st.async.weak.shared::cluster.mbarrier::complete_tx::bytes.v4.b32 [%0], {%1,%2,%3,%4}, [%5];" ::"r"(dst + q * 2048),
                   "r"(pk[4 * q]), "r"(pk[4 * q + 1]), "r"(pk[4 * q + 2]), "r"(pk[4 * q + 3]), "r"(bar)
                   : "memory");
  }
}
template <int S2, bool GATED>
__device__ __forceinline__ void conv_step(const ConvCtx& c, int s, uint32_t (&K)[12], uint32_t (&V)[12][4], const uint32_t (&B)[12][4],
                                          uint32_t (&A)[12][4]) {
  const int nx = ((s + 1) & 2) | (S2 ^ 1);
  uint32_t r[6][6], pk[12];
  const uint32_t a0 = c.a0 + nx * RAW_BYTES;
  if (GATED) NB_SYNC(NB_OPEN, 448);
  else NB_SYNC(NB_PLAN, 192);
  conv_ld4(a0, c.sb + OFF_RAW + nx * RAW_BYTES, c.v, r);
  if (GATED) PIN();
#pragma unroll
  for (int ch = 0; ch < 12; ch++) hmma_acc(V[11 - ch], A[11 - ch], &B[11 - ch][2]);
#pragma unroll
  for (int ch = 0; ch < 12 - EARLY; ch++) hmma_new(A[ch], &B[ch][0]);
  const uint32_t zero = GATED ? c.zero & clock_pin() : c.zero;
  if (GATED) NB_ARRIVE(NB_CLOSE, 256);
#pragma unroll
  for (int ch = 12 - EARLY; ch < 12; ch++) hmma_new(A[ch], &B[ch][0]);
  if (GATED) PIN();
  const bool local = (S2 ^ 1) == c.rank;
  const uint32_t off = local ? 0u : c.peer_off;
  const uint32_t dst = c.a_c + off + (nx >> 1) * C_BYTES;
  const uint32_t bar = c.sb + off + BAR_CFULL + 8 * (nx >> 1);
#pragma unroll
  for (int q = 0; q < 12; q++) {
    const int ch = q & ~1, h = 2 * (q & 1);
    pk[q] = h_add(K[q], pack_f16(__uint_as_float(V[ch][h + 1]), __uint_as_float(V[ch + 1][h])));
  }
#pragma unroll
  for (int q = 0; q < 12; q++) {
    const int ch = q & ~1, h = 2 * (q & 1);
    K[q] = pack_f16(__uint_as_float(V[ch][h]), __uint_as_float(V[ch + 1][h + 1]));
  }
  rfence(K);
  rfence(pk);
  PIN();
  conv_ld8<0, 4>(a0, r);
  if (GATED || s >= 3) conv_send(local, pk, dst, bar);
  conv_frags<8, 12>(zero, r, V);
  PIN();
  conv_ld8<4, 6>(a0, r);
  conv_frags<0, 8>(zero, r, V);
  PIN();
}

__device__ __forceinline__ void conv_role(ConvCtx c) {
  const int lane = laneid(), g = lane >> 2, t = lane & 3;
  const int u = (t >> 1) * 19 + 2 * (g + (t & 1));
  c.a0 = c.sb + OFF_RAW + u * 64 + ((c.v ^ (u >> 1)) & 3) * 16;
  c.a_c = c.sb + OFF_C + 6144 * c.rank + 512 * c.v + ((lane + 2 * c.v) & 31) * 16;
  uint32_t B[12][4];
  {
    const int dc = (g >> 1) & 1, ro = g >> 2, rk = t >> 1;
    const int i0 = (c.dir > 0 ? 4 * (g & 1) : 6 - 4 * (g & 1)) + rk - ro, j0 = 4 * (t & 1) - dc;
    const uint32_t base = c.sb + OFF_XRES + (i0 * 7 + j0) * 192;
    NB_SYNC(NB_INIT, 160);
    mbar_wait(c.sb + BAR_W + 48, 0);
#pragma unroll
    for (int b = 0; b < 2; b++) {
      uint32_t w[4][6];
#pragma unroll
      for (int k = 0; k < 4; k++) {
        const int ok = (unsigned)(i0 + 2 * b * c.dir) < 7u && (unsigned)(j0 + k) < 7u;
#pragma unroll
        for (int q = 0; q < 6; q++) w[k][q] = 0;
        asm volatile(
            "{\n.reg .pred p;\nsetp.ne.s32 p, %8, 0;\n@p ld.shared.v4.b32 {%0,%1,%2,%3}, [%6];\n@p ld.shared.v2.b32 {%4,%5}, [%7];\n}\n"
            : "+r"(w[k][0]), "+r"(w[k][1]), "+r"(w[k][2]), "+r"(w[k][3]), "+r"(w[k][4]), "+r"(w[k][5])
            : "r"(base + (b * 14 * c.dir + k) * 192 + 128 * c.rank + 16 * c.v), "r"(base + (b * 14 * c.dir + k) * 192 + 64 + 32 * c.rank + 8 * c.v), "r"(ok)
            : "memory");
      }
#pragma unroll
      for (int q = 0; q < 6; q++) {
        B[2 * q][2 * b] = __byte_perm(w[0][q], w[1][q], 0x5410);
        B[2 * q][2 * b + 1] = __byte_perm(w[2][q], w[3][q], 0x5410);
        B[2 * q + 1][2 * b] = __shfl_xor_sync(0xffffffffu, __byte_perm(w[0][q], w[1][q], 0x7632), 4);
        B[2 * q + 1][2 * b + 1] = __shfl_xor_sync(0xffffffffu, __byte_perm(w[2][q], w[3][q], 0x7632), 4);
      }
    }
  }
  uint32_t K1[12], K2[12], V[12][4];
#pragma unroll
  for (int ch = 0; ch < 12; ch++)
    asm volatile("" : "=r"(K1[ch]), "=r"(K2[ch]), "=r"(V[ch][0]), "=r"(V[ch][1]), "=r"(V[ch][2]), "=r"(V[ch][3]));
  uint32_t A[12][4], r[6][6];
  mbar_wait(c.sb + BAR_RAW, 0);
  conv_ld8<0, 6>(c.a0, r);
  conv_ld4(c.a0, c.sb + OFF_RAW, c.v, r);
  conv_frags<0, 12>(c.zero, r, A);
  PIN();
  asm volatile("barrier.cluster.wait.aligned;" ::: "memory");
  NB_ARRIVE(NB_CLOSE, 256);
#pragma unroll 1
  for (int s = 0; s < SIGMA; s += 2) {
    conv_step<0, false>(c, s, K1, V, B, A);
    conv_step<1, false>(c, s + 1, K2, A, B, V);
  }
#pragma unroll 1
  for (int s = SIGMA;; s += 2) {
    conv_step<0, true>(c, s, K1, V, B, A);
    if (s == NSTEP - 1) break;
    conv_step<1, true>(c, s + 1, K2, A, B, V);
  }
#pragma unroll 1
  for (int r = NSTEP - SIGMA - c.rank; r < NROUND - 1; r++) {
    NB_SYNC(NB_OPEN, 448);
    NB_ARRIVE(NB_CLOSE, 256);
  }
  NB_SYNC(NB_OPEN, 448);
}

struct TMaps { CUtensorMap m[2]; };

__global__ void __cluster_dims__(2, 1, 1) __launch_bounds__(512, 1)
convnext_kernel(const __grid_constant__ TMaps tms, const __nv_bfloat16* __restrict__ x, const __nv_bfloat16* __restrict__ dw,
                const __nv_bfloat16* __restrict__ w1, const __nv_bfloat16* __restrict__ w2, __nv_bfloat16* __restrict__ out,
                Scratch* scr, int zero) {
  extern __shared__ __align__(1024) uint8_t smem[];
  const uint32_t sb = (uint32_t)__cvta_generic_to_shared(smem);
  const int tid = threadIdx.x, lane = tid & 31;
  const int wid = __shfl_sync(0xffffffffu, tid >> 5, 0);
  const int rank = blockIdx.x & 1, cl = blockIdx.x >> 1;
  const int dir = (cl & 16) ? 1 : -1;
  const int c0 = (cl & 15) * 32, r0 = (cl >> 4) * 128 + (dir > 0 ? 0 : 126);
  const uint32_t peer_off = mapa(sb, rank ^ 1) - sb;

  if (wid == 12 && elect_one()) {
    mbar_init(sb + BAR_W + 48, 1);
#pragma unroll
    for (int i = 0; i < 4; i++) mbar_init(sb + BAR_RAW + 8 * i, 1);
    asm volatile("fence.mbarrier_init.release.cluster;" ::: "memory");
    mbar_expect(sb + BAR_W + 48, 49 * CH * 2);
    bulk_load(sb + OFF_XRES, dw, 49 * CH * 2, sb + BAR_W + 48);
#pragma unroll
    for (int i = 0; i < E0; i++) tma_raw(sb + OFF_RAW + i * RAW_BYTES, tms.m, rank, c0 / 2 - 2, r0 + dir * (2 * i - 3), sb + BAR_RAW + 8 * i);
  }
  ConvCtx c;
  c.sb = sb; c.rank = rank; c.v = wid - 8; c.c0 = c0; c.r0 = r0; c.dir = dir; c.zero = zero; c.tm = tms.m; c.scr = scr;
  c.peer_off = peer_off;
  c.xsrc = reinterpret_cast<const uint8_t*>(x) + ((size_t)(r0 + 2 * dir * rank) * IMG + c0) * (CH * 2);
  c.optr = reinterpret_cast<uint8_t*>(out) + ((size_t)(r0 + 2 * dir * rank) * IMG + c0) * (CH * 2);
  if ((wid >> 2) == 2) {
    asm volatile("barrier.cluster.arrive.relaxed.aligned;" ::: "memory");
    asm volatile("setmaxnreg.inc.sync.aligned.u32 %0;" ::"n"(REG_CONV));
    conv_role(c);
  } else if (wid >= 12) {
    asm volatile("setmaxnreg.dec.sync.aligned.u32 24;");
    if (wid == 12) NB_ARRIVE(NB_INIT, 160);
    if (wid == 14 && elect_one()) {
      asm volatile("cp.async.bulk.prefetch.L2.global [%0], 1152;" ::"l"(reinterpret_cast<const uint8_t*>(rank ? w2 : w1) + cl * 1152) : "memory");
      asm volatile("prefetch.tensormap [%0];" ::"l"(&tms.m[1]) : "memory");
#pragma unroll
      for (int i = 0; i < 3; i++) mbar_init(sb + BAR_W + 8 * i, i == 1 ? 2 : 1);
#pragma unroll
      for (int i = 0; i < 2; i++) mbar_init(sb + BAR_CFULL + 8 * i, CCNT);
#pragma unroll
      for (int i = 0; i < 4; i++) mbar_init(sb + BAR_CEMPTY + 8 * i, 4);
#pragma unroll
      for (int i = 0; i < 2; i++) mbar_init(sb + BAR_XFULL + 8 * i, 1);
#pragma unroll
      for (int i = 0; i < 2; i++) mbar_expect(sb + BAR_CFULL + 8 * i, CTX);
#pragma unroll
      for (int i = 0; i < 2; i++) asm volatile("st.shared.v4.b32 [%0], {0, 0, 0, 0};" ::"r"(sb + OFF_BAD + 16 * i) : "memory");
      asm volatile("fence.mbarrier_init.release.cluster;" ::: "memory");
    }
    __syncwarp();
    asm volatile("barrier.cluster.arrive.relaxed.aligned;" ::: "memory");
    if (wid == 15) TC(scr, 0);
    if (wid == 12) {
#pragma unroll 1
      for (int h = E0 - 4; h < 0; h++) raw_refill(c, h);
      prod_rows(c);
    } else if (wid == 15) {
      prod_checks(c);
    } else if (wid == 14) {
#pragma unroll 1
      for (int n = 0; n < (1 << 20); n++) {
        unsigned v;
        __nanosleep(n ? PSL : PS0);
        asm volatile("ld.acquire.gpu.global.u32 %0, [%1];" : "=r"(v) : "l"(&scr->done) : "memory");
        if (__shfl_sync(0xffffffffu, v, 0) >= 48) break;
      }
      TP(scr, 90);
      asm volatile("barrier.cluster.wait.aligned;" ::: "memory");
      asm volatile("fence.proxy.async.global;" ::: "memory");
      if (elect_one()) {
        mbar_expect(sb + BAR_W, 36864 + 768);
        mbar_expect(sb + BAR_W + 8, 110592);
        bulk_load(sb + OFF_NRM, scr->nrm, 768, sb + BAR_W);
      }
      __syncwarp();
#pragma unroll 1
      for (int i = 0; i < 8; i++) {
        if (elect_one()) bulk_load(sb + i * 18432, reinterpret_cast<const uint8_t*>(scr->w) + i * 18432, 18432, sb + BAR_W + (i < 2 ? 0 : 8));
        if (i >= PFIRST) __nanosleep(PACE);
      }
      check_weights(sb);
      if (elect_one() && atomicAdd(&scr->seen, 1u) == gridDim.x - 1) { scr->done = 0; scr->seen = 0; }
    } else if (wid == 13) {
      prod_tiles(c);
      __syncwarp();
      if (elect_one()) asm volatile("mbarrier.arrive.shared::cta.b64 _, [%0];" ::"r"(sb + BAR_W + 16) : "memory");
    }
  } else {
    asm volatile("barrier.cluster.arrive.relaxed.aligned;" ::: "memory");
    if (blockIdx.x < 48) convert_tile(blockIdx.x, wid, reinterpret_cast<const uint4*>(w1), reinterpret_cast<const uint4*>(w2), sb, scr);
    MlpCtx m;
    m.sb = sb; m.wg = wid >> 2; m.warp = wid & 3; m.rank = rank; m.peer_off = peer_off; m.zero = zero;
    m.optr = reinterpret_cast<uint8_t*>(out) + ((size_t)(r0 + dir * (120 + 4 * m.wg + 2 * rank)) * IMG + c0 + 8 * m.warp) * (CH * 2);
    m.caddr = sb + OFF_C + m.wg * C_BYTES + (lane & 3) * 512 + ((m.warp * 8 + (lane >> 2) + 2 * (lane & 3)) & 31) * 16;
    m.xaddr = sb + OFF_XRES + m.wg * 12288 + m.warp * 1536 + ((lane >> 3) & 1) * 6144 + ((lane >> 4) * 4 + ((lane >> 2) & 1)) * 192 + (lane & 3) * 16;
    m.unscale = 0;
    asm volatile("setmaxnreg.inc.sync.aligned.u32 %0;" ::"n"(REG_MLP));
    const uint32_t bad = mlp_role(m);
    TC(scr, 3);
    if (bad) {
      mbar_wait(sb + BAR_W + 16, 0);
      __syncwarp();
      asm volatile("fence.proxy.async;" ::: "memory");
#pragma unroll 1
      for (int i = 0; i < 16; i++)
        if (bad >> i & 1)
          slow_tile(x, dw, w1, w2, out, r0 + dir * (8 * i + 4 * m.wg + 2 * rank), c0 + 8 * m.warp,
                    reinterpret_cast<float*>(smem + OFF_RAW + wid * 2048));
    }
  }
}

typedef CUresult (*EncodeFn)(CUtensorMap*, CUtensorMapDataType, cuuint32_t, void*, const cuuint64_t*, const cuuint64_t*,
                             const cuuint32_t*, const cuuint32_t*, CUtensorMapInterleave, CUtensorMapSwizzle,
                             CUtensorMapL2promotion, CUtensorMapFloatOOBfill);

}

extern "C" void kernel_launch(void* const* d_in, const int* in_sizes, int n_in, void* d_out, int out_size) {
  const __nv_bfloat16* x = (const __nv_bfloat16*)d_in[0];
  const __nv_bfloat16* dw = (const __nv_bfloat16*)d_in[1];
  const __nv_bfloat16* w1 = (const __nv_bfloat16*)d_in[2];
  const __nv_bfloat16* w2 = (const __nv_bfloat16*)d_in[3];
  __nv_bfloat16* out = (__nv_bfloat16*)d_out;

  static EncodeFn encode = nullptr;
  static Scratch* scr = nullptr;
  if (!encode) {
    cudaDriverEntryPointQueryResult st;
    void* fn = nullptr;
    cudaGetDriverEntryPoint("cuTensorMapEncodeTiled", &fn, cudaEnableDefault, &st);
    encode = (EncodeFn)fn;
    cudaGetSymbolAddress((void**)&scr, g_scratch);
    cudaFuncSetAttribute(convnext_kernel, cudaFuncAttributeMaxDynamicSharedMemorySize, SMEM_BYTES);
  }
  TMaps tm;
  cuuint64_t dims[4] = {CH, IMG / 2, IMG, 2};
  cuuint64_t strides[3] = {CH * 4, (cuuint64_t)IMG * CH * 2, CH * 2};
  cuuint32_t es[4] = {1, 1, 1, 1};
  for (int i = 0; i < 2; i++) {
    cuuint32_t box[4] = {i ? 16u : 32u, 19, 2, 1};
    encode(&tm.m[i], CU_TENSOR_MAP_DATA_TYPE_BFLOAT16, 4, (void*)x, dims, strides, box, es, CU_TENSOR_MAP_INTERLEAVE_NONE,
           i ? CU_TENSOR_MAP_SWIZZLE_NONE : CU_TENSOR_MAP_SWIZZLE_64B, PROMO, CU_TENSOR_MAP_FLOAT_OOB_FILL_NONE);
  }
  convnext_kernel<<<128, 512, SMEM_BYTES>>>(tm, x, dw, w1, w2, out, scr, 0);
}
```
